```python
import torch

def _softmax(x, axis=-1):
    return torch.softmax(x, dim=axis)

def _gelu(x):
    return torch.nn.functional.gelu(x, approximate='tanh')

def _silu(x):
    return torch.nn.functional.silu(x)

def _sigmoid(x):
    return torch.sigmoid(x)

def _layernorm(x, axis=-1, eps=1e-05):
    m = x.mean(dim=axis, keepdim=True)
    v = x.var(dim=axis, keepdim=True, unbiased=False)
    return (x - m) / torch.sqrt(v + eps)

def _scatter_add(tgt, idx, src, axis=0):
    return tgt.clone().index_add_(axis, idx, src)

def _segment_sum(src, seg, n):
    out = torch.zeros((n,) + src.shape[1:], dtype=src.dtype)
    return out.index_add_(0, seg, src)

def _pad(x, pw):
    flat = tuple((v for pair in reversed(pw) for v in pair))
    return torch.nn.functional.pad(x, flat)
kernel_name = 'parallel_sum__memory_aug_recurrent_mem_tr__moe_arch_mod__prompt'

def setup_inputs():

    _w = lambda a: (lambda t: t.to(torch.bfloat16) if t.is_floating_point() else t)(torch.as_tensor(a))

    def _A_setup():
        B, S, Dm = (1, 2048, 1024)
        H, Dh = (32, 128)
        M, seg = (8, 32)
        seg = min(seg, S)
        S = S // seg * seg
        return {'x': _w((lambda *s: torch.randn(*s, dtype=torch.bfloat16) * 0.05)(B, S, Dm)), 'mem0': _w((lambda *s: torch.randn(*s, dtype=torch.bfloat16) * 1.6)(B, M, Dm)), 'Wq': _w((lambda *s: torch.randn(*s, dtype=torch.bfloat16) * 0.8)(Dm, H, Dh) * Dm ** (-0.5)), 'Wk': _w((lambda *s: torch.randn(*s, dtype=torch.bfloat16) * 0.8)(Dm, H, Dh) * Dm ** (-0.5)), 'Wv': _w((lambda *s: torch.randn(*s, dtype=torch.bfloat16) * 1.6)(Dm, H, Dh) * Dm ** (-0.5)), 'Wo': _w((lambda *s: torch.randn(*s, dtype=torch.bfloat16) * 1.6)(H, Dh, Dm) * (H * Dh) ** (-0.5)), 'seg_len': seg}
    _A_in = _A_setup()

    def _B_setup():
        B, S, D, F, C = (1, 2048, 1024, 3584, 2)
        return {'x': _w((lambda *s: torch.randn(*s, dtype=torch.bfloat16) * 0.05)(B, S, D)), 'w_r': _w((lambda *s: torch.randn(*s, dtype=torch.bfloat16) * 0.05)(D)), 'w_gate': _w((lambda *s: torch.randn(*s, dtype=torch.bfloat16) * 0.05)(D, F)), 'w_up': _w((lambda *s: torch.randn(*s, dtype=torch.bfloat16) * 0.05)(D, F)), 'w_down': _w((lambda *s: torch.randn(*s, dtype=torch.bfloat16) * 0.05)(F, D))}
    _B_in = _B_setup()
    return {'A_x': _A_in['x'], 'A_mem0': _A_in['mem0'], 'A_Wq': _A_in['Wq'], 'A_Wk': _A_in['Wk'], 'A_Wv': _A_in['Wv'], 'A_Wo': _A_in['Wo'], 'A_seg_len': _A_in['seg_len'], 'B_x': _B_in['x'], 'B_w_r': _B_in['w_r'], 'B_w_gate': _B_in['w_gate'], 'B_w_up': _B_in['w_up'], 'B_w_down': _B_in['w_down']}

def reference(A_x, A_mem0, A_Wq, A_Wk, A_Wv, A_Wo, A_seg_len, B_x, B_w_r, B_w_gate, B_w_up, B_w_down):

    def _A_ref(x, mem0, Wq, Wk, Wv, Wo, seg_len):
        B, S, Dm = x.shape
        H, Dh = (Wq.shape[1], Wq.shape[2])
        M = mem0.shape[1]
        scale = Dh ** (-0.5)
        n_seg = S // seg_len
        L = M + seg_len
        idx = torch.arange(L)
        mask = (idx[:, None] < M) | (idx[:, None] >= idx[None, :])
        mem = mem0
        outs = []
        for s in range(n_seg):
            xs = x[:, s * seg_len:(s + 1) * seg_len, :].clone()
            h = torch.concatenate([mem, xs], axis=1)
            q = torch.einsum('btd,dhe->bhte', h, Wq)
            k = torch.einsum('btd,dhe->bhte', h, Wk)
            v = torch.einsum('btd,dhe->bhte', h, Wv)
            scores = torch.einsum('bhqe,bhke->bhqk', q, k) * scale
            scores = torch.where(mask[None, None], scores, -1000000000.0)
            p = _softmax(scores, axis=-1)
            o = torch.einsum('bhqk,bhke->bhqe', p, v)
            o = torch.einsum('bhte,hed->btd', o, Wo)
            mem = o[:, :M, :].clone()
            outs.append(o[:, M:, :])
        return torch.concatenate(outs, axis=1)

    def _B_ref(x, w_r, w_gate, w_up, w_down):
        B, S, D = x.shape
        C = 2
        r = x @ w_r
        idx = torch.argsort(-r, axis=-1)[:, :C]
        idx_e = (lambda x, n, axis: torch.repeat_interleave(x, n, dim=axis))(idx.reshape(B, C, 1), D, axis=2)
        x_sel = (lambda x, i, axis: torch.take_along_dim(x, i, dim=axis))(x, idx_e, axis=1)
        g = _silu(x_sel @ w_gate)
        u = x_sel @ w_up
        y = g * u @ w_down
        r_sel = _sigmoid((lambda x, i, axis: torch.take_along_dim(x, i, dim=axis))(r, idx, axis=1))
        y = y * r_sel.reshape(B, C, 1)
        b_off = (torch.arange(B) * S).reshape(B, 1)
        flat_idx = (idx + b_off).reshape(B * C)
        zero = (x * 0.0).reshape(B * S, D)
        upd = _scatter_add(zero, flat_idx, y.reshape(B * C, D), axis=0)
        return x + upd.reshape(B, S, D)
    x = A_x
    xn = _layernorm(x, axis=-1)
    return x + _A_ref(xn, A_mem0, A_Wq, A_Wk, A_Wv, A_Wo, A_seg_len) + _B_ref(xn, B_w_r, B_w_gate, B_w_up, B_w_down)
```

```cpp
#include <cuda_runtime.h>
#include <cuda_bf16.h>
#include <cuda.h>
#include <stdint.h>

typedef __nv_bfloat16 bf16;

#define S_LEN 2048
#define DM 1024
#define NH 32
#define DH 128
#define NSEG 64
#define SEGL 32
#define HD 4096
#define NQKV 12288
#define FF 3584
#define SENT 0xFFFFFFFFu

__device__ __align__(1024) bf16 g_xn[S_LEN * DM];
__device__ __align__(1024) bf16 g_qkv[(size_t)S_LEN * NQKV];
__device__ __align__(1024) bf16 g_otok[(size_t)S_LEN * HD];
__device__ float g_r[S_LEN];
__device__ __align__(128) uint4 g_bufA[4][128][96];
__device__ __align__(128) uint4 g_bufB[4][128][32][16];
__device__ __align__(128) uint4 g_bufC[4][1024];
__device__ __align__(128) bf16 g_h[2][FF];
__device__ float g_upd[2][DM];
__device__ int g_sel[2];
__device__ unsigned g_moe_cnt;

__device__ __forceinline__ float bfr(float x) { return __bfloat162float(__float2bfloat16_rn(x)); }
__device__ __forceinline__ uint32_t pack2(float lo, float hi) {
  __nv_bfloat162 v = __floats2bfloat162_rn(lo, hi);
  return *reinterpret_cast<uint32_t*>(&v);
}
__device__ __forceinline__ float bflo(uint32_t v) { return __uint_as_float(v << 16); }
__device__ __forceinline__ float bfhi(uint32_t v) { return __uint_as_float(v & 0xFFFF0000u); }
__device__ __forceinline__ uint32_t smem_u32(const void* p) { return (uint32_t)__cvta_generic_to_shared(p); }

__device__ __forceinline__ uint4 ld_poll(const uint4* p) {
  uint4 v;
  asm volatile("ld.relaxed.gpu.global.v4.u32 {%0,%1,%2,%3},[%4];" : "=r"(v.x), "=r"(v.y), "=r"(v.z), "=r"(v.w) : "l"(p) : "memory");
  return v;
}
__device__ __forceinline__ void st_pub32(void* p, uint32_t v) {
  asm volatile("st.relaxed.gpu.global.u32 [%0],%1;" ::"l"(p), "r"(v) : "memory");
}
__device__ __forceinline__ void st_pub64(void* p, uint32_t a, uint32_t b) {
  asm volatile("st.relaxed.gpu.global.v2.u32 [%0],{%1,%2};" ::"l"(p), "r"(a), "r"(b) : "memory");
}
__device__ __forceinline__ bool pkt_ok(const uint4& v) { return v.x != SENT && v.y != SENT && v.z != SENT && v.w != SENT; }
__device__ __forceinline__ uint32_t desent(uint32_t v) { return v == SENT ? 0x7FFF7FFFu : v; }

__device__ __forceinline__ void ldsm4(uint32_t& r0, uint32_t& r1, uint32_t& r2, uint32_t& r3, uint32_t addr) {
  asm volatile("ldmatrix.sync.aligned.m8n8.x4.shared.b16 {%0,%1,%2,%3},[%4];" : "=r"(r0), "=r"(r1), "=r"(r2), "=r"(r3) : "r"(addr) : "memory");
}
__device__ __forceinline__ void ldsm4t(uint32_t& r0, uint32_t& r1, uint32_t& r2, uint32_t& r3, uint32_t addr) {
  asm volatile("ldmatrix.sync.aligned.m8n8.x4.trans.shared.b16 {%0,%1,%2,%3},[%4];" : "=r"(r0), "=r"(r1), "=r"(r2), "=r"(r3) : "r"(addr) : "memory");
}
__device__ __forceinline__ void mma16816(float (&d)[4], uint32_t a0, uint32_t a1, uint32_t a2, uint32_t a3, uint32_t b0, uint32_t b1) {
  asm volatile("mma.sync.aligned.m16n8k16.row.col.f32.bf16.bf16.f32 {%0,%1,%2,%3},{%4,%5,%6,%7},{%8,%9},{%0,%1,%2,%3};"
               : "+f"(d[0]), "+f"(d[1]), "+f"(d[2]), "+f"(d[3])
               : "r"(a0), "r"(a1), "r"(a2), "r"(a3), "r"(b0), "r"(b1));
}
__device__ __forceinline__ void cp_async16(uint32_t dst, const void* src) {
  asm volatile("cp.async.cg.shared.global [%0],[%1],16;" ::"r"(dst), "l"(src) : "memory");
}
__device__ __forceinline__ void cp_commit() { asm volatile("cp.async.commit_group;" ::: "memory"); }
template <int N>
__device__ __forceinline__ void cp_wait() { asm volatile("cp.async.wait_group %0;" ::"n"(N) : "memory"); }

__device__ __forceinline__ void mbar_init(uint32_t bar, uint32_t cnt) { asm volatile("mbarrier.init.shared::cta.b64 [%0],%1;" ::"r"(bar), "r"(cnt) : "memory"); }
__device__ __forceinline__ void mbar_expect_tx(uint32_t bar, uint32_t bytes) {
  asm volatile("mbarrier.arrive.expect_tx.shared::cta.b64 _,[%0],%1;" ::"r"(bar), "r"(bytes) : "memory");
}
__device__ __forceinline__ void mbar_arrive(uint32_t bar) { asm volatile("mbarrier.arrive.shared::cta.b64 _,[%0];" ::"r"(bar) : "memory"); }
__device__ __forceinline__ void mbar_wait(uint32_t bar, uint32_t parity) {
  asm volatile(
      "{\n.reg .pred p;\n"
      "WAIT_LOOP:\n"
      "mbarrier.try_wait.parity.shared::cta.b64 p,[%0],%1;\n"
      "@p bra WAIT_DONE;\n"
      "bra WAIT_LOOP;\n"
      "WAIT_DONE:\n}\n" ::"r"(bar), "r"(parity) : "memory");
}
__device__ __forceinline__ void tma_load2d(uint32_t dst, const CUtensorMap* tm, uint32_t bar, int c0, int c1) {
  asm volatile("cp.async.bulk.tensor.2d.shared::cluster.global.mbarrier::complete_tx::bytes [%0],[%1,{%3,%4}],[%2];"
               ::"r"(dst), "l"(tm), "r"(bar), "r"(c0), "r"(c1) : "memory");
}
__device__ __forceinline__ void wg_fence() { asm volatile("wgmma.fence.sync.aligned;" ::: "memory"); }
__device__ __forceinline__ void wg_commit() { asm volatile("wgmma.commit_group.sync.aligned;" ::: "memory"); }
template <int N>
__device__ __forceinline__ void wg_wait() { asm volatile("wgmma.wait_group.sync.aligned %0;" ::"n"(N) : "memory"); }
__device__ __forceinline__ uint64_t make_desc(uint32_t addr, uint32_t lbo, uint32_t sbo) {
  return (uint64_t)((addr & 0x3FFFF) >> 4) | ((uint64_t)(lbo >> 4) << 16) | ((uint64_t)(sbo >> 4) << 32) | (1ull << 62);
}

__device__ __forceinline__ void wgmma_m64n256k16(float (&d)[128], uint64_t da, uint64_t db, int scaleD) {
  asm volatile(
    "{\n.reg .pred p;\nsetp.ne.b32 p, %130, 0;\n"
    "wgmma.mma_async.sync.aligned.m64n256k16.f32.bf16.bf16 "
    "{%0, %1, %2, %3, %4, %5, %6, %7, %8, %9, %10, %11, %12, %13, %14, %15, %16, %17, %18, %19, %20, %21, %22, %23, %24, %25, %26, %27, %28, %29, %30, %31, %32, %33, %34, %35, %36, %37, %38, %39, %40, %41, %42, %43, %44, %45, %46, %47, %48, %49, %50, %51, %52, %53, %54, %55, %56, %57, %58, %59, %60, %61, %62, %63, %64, %65, %66, %67, %68, %69, %70, %71, %72, %73, %74, %75, %76, %77, %78, %79, %80, %81, %82, %83, %84, %85, %86, %87, %88, %89, %90, %91, %92, %93, %94, %95, %96, %97, %98, %99, %100, %101, %102, %103, %104, %105, %106, %107, %108, %109, %110, %111, %112, %113, %114, %115, %116, %117, %118, %119, %120, %121, %122, %123, %124, %125, %126, %127}, %128, %129, p, 1, 1, 0, 1;\n}\n"
    : "+f"(d[0]), "+f"(d[1]), "+f"(d[2]), "+f"(d[3]), "+f"(d[4]), "+f"(d[5]), "+f"(d[6]), "+f"(d[7]), "+f"(d[8]), "+f"(d[9]), "+f"(d[10]), "+f"(d[11]), "+f"(d[12]), "+f"(d[13]), "+f"(d[14]), "+f"(d[15]), "+f"(d[16]), "+f"(d[17]), "+f"(d[18]), "+f"(d[19]), "+f"(d[20]), "+f"(d[21]), "+f"(d[22]), "+f"(d[23]), "+f"(d[24]), "+f"(d[25]), "+f"(d[26]), "+f"(d[27]), "+f"(d[28]), "+f"(d[29]), "+f"(d[30]), "+f"(d[31]), "+f"(d[32]), "+f"(d[33]), "+f"(d[34]), "+f"(d[35]), "+f"(d[36]), "+f"(d[37]), "+f"(d[38]), "+f"(d[39]), "+f"(d[40]), "+f"(d[41]), "+f"(d[42]), "+f"(d[43]), "+f"(d[44]), "+f"(d[45]), "+f"(d[46]), "+f"(d[47]), "+f"(d[48]), "+f"(d[49]), "+f"(d[50]), "+f"(d[51]), "+f"(d[52]), "+f"(d[53]), "+f"(d[54]), "+f"(d[55]), "+f"(d[56]), "+f"(d[57]), "+f"(d[58]), "+f"(d[59]), "+f"(d[60]), "+f"(d[61]), "+f"(d[62]), "+f"(d[63]), "+f"(d[64]), "+f"(d[65]), "+f"(d[66]), "+f"(d[67]), "+f"(d[68]), "+f"(d[69]), "+f"(d[70]), "+f"(d[71]), "+f"(d[72]), "+f"(d[73]), "+f"(d[74]), "+f"(d[75]), "+f"(d[76]), "+f"(d[77]), "+f"(d[78]), "+f"(d[79]), "+f"(d[80]), "+f"(d[81]), "+f"(d[82]), "+f"(d[83]), "+f"(d[84]), "+f"(d[85]), "+f"(d[86]), "+f"(d[87]), "+f"(d[88]), "+f"(d[89]), "+f"(d[90]), "+f"(d[91]), "+f"(d[92]), "+f"(d[93]), "+f"(d[94]), "+f"(d[95]), "+f"(d[96]), "+f"(d[97]), "+f"(d[98]), "+f"(d[99]), "+f"(d[100]), "+f"(d[101]), "+f"(d[102]), "+f"(d[103]), "+f"(d[104]), "+f"(d[105]), "+f"(d[106]), "+f"(d[107]), "+f"(d[108]), "+f"(d[109]), "+f"(d[110]), "+f"(d[111]), "+f"(d[112]), "+f"(d[113]), "+f"(d[114]), "+f"(d[115]), "+f"(d[116]), "+f"(d[117]), "+f"(d[118]), "+f"(d[119]), "+f"(d[120]), "+f"(d[121]), "+f"(d[122]), "+f"(d[123]), "+f"(d[124]), "+f"(d[125]), "+f"(d[126]), "+f"(d[127])
    : "l"(da), "l"(db), "r"(scaleD));
}

__device__ __forceinline__ void wgmma_m64n128k16(float (&d)[64], uint64_t da, uint64_t db, int scaleD) {
  asm volatile(
    "{\n.reg .pred p;\nsetp.ne.b32 p, %66, 0;\n"
    "wgmma.mma_async.sync.aligned.m64n128k16.f32.bf16.bf16 "
    "{%0, %1, %2, %3, %4, %5, %6, %7, %8, %9, %10, %11, %12, %13, %14, %15, %16, %17, %18, %19, %20, %21, %22, %23, %24, %25, %26, %27, %28, %29, %30, %31, %32, %33, %34, %35, %36, %37, %38, %39, %40, %41, %42, %43, %44, %45, %46, %47, %48, %49, %50, %51, %52, %53, %54, %55, %56, %57, %58, %59, %60, %61, %62, %63}, %64, %65, p, 1, 1, 0, 1;\n}\n"
    : "+f"(d[0]), "+f"(d[1]), "+f"(d[2]), "+f"(d[3]), "+f"(d[4]), "+f"(d[5]), "+f"(d[6]), "+f"(d[7]), "+f"(d[8]), "+f"(d[9]), "+f"(d[10]), "+f"(d[11]), "+f"(d[12]), "+f"(d[13]), "+f"(d[14]), "+f"(d[15]), "+f"(d[16]), "+f"(d[17]), "+f"(d[18]), "+f"(d[19]), "+f"(d[20]), "+f"(d[21]), "+f"(d[22]), "+f"(d[23]), "+f"(d[24]), "+f"(d[25]), "+f"(d[26]), "+f"(d[27]), "+f"(d[28]), "+f"(d[29]), "+f"(d[30]), "+f"(d[31]), "+f"(d[32]), "+f"(d[33]), "+f"(d[34]), "+f"(d[35]), "+f"(d[36]), "+f"(d[37]), "+f"(d[38]), "+f"(d[39]), "+f"(d[40]), "+f"(d[41]), "+f"(d[42]), "+f"(d[43]), "+f"(d[44]), "+f"(d[45]), "+f"(d[46]), "+f"(d[47]), "+f"(d[48]), "+f"(d[49]), "+f"(d[50]), "+f"(d[51]), "+f"(d[52]), "+f"(d[53]), "+f"(d[54]), "+f"(d[55]), "+f"(d[56]), "+f"(d[57]), "+f"(d[58]), "+f"(d[59]), "+f"(d[60]), "+f"(d[61]), "+f"(d[62]), "+f"(d[63])
    : "l"(da), "l"(db), "r"(scaleD));
}


template <int BN> struct WG;
template <> struct WG<256> { static __device__ __forceinline__ void mma(float (&d)[128], uint64_t a, uint64_t b, int s) { wgmma_m64n256k16(d, a, b, s); } };
template <> struct WG<128> { static __device__ __forceinline__ void mma(float (&d)[64], uint64_t a, uint64_t b, int s) { wgmma_m64n128k16(d, a, b, s); } };

__global__ void __launch_bounds__(256) ln_kernel(const bf16* __restrict__ x, const bf16* __restrict__ w_r) {
  int warp = threadIdx.x >> 5, lane = threadIdx.x & 31;
  int row = blockIdx.x * 8 + warp;
  const uint4* xp = reinterpret_cast<const uint4*>(x + (size_t)row * DM);
  uint4 v[4];
#pragma unroll
  for (int i = 0; i < 4; i++) v[i] = xp[lane + 32 * i];
  float f[32];
#pragma unroll
  for (int i = 0; i < 4; i++) {
    f[8 * i + 0] = bflo(v[i].x); f[8 * i + 1] = bfhi(v[i].x);
    f[8 * i + 2] = bflo(v[i].y); f[8 * i + 3] = bfhi(v[i].y);
    f[8 * i + 4] = bflo(v[i].z); f[8 * i + 5] = bfhi(v[i].z);
    f[8 * i + 6] = bflo(v[i].w); f[8 * i + 7] = bfhi(v[i].w);
  }
  float s = 0.f;
#pragma unroll
  for (int i = 0; i < 32; i++) s += f[i];
#pragma unroll
  for (int o = 16; o > 0; o >>= 1) s += __shfl_xor_sync(0xffffffffu, s, o);
  float mean = s * (1.0f / DM);
  float q = 0.f;
#pragma unroll
  for (int i = 0; i < 32; i++) { float d = f[i] - mean; q += d * d; }
#pragma unroll
  for (int o = 16; o > 0; o >>= 1) q += __shfl_xor_sync(0xffffffffu, q, o);
  float var = bfr(q * (1.0f / DM));
  float mb = bfr(mean);
  float den = bfr(sqrtf(bfr(var + 1e-5f)));
  const uint4* wp = reinterpret_cast<const uint4*>(w_r);
  uint4* op = reinterpret_cast<uint4*>(g_xn + (size_t)row * DM);
  float r = 0.f;
#pragma unroll
  for (int i = 0; i < 4; i++) {
    uint4 w = wp[lane + 32 * i];
    float y[8];
#pragma unroll
    for (int k = 0; k < 8; k++) y[k] = bfr(bfr(f[8 * i + k] - mb) / den);
    r += y[0] * bflo(w.x) + y[1] * bfhi(w.x) + y[2] * bflo(w.y) + y[3] * bfhi(w.y) + y[4] * bflo(w.z) + y[5] * bfhi(w.z) +
         y[6] * bflo(w.w) + y[7] * bfhi(w.w);
    op[lane + 32 * i] = make_uint4(pack2(y[0], y[1]), pack2(y[2], y[3]), pack2(y[4], y[5]), pack2(y[6], y[7]));
  }
#pragma unroll
  for (int o = 16; o > 0; o >>= 1) r += __shfl_xor_sync(0xffffffffu, r, o);
  if (lane == 0) g_r[row] = bfr(r);
  int gt = blockIdx.x * 256 + threadIdx.x;
  const uint4 sv = make_uint4(SENT, SENT, SENT, SENT);
  uint4* a = &g_bufA[0][0][0];
  for (int i = gt; i < 2 * 128 * 96; i += 65536) a[i] = sv;
  uint4* b = &g_bufB[0][0][0][0];
  for (int i = gt; i < 2 * 128 * 32 * 16; i += 65536) b[i] = sv;
  uint4* c = &g_bufC[0][0];
  for (int i = gt; i < 2 * 1024; i += 65536) c[i] = sv;
  if (gt == 0) g_moe_cnt = 0;
}

template <int BN, int STAGES>
struct GemmSmem {
  static constexpr int A_BYTES = 128 * 64 * 2;
  static constexpr int B_BYTES = 64 * BN * 2;
  static constexpr int STAGE_BYTES = A_BYTES + B_BYTES;
  static constexpr int TOTAL = STAGES * STAGE_BYTES + 1024 + 256;
};

__device__ __forceinline__ void quad_transpose(uint32_t (&v)[4], int c) {
  {
    uint32_t s0 = (c & 1) ? v[0] : v[1];
    uint32_t s1 = (c & 1) ? v[2] : v[3];
    uint32_t r0 = __shfl_xor_sync(0xffffffffu, s0, 1);
    uint32_t r1 = __shfl_xor_sync(0xffffffffu, s1, 1);
    if (c & 1) { v[0] = r0; v[2] = r1; } else { v[1] = r0; v[3] = r1; }
  }
  {
    uint32_t s0 = (c & 2) ? v[0] : v[2];
    uint32_t s1 = (c & 2) ? v[1] : v[3];
    uint32_t r0 = __shfl_xor_sync(0xffffffffu, s0, 2);
    uint32_t r1 = __shfl_xor_sync(0xffffffffu, s1, 2);
    if (c & 2) { v[0] = r0; v[1] = r1; } else { v[2] = r0; v[3] = r1; }
  }
}

__device__ __forceinline__ uint32_t add3(uint32_t a, uint32_t x, uint32_t b) {
  float lo = bfr(bflo(x) + bflo(a)) + bflo(b);
  float hi = bfr(bfhi(x) + bfhi(a)) + bfhi(b);
  return pack2(lo, hi);
}

template <int BN, int STAGES, int EPI>
__global__ void __launch_bounds__(288, 1)
gemm_kernel(const __grid_constant__ CUtensorMap tmA, const __grid_constant__ CUtensorMap tmB0,
            const __grid_constant__ CUtensorMap tmB1, const __grid_constant__ CUtensorMap tmB2,
            int kblocks, int tiles_m, int tiles_total, const bf16* __restrict__ xin, bf16* __restrict__ outp) {
  using SM = GemmSmem<BN, STAGES>;
  extern __shared__ uint8_t smem_raw[];
  uint32_t base = (smem_u32(smem_raw) + 1023) & ~1023u;
  uint32_t bars = base + STAGES * SM::STAGE_BYTES;
  int warp = threadIdx.x >> 5, lane = threadIdx.x & 31;
  if (threadIdx.x == 0) {
    for (int i = 0; i < STAGES; i++) { mbar_init(bars + 8 * i, 1); mbar_init(bars + 8 * (STAGES + i), 8); }
    asm volatile("fence.mbarrier_init.release.cluster;" ::: "memory");
  }
  __syncthreads();
  if (warp == 8) {
    if (lane == 0) {
      int it = 0;
      for (int t = blockIdx.x; t < tiles_total; t += gridDim.x) {
        int tm = t % tiles_m, tn = t / tiles_m;
        int n0 = tn * BN;
        const CUtensorMap* tb = &tmB0;
        if (EPI == 0) { int wsel = n0 >> 12; tb = wsel == 0 ? &tmB0 : (wsel == 1 ? &tmB1 : &tmB2); n0 &= 4095; }
        for (int kb = 0; kb < kblocks; kb++, it++) {
          int st = it % STAGES; uint32_t ph = (it / STAGES) & 1;
          mbar_wait(bars + 8 * (STAGES + st), ph ^ 1);
          uint32_t sa = base + st * SM::STAGE_BYTES, sb = sa + SM::A_BYTES;
          mbar_expect_tx(bars + 8 * st, SM::STAGE_BYTES);
          tma_load2d(sa, &tmA, bars + 8 * st, kb * 64, tm * 128);
#pragma unroll
          for (int i = 0; i < BN / 64; i++) tma_load2d(sb + i * 8192, tb, bars + 8 * st, n0 + i * 64, kb * 64);
        }
      }
    }
  } else {
    int wg = warp >> 2;
    int g = lane >> 2, c = lane & 3;
    int it = 0;
    float acc[BN / 2];
    for (int t = blockIdx.x; t < tiles_total; t += gridDim.x) {
      int tm = t % tiles_m, tn = t / tiles_m;
      for (int kb = 0; kb < kblocks; kb++, it++) {
        int st = it % STAGES; uint32_t ph = (it / STAGES) & 1;
        mbar_wait(bars + 8 * st, ph);
        uint32_t sa = base + st * SM::STAGE_BYTES + wg * 8192, sb = base + st * SM::STAGE_BYTES + SM::A_BYTES;
        wg_fence();
#pragma unroll
        for (int kk = 0; kk < 4; kk++) {
          uint64_t da = make_desc(sa + kk * 32, 16, 1024);
          uint64_t db = make_desc(sb + kk * 2048, 8192, 1024);
          WG<BN>::mma(acc, da, db, (kb | kk) != 0);
        }
        wg_commit();
        if (kb > 0) {
          wg_wait<1>();
          int pst = (it - 1) % STAGES;
          if (lane == 0) mbar_arrive(bars + 8 * (STAGES + pst));
        }
      }
      wg_wait<0>();
      { int pst = (it - 1) % STAGES; if (lane == 0) mbar_arrive(bars + 8 * (STAGES + pst)); }
      int row0 = tm * 128 + wg * 64 + (warp & 3) * 16 + g;
      int sel0 = -1, sel1 = -1;
      if (EPI == 1) { sel0 = g_sel[0]; sel1 = g_sel[1]; }
#pragma unroll
      for (int half = 0; half < 2; half++) {
        int row = row0 + half * 8;
#pragma unroll
        for (int q = 0; q < BN / 32; q++) {
          uint32_t v[4];
#pragma unroll
          for (int tt = 0; tt < 4; tt++) v[tt] = pack2(acc[(q * 4 + tt) * 4 + half * 2], acc[(q * 4 + tt) * 4 + half * 2 + 1]);
          quad_transpose(v, c);
          int col = tn * BN + q * 32 + c * 8;
          if (EPI == 0) {
            *reinterpret_cast<uint4*>(outp + (size_t)row * NQKV + col) = make_uint4(v[0], v[1], v[2], v[3]);
          } else {
            uint4 xv = *reinterpret_cast<const uint4*>(xin + (size_t)row * DM + col);
            uint4 bv = *reinterpret_cast<const uint4*>(g_xn + (size_t)row * DM + col);
            if (row == sel0 || row == sel1) {
              const float* u = &g_upd[row == sel0 ? 0 : 1][col];
              bv.x = pack2(bflo(bv.x) + u[0], bfhi(bv.x) + u[1]);
              bv.y = pack2(bflo(bv.y) + u[2], bfhi(bv.y) + u[3]);
              bv.z = pack2(bflo(bv.z) + u[4], bfhi(bv.z) + u[5]);
              bv.w = pack2(bflo(bv.w) + u[6], bfhi(bv.w) + u[7]);
            }
            uint4 o = make_uint4(add3(v[0], xv.x, bv.x), add3(v[1], xv.y, bv.y), add3(v[2], xv.z, bv.z), add3(v[3], xv.w, bv.w));
            *reinterpret_cast<uint4*>(outp + (size_t)row * DM + col) = o;
          }
        }
      }
    }
  }
}

#define RK 11
#define SK (16 - RK)
#define TP 272
#define OFF_WQS 0
#define OFF_MEMT (OFF_WQS + 8 * SK * 3 * 512)
#define OFF_RED (OFF_MEMT + 16384)
#define OFF_QKVM (OFF_RED + 12288)
#define OFF_TOK (OFF_QKVM + 6144)
#define TOK_BYTES (72 * TP)
#define OFF_SA (OFF_TOK + 2 * TOK_BYTES)
#define OFF_RED2 (OFF_SA + 8 * TP)
#define CH_END (OFF_RED2 + 2048)
#define CH_STG2 (131072)
#define CH_SMEM (196608 + 1024)

__device__ void moe_part(int m, const bf16* __restrict__ wg, const bf16* __restrict__ wu, const bf16* __restrict__ wd, uint8_t* smem);

template <int N>
__device__ __forceinline__ void poll_pkts(const uint4* base, int idx0, int total, uint4 (&v)[N]) {
#pragma unroll
  for (int i = 0; i < N; i++) v[i] = (idx0 + i * 256 < total) ? make_uint4(SENT, SENT, SENT, SENT) : make_uint4(0, 0, 0, 0);
  int it = 0;
  bool ok;
  do {
#pragma unroll
    for (int i = 0; i < N; i++)
      if (!pkt_ok(v[i])) v[i] = ld_poll(base + idx0 + i * 256);
    ok = true;
#pragma unroll
    for (int i = 0; i < N; i++) ok = ok && pkt_ok(v[i]);
  } while (!ok && ++it < (1 << 22));
}

__global__ void __launch_bounds__(256, 1)
chain_kernel(const bf16* __restrict__ mem0, const bf16* __restrict__ Wq, const bf16* __restrict__ Wk, const bf16* __restrict__ Wv,
             const bf16* __restrict__ Wo, const bf16* __restrict__ wgate, const bf16* __restrict__ wup, const bf16* __restrict__ wdown) {
  extern __shared__ __align__(1024) uint8_t smem[];
  const int cta = blockIdx.x, t = threadIdx.x, warp = t >> 5, lane = t & 31;
  if (cta >= 128) { moe_part(cta - 128, wgate, wup, wdown, smem); return; }
  const int h = cta >> 2, j = cta & 3;
  const int g = lane >> 2, c = lane & 3;
  const uint32_t sb = smem_u32(smem);
  const int mg = warp & 1, kq = warp >> 1;

  uint32_t wq[RK][3][4];
  uint32_t wo[2][8][4];
  {
    for (int i = t; i < 3 * 1024 * 4; i += 256) {
      int which = i >> 12, k = (i >> 2) & 1023, ch = i & 3;
      const bf16* W = which == 0 ? Wq : (which == 1 ? Wk : Wv);
      cp_async16(sb + (which * 1024 + k) * 64 + ch * 16, W + (size_t)k * HD + h * 128 + 32 * j + ch * 8);
    }
    cp_commit(); cp_wait<0>();
    __syncthreads();
    uint32_t tmp[SK][3][4];
#pragma unroll
    for (int ks = 0; ks < 16; ks++) {
#pragma unroll
      for (int tt = 0; tt < 3; tt++) {
        int tile = 3 * mg + tt;
        int which = tile >> 1, ch = tile & 1;
        int k = (16 * kq + ks) * 16 + (lane & 7) + 8 * (lane >> 4);
        uint32_t addr = sb + (which * 1024 + k) * 64 + ch * 32 + 16 * ((lane >> 3) & 1);
        if (ks < RK) ldsm4t(wq[ks][tt][0], wq[ks][tt][1], wq[ks][tt][2], wq[ks][tt][3], addr);
        else ldsm4t(tmp[ks - RK][tt][0], tmp[ks - RK][tt][1], tmp[ks - RK][tt][2], tmp[ks - RK][tt][3], addr);
      }
    }
    __syncthreads();
#pragma unroll
    for (int ks = 0; ks < SK; ks++)
#pragma unroll
      for (int tt = 0; tt < 3; tt++)
        *reinterpret_cast<uint4*>(smem + OFF_WQS + (((warp * SK + ks) * 3 + tt) * 32 + lane) * 16) =
            make_uint4(tmp[ks][tt][0], tmp[ks][tt][1], tmp[ks][tt][2], tmp[ks][tt][3]);
    for (int i = t; i < 128 * 32; i += 256) {
      int e = i >> 5, ch = i & 31;
      cp_async16(sb + CH_STG2 + e * 512 + ch * 16, Wo + (size_t)(h * 128 + e) * DM + 256 * j + ch * 8);
    }
    cp_commit(); cp_wait<0>();
    __syncthreads();
#pragma unroll
    for (int tt = 0; tt < 2; tt++)
#pragma unroll
      for (int ks = 0; ks < 8; ks++) {
        int e = 16 * ks + (lane & 7) + 8 * (lane >> 4);
        uint32_t addr = sb + CH_STG2 + e * 512 + (32 * warp + 16 * tt + 8 * ((lane >> 3) & 1)) * 2;
        ldsm4t(wo[tt][ks][0], wo[tt][ks][1], wo[tt][ks][2], wo[tt][ks][3], addr);
      }
    __syncthreads();
  }
  auto prefetch_tok = [&](int s) {
    uint32_t dst = sb + OFF_TOK + (s & 1) * TOK_BYTES;
    for (int i = t; i < 1152; i += 256) {
      int r = i >> 4, ch = i & 15;
      const bf16* src;
      if (r < 32) src = g_qkv + (size_t)(s * 32 + r) * NQKV + HD + h * 128;
      else if (r < 64) src = g_qkv + (size_t)(s * 32 + r - 32) * NQKV + 2 * HD + h * 128;
      else src = g_qkv + (size_t)(s * 32 + 8 * j + r - 64) * NQKV + h * 128;
      cp_async16(dst + r * TP + ch * 16, src + ch * 8);
    }
    cp_commit();
  };
  prefetch_tok(0);
  for (int i = t; i < 8 * 1024; i += 256) {
    int r = i >> 10, k = i & 1023;
    reinterpret_cast<bf16*>(smem + OFF_MEMT)[k * 8 + r] = mem0[i];
  }

  for (int s = 0; s < NSEG; s++) {
    const int slot = s & 3, slot2 = (s + 2) & 3;
    if (s > 0) {
      uint4 v[4];
      poll_pkts<4>(&g_bufC[(s - 1) & 3][0], t, 1024, v);
#pragma unroll
      for (int i = 0; i < 4; i++) *reinterpret_cast<uint4*>(smem + OFF_MEMT + (t + 256 * i) * 16) = v[i];
    }
    __syncthreads();
    if (s + 1 < NSEG) prefetch_tok(s + 1); else cp_commit();
    {
      float acc[2][3][4];
#pragma unroll
      for (int a = 0; a < 2; a++)
#pragma unroll
        for (int tt = 0; tt < 3; tt++)
#pragma unroll
          for (int i = 0; i < 4; i++) acc[a][tt][i] = 0.f;
#pragma unroll
      for (int kp = 0; kp < 8; kp++) {
        uint32_t b0, b1, b2, b3;
        ldsm4t(b0, b1, b2, b3, sb + OFF_MEMT + ((16 * kq + 2 * kp) * 16 + lane) * 16);
#pragma unroll
        for (int u = 0; u < 2; u++) {
          int ks = 2 * kp + u;
#pragma unroll
          for (int tt = 0; tt < 3; tt++) {
            if (ks < RK) {
              mma16816(acc[u][tt], wq[ks][tt][0], wq[ks][tt][1], wq[ks][tt][2], wq[ks][tt][3], u ? b2 : b0, u ? b3 : b1);
            } else {
              uint4 a = *reinterpret_cast<const uint4*>(smem + OFF_WQS + (((warp * SK + (ks - RK)) * 3 + tt) * 32 + lane) * 16);
              mma16816(acc[u][tt], a.x, a.y, a.z, a.w, u ? b2 : b0, u ? b3 : b1);
            }
          }
        }
      }
#pragma unroll
      for (int tt = 0; tt < 3; tt++)
        *reinterpret_cast<float4*>(smem + OFF_RED + ((kq * 6 + 3 * mg + tt) * 32 + lane) * 16) =
            make_float4(acc[0][tt][0] + acc[1][tt][0], acc[0][tt][1] + acc[1][tt][1], acc[0][tt][2] + acc[1][tt][2], acc[0][tt][3] + acc[1][tt][3]);
    }
    __syncthreads();
    if (warp < 6) {
      float4 r = *reinterpret_cast<const float4*>(smem + OFF_RED + ((0 * 6 + warp) * 32 + lane) * 16);
#pragma unroll
      for (int q = 1; q < 4; q++) {
        float4 x = *reinterpret_cast<const float4*>(smem + OFF_RED + ((q * 6 + warp) * 32 + lane) * 16);
        r.x += x.x; r.y += x.y; r.z += x.z; r.w += x.w;
      }
      uint32_t* dst = reinterpret_cast<uint32_t*>(&g_bufA[slot][cta][16 * warp + g]) + c;
      st_pub32(dst, desent(pack2(r.x, r.y)));
      st_pub32(dst + 32, desent(pack2(r.z, r.w)));
      uint32_t* d2 = reinterpret_cast<uint32_t*>(&g_bufA[slot2][cta][16 * warp + g]) + c;
      st_pub32(d2, SENT);
      st_pub32(d2 + 32, SENT);
    }
    {
      uint4 v[2];
      poll_pkts<2>(&g_bufA[slot][4 * h][0], t, 384, v);
#pragma unroll
      for (int i = 0; i < 2; i++) {
        int p = t + 256 * i;
        if (p < 384) {
          int jj = p / 96, f = p % 96;
          int which = f >> 5, e = 32 * jj + (f & 31);
          *reinterpret_cast<uint4*>(smem + OFF_QKVM + (which * 128 + e) * 16) = v[i];
        }
      }
    }
    cp_wait<1>();
    __syncthreads();
    if (warp < 4) {
      const uint32_t tok = sb + OFF_TOK + (s & 1) * TOK_BYTES;
      float sc[5][4];
#pragma unroll
      for (int n = 0; n < 5; n++)
#pragma unroll
        for (int i = 0; i < 4; i++) sc[n][i] = 0.f;
#pragma unroll
      for (int kp = 0; kp < 4; kp++) {
        uint32_t qm[4], qt[4];
        ldsm4t(qm[0], qm[1], qm[2], qm[3], sb + OFF_QKVM + (0 * 128 + 32 * kp + lane) * 16);
        ldsm4(qt[0], qt[1], qt[2], qt[3], tok + (64 + (lane & 7)) * TP + (32 * kp + 8 * (lane >> 3)) * 2);
        uint32_t km[4];
        ldsm4t(km[0], km[1], km[2], km[3], sb + OFF_QKVM + (1 * 128 + 32 * kp + lane) * 16);
        mma16816(sc[0], qm[0], qt[0], qm[1], qt[1], km[0], km[1]);
        mma16816(sc[0], qm[2], qt[2], qm[3], qt[3], km[2], km[3]);
#pragma unroll
        for (int n = 1; n < 5; n++) {
          uint32_t kt[4];
          ldsm4(kt[0], kt[1], kt[2], kt[3], tok + (8 * (n - 1) + (lane & 7)) * TP + (32 * kp + 8 * (lane >> 3)) * 2);
          mma16816(sc[n], qm[0], qt[0], qm[1], qt[1], kt[0], kt[1]);
          mma16816(sc[n], qm[2], qt[2], qm[3], qt[3], kt[2], kt[3]);
        }
      }
      const float scale = 0.08838834764831845f;
      const int tr = 8 * j + g;
      float m0 = -3.0e38f, m1 = -3.0e38f;
#pragma unroll
      for (int n = 0; n < 5; n++) {
#pragma unroll
        for (int i = 0; i < 4; i++) sc[n][i] = bfr(bfr(sc[n][i]) * scale);
        if (n > 0) {
          int kt = 8 * (n - 1) + 2 * c;
          if (kt > tr) sc[n][2] = -1.0e9f;
          if (kt + 1 > tr) sc[n][3] = -1.0e9f;
        }
        m0 = fmaxf(m0, fmaxf(sc[n][0], sc[n][1]));
        m1 = fmaxf(m1, fmaxf(sc[n][2], sc[n][3]));
      }
      m0 = fmaxf(m0, __shfl_xor_sync(0xffffffffu, m0, 1)); m0 = fmaxf(m0, __shfl_xor_sync(0xffffffffu, m0, 2));
      m1 = fmaxf(m1, __shfl_xor_sync(0xffffffffu, m1, 1)); m1 = fmaxf(m1, __shfl_xor_sync(0xffffffffu, m1, 2));
      float s0 = 0.f, s1 = 0.f;
#pragma unroll
      for (int n = 0; n < 5; n++) {
        sc[n][0] = __expf(sc[n][0] - m0); sc[n][1] = __expf(sc[n][1] - m0);
        sc[n][2] = __expf(sc[n][2] - m1); sc[n][3] = __expf(sc[n][3] - m1);
        s0 += sc[n][0] + sc[n][1]; s1 += sc[n][2] + sc[n][3];
      }
      s0 += __shfl_xor_sync(0xffffffffu, s0, 1); s0 += __shfl_xor_sync(0xffffffffu, s0, 2);
      s1 += __shfl_xor_sync(0xffffffffu, s1, 1); s1 += __shfl_xor_sync(0xffffffffu, s1, 2);
      float i0 = 1.0f / s0, i1 = 1.0f / s1;
      uint32_t pa[3][4];
#pragma unroll
      for (int kk = 0; kk < 3; kk++) {
        pa[kk][0] = pack2(sc[2 * kk][0] * i0, sc[2 * kk][1] * i0);
        pa[kk][1] = pack2(sc[2 * kk][2] * i1, sc[2 * kk][3] * i1);
        if (kk < 2) {
          pa[kk][2] = pack2(sc[2 * kk + 1][0] * i0, sc[2 * kk + 1][1] * i0);
          pa[kk][3] = pack2(sc[2 * kk + 1][2] * i1, sc[2 * kk + 1][3] * i1);
        } else { pa[kk][2] = 0; pa[kk][3] = 0; }
      }
      uint32_t vm[4];
      ldsm4(vm[0], vm[1], vm[2], vm[3], sb + OFF_QKVM + (2 * 128 + 32 * warp + lane) * 16);
#pragma unroll
      for (int n = 0; n < 4; n++) {
        uint32_t vt[4];
        ldsm4t(vt[0], vt[1], vt[2], vt[3], tok + (32 + lane) * TP + (32 * warp + 8 * n) * 2);
        float o[4] = {0.f, 0.f, 0.f, 0.f};
        mma16816(o, pa[0][0], pa[0][1], pa[0][2], pa[0][3], vm[n], vt[0]);
        mma16816(o, pa[1][0], pa[1][1], pa[1][2], pa[1][3], vt[1], vt[2]);
        mma16816(o, pa[2][0], pa[2][1], pa[2][2], pa[2][3], vt[3], 0u);
        int e = 32 * warp + 8 * n + 2 * c;
        *reinterpret_cast<uint32_t*>(smem + OFF_SA + g * TP + e * 2) = pack2(o[0], o[1]);
        *reinterpret_cast<uint32_t*>(g_otok + (size_t)(s * 32 + tr) * HD + h * 128 + e) = pack2(o[2], o[3]);
      }
    }
    if (s == NSEG - 1) break;
    __syncthreads();
    {
      float acc[2][2][4];
#pragma unroll
      for (int a = 0; a < 2; a++)
#pragma unroll
        for (int tt = 0; tt < 2; tt++)
#pragma unroll
          for (int i = 0; i < 4; i++) acc[a][tt][i] = 0.f;
#pragma unroll
      for (int kp = 0; kp < 4; kp++) {
        uint32_t b0, b1, b2, b3;
        ldsm4(b0, b1, b2, b3, sb + OFF_SA + (lane & 7) * TP + (32 * kp + 8 * (lane >> 3)) * 2);
#pragma unroll
        for (int tt = 0; tt < 2; tt++) {
          mma16816(acc[0][tt], wo[tt][2 * kp][0], wo[tt][2 * kp][1], wo[tt][2 * kp][2], wo[tt][2 * kp][3], b0, b1);
          mma16816(acc[1][tt], wo[tt][2 * kp + 1][0], wo[tt][2 * kp + 1][1], wo[tt][2 * kp + 1][2], wo[tt][2 * kp + 1][3], b2, b3);
        }
      }
#pragma unroll
      for (int tt = 0; tt < 2; tt++) {
        int r0 = 32 * j + 4 * warp + 2 * tt;
        uint32_t x0 = __float_as_uint(acc[0][tt][0] + acc[1][tt][0]), x1 = __float_as_uint(acc[0][tt][1] + acc[1][tt][1]);
        uint32_t x2 = __float_as_uint(acc[0][tt][2] + acc[1][tt][2]), x3 = __float_as_uint(acc[0][tt][3] + acc[1][tt][3]);
        x0 = x0 == SENT ? 0x7FFFFFFFu : x0; x1 = x1 == SENT ? 0x7FFFFFFFu : x1;
        x2 = x2 == SENT ? 0x7FFFFFFFu : x2; x3 = x3 == SENT ? 0x7FFFFFFFu : x3;
        uint2* d0 = reinterpret_cast<uint2*>(&g_bufB[slot][r0][h][0]) + lane;
        uint2* d1 = reinterpret_cast<uint2*>(&g_bufB[slot][r0 + 1][h][0]) + lane;
        st_pub64(d0, x0, x1);
        st_pub64(d1, x2, x3);
        st_pub64(reinterpret_cast<uint2*>(&g_bufB[slot2][r0][h][0]) + lane, SENT, SENT);
        st_pub64(reinterpret_cast<uint2*>(&g_bufB[slot2][r0 + 1][h][0]) + lane, SENT, SENT);
      }
    }
    {
      uint4 v[2];
      poll_pkts<2>(&g_bufB[slot][cta][0][0], t, 512, v);
      float4 r = make_float4(__uint_as_float(v[0].x) + __uint_as_float(v[1].x), __uint_as_float(v[0].y) + __uint_as_float(v[1].y),
                             __uint_as_float(v[0].z) + __uint_as_float(v[1].z), __uint_as_float(v[0].w) + __uint_as_float(v[1].w));
      r.x += __shfl_xor_sync(0xffffffffu, r.x, 16); r.y += __shfl_xor_sync(0xffffffffu, r.y, 16);
      r.z += __shfl_xor_sync(0xffffffffu, r.z, 16); r.w += __shfl_xor_sync(0xffffffffu, r.w, 16);
      if (lane < 16) *reinterpret_cast<float4*>(smem + OFF_RED2 + (warp * 16 + lane) * 16) = r;
    }
    __syncthreads();
    if (t < 16) {
      float4 r = *reinterpret_cast<const float4*>(smem + OFF_RED2 + t * 16);
#pragma unroll
      for (int q = 1; q < 8; q++) {
        float4 x = *reinterpret_cast<const float4*>(smem + OFF_RED2 + (q * 16 + t) * 16);
        r.x += x.x; r.y += x.y; r.z += x.z; r.w += x.w;
      }
      uint2* d = reinterpret_cast<uint2*>(&g_bufC[slot][8 * cta]) + t;
      st_pub64(d, desent(pack2(r.x, r.y)), desent(pack2(r.z, r.w)));
      st_pub64(reinterpret_cast<uint2*>(&g_bufC[slot2][8 * cta]) + t, SENT, SENT);
    }
  }
}

__device__ void moe_part(int m, const bf16* __restrict__ wg, const bf16* __restrict__ wu, const bf16* __restrict__ wd, uint8_t* smem) {
  const int t = threadIdx.x, warp = t >> 5, lane = t & 31;
  float* xs = reinterpret_cast<float*>(smem);
  float* red = reinterpret_cast<float*>(smem + 8192);
  float* hs = reinterpret_cast<float*>(smem + 65536);
  __shared__ float bv[8];
  __shared__ int bi[8];
  __shared__ int sel[2];
  int first = -1;
  for (int pass = 0; pass < 2; pass++) {
    float best = -INFINITY; int bidx = 0x7fffffff;
    for (int i = t; i < S_LEN; i += 256) {
      float v = g_r[i];
      if (i == first) continue;
      if (v > best || (v == best && i < bidx) || bidx == 0x7fffffff) { best = v; bidx = i; }
    }
#pragma unroll
    for (int o = 16; o > 0; o >>= 1) {
      float ov = __shfl_xor_sync(0xffffffffu, best, o); int oi = __shfl_xor_sync(0xffffffffu, bidx, o);
      if (oi != 0x7fffffff && (bidx == 0x7fffffff || ov > best || (ov == best && oi < bidx))) { best = ov; bidx = oi; }
    }
    if (lane == 0) { bv[warp] = best; bi[warp] = bidx; }
    __syncthreads();
    if (t == 0) {
      float b = bv[0]; int ix = bi[0];
      for (int w = 1; w < 8; w++) if (bv[w] > b || (bv[w] == b && bi[w] < ix)) { b = bv[w]; ix = bi[w]; }
      sel[pass] = ix;
    }
    __syncthreads();
    first = sel[0];
  }
  const int s0 = sel[0], s1 = sel[1];
  for (int i = t; i < 2048; i += 256) xs[i] = __bfloat162float(g_xn[(size_t)(i < 1024 ? s0 : s1) * DM + (i & 1023)]);
  __syncthreads();
  {
    int cg = t % 112, kh = t / 112;
    float a[2][2][8];
#pragma unroll
    for (int i = 0; i < 8; i++) { a[0][0][i] = a[0][1][i] = a[1][0][i] = a[1][1][i] = 0.f; }
    if (kh < 2) {
      const bf16* pg = wg + (size_t)(kh * 512) * FF + 896 * m + cg * 8;
      const bf16* pu = wu + (size_t)(kh * 512) * FF + 896 * m + cg * 8;
#pragma unroll 8
      for (int k = 0; k < 512; k++) {
        uint4 gv = __ldg(reinterpret_cast<const uint4*>(pg + (size_t)k * FF));
        uint4 uv = __ldg(reinterpret_cast<const uint4*>(pu + (size_t)k * FF));
        float x0 = xs[kh * 512 + k], x1 = xs[1024 + kh * 512 + k];
        float gf[8] = {bflo(gv.x), bfhi(gv.x), bflo(gv.y), bfhi(gv.y), bflo(gv.z), bfhi(gv.z), bflo(gv.w), bfhi(gv.w)};
        float uf[8] = {bflo(uv.x), bfhi(uv.x), bflo(uv.y), bfhi(uv.y), bflo(uv.z), bfhi(uv.z), bflo(uv.w), bfhi(uv.w)};
#pragma unroll
        for (int i = 0; i < 8; i++) {
          a[0][0][i] += x0 * gf[i]; a[0][1][i] += x1 * gf[i];
          a[1][0][i] += x0 * uf[i]; a[1][1][i] += x1 * uf[i];
        }
      }
      if (kh == 1) {
#pragma unroll
        for (int i = 0; i < 8; i++) {
          red[(0 * 2 + 0) * 896 + cg * 8 + i] = a[0][0][i]; red[(0 * 2 + 1) * 896 + cg * 8 + i] = a[0][1][i];
          red[(1 * 2 + 0) * 896 + cg * 8 + i] = a[1][0][i]; red[(1 * 2 + 1) * 896 + cg * 8 + i] = a[1][1][i];
        }
      }
    }
    __syncthreads();
    if (kh == 0) {
#pragma unroll
      for (int i = 0; i < 8; i++) {
#pragma unroll
        for (int tk = 0; tk < 2; tk++) {
          float gq = bfr(a[0][tk][i] + red[(0 * 2 + tk) * 896 + cg * 8 + i]);
          float uq = bfr(a[1][tk][i] + red[(1 * 2 + tk) * 896 + cg * 8 + i]);
          float sg = bfr(gq / (1.0f + __expf(-gq)));
          g_h[tk][896 * m + cg * 8 + i] = __float2bfloat16_rn(sg * uq);
        }
      }
    }
    __threadfence();
    __syncthreads();
    if (t == 0) {
      atomicAdd(&g_moe_cnt, 1u);
      int it = 0;
      while (*reinterpret_cast<volatile unsigned*>(&g_moe_cnt) < 4u && ++it < (1 << 24)) {}
      __threadfence();
    }
    __syncthreads();
  }
  for (int i = t; i < 2 * FF; i += 256) {
    const volatile unsigned short* p = reinterpret_cast<const volatile unsigned short*>(&g_h[0][0]);
    hs[i] = __uint_as_float(((uint32_t)p[i]) << 16);
  }
  __syncthreads();
  {
    int cg = t & 31, ksl = t >> 5;
    float a[2][8];
#pragma unroll
    for (int i = 0; i < 8; i++) a[0][i] = a[1][i] = 0.f;
    const bf16* pd = wd + (size_t)(ksl * 448) * DM + 256 * m + cg * 8;
#pragma unroll 8
    for (int k = 0; k < 448; k++) {
      uint4 dv = __ldg(reinterpret_cast<const uint4*>(pd + (size_t)k * DM));
      float x0 = hs[ksl * 448 + k], x1 = hs[FF + ksl * 448 + k];
      float df[8] = {bflo(dv.x), bfhi(dv.x), bflo(dv.y), bfhi(dv.y), bflo(dv.z), bfhi(dv.z), bflo(dv.w), bfhi(dv.w)};
#pragma unroll
      for (int i = 0; i < 8; i++) { a[0][i] += x0 * df[i]; a[1][i] += x1 * df[i]; }
    }
#pragma unroll
    for (int i = 0; i < 8; i++) { red[(ksl * 2 + 0) * 256 + cg * 8 + i] = a[0][i]; red[(ksl * 2 + 1) * 256 + cg * 8 + i] = a[1][i]; }
    __syncthreads();
    for (int i = t; i < 512; i += 256) {
      int tk = i >> 8, col = i & 255;
      float y = 0.f;
#pragma unroll
      for (int q = 0; q < 8; q++) y += red[(q * 2 + tk) * 256 + col];
      float rr = g_r[tk == 0 ? s0 : s1];
      float sg = bfr(1.0f / (1.0f + __expf(-rr)));
      g_upd[tk][256 * m + col] = bfr(bfr(y) * sg);
    }
    if (m == 0 && t == 0) { g_sel[0] = s0; g_sel[1] = s1; }
  }
}

typedef CUresult (*EncodeFn)(CUtensorMap*, CUtensorMapDataType, cuuint32_t, void*, const cuuint64_t*, const cuuint64_t*,
                             const cuuint32_t*, const cuuint32_t*, CUtensorMapInterleave, CUtensorMapSwizzle,
                             CUtensorMapL2promotion, CUtensorMapFloatOOBfill);

static void make_map(EncodeFn enc, CUtensorMap* m, const void* ptr, uint64_t inner, uint64_t outer, uint32_t bi, uint32_t bo) {
  cuuint64_t dims[2] = {inner, outer};
  cuuint64_t strides[1] = {inner * 2};
  cuuint32_t box[2] = {bi, bo};
  cuuint32_t es[2] = {1, 1};
  enc(m, CU_TENSOR_MAP_DATA_TYPE_BFLOAT16, 2, const_cast<void*>(ptr), dims, strides, box, es, CU_TENSOR_MAP_INTERLEAVE_NONE,
      CU_TENSOR_MAP_SWIZZLE_128B, CU_TENSOR_MAP_L2_PROMOTION_L2_256B, CU_TENSOR_MAP_FLOAT_OOB_FILL_NONE);
}

extern "C" void kernel_launch(void* const* d_in, const int* in_sizes, int n_in, void* d_out, int out_size) {
  const bf16* x = (const bf16*)d_in[0];
  const bf16* mem0 = (const bf16*)d_in[1];
  const bf16* Wq = (const bf16*)d_in[2];
  const bf16* Wk = (const bf16*)d_in[3];
  const bf16* Wv = (const bf16*)d_in[4];
  const bf16* Wo = (const bf16*)d_in[5];
  const bf16* w_r = (const bf16*)d_in[8];
  const bf16* wg = (const bf16*)d_in[9];
  const bf16* wu = (const bf16*)d_in[10];
  const bf16* wd = (const bf16*)d_in[11];
  bf16* out = (bf16*)d_out;

  static EncodeFn enc = nullptr;
  static void *p_xn, *p_qkv, *p_otok;
  if (!enc) {
    cudaDriverEntryPointQueryResult qr;
    void* fn = nullptr;
    cudaGetDriverEntryPoint("cuTensorMapEncodeTiled", &fn, cudaEnableDefault, &qr);
    enc = (EncodeFn)fn;
    cudaGetSymbolAddress(&p_xn, g_xn);
    cudaGetSymbolAddress(&p_qkv, g_qkv);
    cudaGetSymbolAddress(&p_otok, g_otok);
    cudaFuncSetAttribute(gemm_kernel<256, 4, 0>, cudaFuncAttributeMaxDynamicSharedMemorySize, GemmSmem<256, 4>::TOTAL);
    cudaFuncSetAttribute(gemm_kernel<128, 6, 1>, cudaFuncAttributeMaxDynamicSharedMemorySize, GemmSmem<128, 6>::TOTAL);
    cudaFuncSetAttribute(chain_kernel, cudaFuncAttributeMaxDynamicSharedMemorySize, CH_SMEM);
  }
  CUtensorMap mA, mQ, mK, mV, mO, mWo;
  make_map(enc, &mA, p_xn, DM, S_LEN, 64, 128);
  make_map(enc, &mQ, Wq, HD, DM, 64, 64);
  make_map(enc, &mK, Wk, HD, DM, 64, 64);
  make_map(enc, &mV, Wv, HD, DM, 64, 64);
  make_map(enc, &mO, p_otok, HD, S_LEN, 64, 128);
  make_map(enc, &mWo, Wo, DM, HD, 64, 64);

  cudaStream_t st = cudaStreamPerThread;
  ln_kernel<<<256, 256, 0, st>>>(x, w_r);
  gemm_kernel<256, 4, 0><<<132, 288, GemmSmem<256, 4>::TOTAL, st>>>(mA, mQ, mK, mV, 16, 16, 16 * 48, nullptr, (bf16*)p_qkv);
  chain_kernel<<<132, 256, CH_SMEM, st>>>(mem0, Wq, Wk, Wv, Wo, wg, wu, wd);
  gemm_kernel<128, 6, 1><<<128, 288, GemmSmem<128, 6>::TOTAL, st>>>(mO, mWo, mWo, mWo, 64, 16, 16 * 8, x, out);
}
```

```cpp
#include <cuda_runtime.h>
#include <cuda_bf16.h>
#include <cuda.h>
#include <stdint.h>

typedef __nv_bfloat16 bf16;

#define S_LEN 2048
#define DM 1024
#define NH 32
#define DH 128
#define NSEG 64
#define SEGL 32
#define HD 4096
#define NQKV 12288
#define FF 3584
#define SENT 0xFFFFFFFFu

__device__ __align__(1024) bf16 g_xn[S_LEN * DM];
__device__ __align__(1024) bf16 g_qkv[(size_t)S_LEN * NQKV];
__device__ __align__(1024) bf16 g_otok[(size_t)S_LEN * HD];
__device__ float g_r[S_LEN];
__device__ __align__(128) uint4 g_bufA[4][128][96];
__device__ __align__(128) uint4 g_bufB[4][128][16][32];
__device__ __align__(128) uint4 g_bufC[4][1024];
__device__ __align__(128) bf16 g_h[2][FF];
__device__ float g_upd[2][DM];
__device__ int g_sel[2];
__device__ unsigned g_moe_cnt;
#define TS(i)

__device__ __forceinline__ float bfr(float x) { return __bfloat162float(__float2bfloat16_rn(x)); }
__device__ __forceinline__ uint32_t pack2(float lo, float hi) {
  __nv_bfloat162 v = __floats2bfloat162_rn(lo, hi);
  return *reinterpret_cast<uint32_t*>(&v);
}
__device__ __forceinline__ float bflo(uint32_t v) { return __uint_as_float(v << 16); }
__device__ __forceinline__ float bfhi(uint32_t v) { return __uint_as_float(v & 0xFFFF0000u); }
__device__ __forceinline__ uint32_t smem_u32(const void* p) { return (uint32_t)__cvta_generic_to_shared(p); }

__device__ __forceinline__ uint4 ld_poll(const uint4* p) {
  uint4 v;
  asm volatile("ld.relaxed.gpu.global.v4.u32 {%0,%1,%2,%3},[%4];" : "=r"(v.x), "=r"(v.y), "=r"(v.z), "=r"(v.w) : "l"(p) : "memory");
  return v;
}
__device__ __forceinline__ void st_pub32(void* p, uint32_t v) {
  asm volatile("st.relaxed.gpu.global.u32 [%0],%1;" ::"l"(p), "r"(v) : "memory");
}
__device__ __forceinline__ void st_pub64(void* p, uint32_t a, uint32_t b) {
  asm volatile("st.relaxed.gpu.global.v2.u32 [%0],{%1,%2};" ::"l"(p), "r"(a), "r"(b) : "memory");
}
__device__ __forceinline__ bool pkt_ok(const uint4& v) { return v.x != SENT && v.y != SENT && v.z != SENT && v.w != SENT; }
__device__ __forceinline__ uint32_t desent(uint32_t v) { return v == SENT ? 0x7FFF7FFFu : v; }

__device__ __forceinline__ void ldsm4(uint32_t& r0, uint32_t& r1, uint32_t& r2, uint32_t& r3, uint32_t addr) {
  asm volatile("ldmatrix.sync.aligned.m8n8.x4.shared.b16 {%0,%1,%2,%3},[%4];" : "=r"(r0), "=r"(r1), "=r"(r2), "=r"(r3) : "r"(addr) : "memory");
}
__device__ __forceinline__ void ldsm4t(uint32_t& r0, uint32_t& r1, uint32_t& r2, uint32_t& r3, uint32_t addr) {
  asm volatile("ldmatrix.sync.aligned.m8n8.x4.trans.shared.b16 {%0,%1,%2,%3},[%4];" : "=r"(r0), "=r"(r1), "=r"(r2), "=r"(r3) : "r"(addr) : "memory");
}
__device__ __forceinline__ void mma16816(float (&d)[4], uint32_t a0, uint32_t a1, uint32_t a2, uint32_t a3, uint32_t b0, uint32_t b1) {
  asm("mma.sync.aligned.m16n8k16.row.col.f32.bf16.bf16.f32 {%0,%1,%2,%3},{%4,%5,%6,%7},{%8,%9},{%0,%1,%2,%3};"
               : "+f"(d[0]), "+f"(d[1]), "+f"(d[2]), "+f"(d[3])
               : "r"(a0), "r"(a1), "r"(a2), "r"(a3), "r"(b0), "r"(b1));
}
__device__ __forceinline__ void cp_async16(uint32_t dst, const void* src) {
  asm volatile("cp.async.cg.shared.global [%0],[%1],16;" ::"r"(dst), "l"(src) : "memory");
}
__device__ __forceinline__ void cp_commit() { asm volatile("cp.async.commit_group;" ::: "memory"); }
template <int N>
__device__ __forceinline__ void cp_wait() { asm volatile("cp.async.wait_group %0;" ::"n"(N) : "memory"); }

__device__ __forceinline__ void mbar_init(uint32_t bar, uint32_t cnt) { asm volatile("mbarrier.init.shared::cta.b64 [%0],%1;" ::"r"(bar), "r"(cnt) : "memory"); }
__device__ __forceinline__ void mbar_expect_tx(uint32_t bar, uint32_t bytes) {
  asm volatile("mbarrier.arrive.expect_tx.shared::cta.b64 _,[%0],%1;" ::"r"(bar), "r"(bytes) : "memory");
}
__device__ __forceinline__ void mbar_arrive(uint32_t bar) { asm volatile("mbarrier.arrive.shared::cta.b64 _,[%0];" ::"r"(bar) : "memory"); }
__device__ __forceinline__ void mbar_wait(uint32_t bar, uint32_t parity) {
  asm volatile(
      "{\n.reg .pred p;\n"
      "WAIT_LOOP:\n"
      "mbarrier.try_wait.parity.shared::cta.b64 p,[%0],%1;\n"
      "@p bra WAIT_DONE;\n"
      "bra WAIT_LOOP;\n"
      "WAIT_DONE:\n}\n" ::"r"(bar), "r"(parity) : "memory");
}
__device__ __forceinline__ void tma_load2d(uint32_t dst, const CUtensorMap* tm, uint32_t bar, int c0, int c1) {
  asm volatile("cp.async.bulk.tensor.2d.shared::cluster.global.mbarrier::complete_tx::bytes [%0],[%1,{%3,%4}],[%2];"
               ::"r"(dst), "l"(tm), "r"(bar), "r"(c0), "r"(c1) : "memory");
}
__device__ __forceinline__ void wg_fence() { asm volatile("wgmma.fence.sync.aligned;" ::: "memory"); }
__device__ __forceinline__ void wg_commit() { asm volatile("wgmma.commit_group.sync.aligned;" ::: "memory"); }
template <int N>
__device__ __forceinline__ void wg_wait() { asm volatile("wgmma.wait_group.sync.aligned %0;" ::"n"(N) : "memory"); }
__device__ __forceinline__ uint64_t make_desc(uint32_t addr, uint32_t lbo, uint32_t sbo) {
  return (uint64_t)((addr & 0x3FFFF) >> 4) | ((uint64_t)(lbo >> 4) << 16) | ((uint64_t)(sbo >> 4) << 32) | (1ull << 62);
}

__device__ __forceinline__ void wgmma_m64n256k16(float (&d)[128], uint64_t da, uint64_t db, int scaleD) {
  asm volatile(
    "{\n.reg .pred p;\nsetp.ne.b32 p, %130, 0;\n"
    "wgmma.mma_async.sync.aligned.m64n256k16.f32.bf16.bf16 "
    "{%0, %1, %2, %3, %4, %5, %6, %7, %8, %9, %10, %11, %12, %13, %14, %15, %16, %17, %18, %19, %20, %21, %22, %23, %24, %25, %26, %27, %28, %29, %30, %31, %32, %33, %34, %35, %36, %37, %38, %39, %40, %41, %42, %43, %44, %45, %46, %47, %48, %49, %50, %51, %52, %53, %54, %55, %56, %57, %58, %59, %60, %61, %62, %63, %64, %65, %66, %67, %68, %69, %70, %71, %72, %73, %74, %75, %76, %77, %78, %79, %80, %81, %82, %83, %84, %85, %86, %87, %88, %89, %90, %91, %92, %93, %94, %95, %96, %97, %98, %99, %100, %101, %102, %103, %104, %105, %106, %107, %108, %109, %110, %111, %112, %113, %114, %115, %116, %117, %118, %119, %120, %121, %122, %123, %124, %125, %126, %127}, %128, %129, p, 1, 1, 0, 1;\n}\n"
    : "+f"(d[0]), "+f"(d[1]), "+f"(d[2]), "+f"(d[3]), "+f"(d[4]), "+f"(d[5]), "+f"(d[6]), "+f"(d[7]), "+f"(d[8]), "+f"(d[9]), "+f"(d[10]), "+f"(d[11]), "+f"(d[12]), "+f"(d[13]), "+f"(d[14]), "+f"(d[15]), "+f"(d[16]), "+f"(d[17]), "+f"(d[18]), "+f"(d[19]), "+f"(d[20]), "+f"(d[21]), "+f"(d[22]), "+f"(d[23]), "+f"(d[24]), "+f"(d[25]), "+f"(d[26]), "+f"(d[27]), "+f"(d[28]), "+f"(d[29]), "+f"(d[30]), "+f"(d[31]), "+f"(d[32]), "+f"(d[33]), "+f"(d[34]), "+f"(d[35]), "+f"(d[36]), "+f"(d[37]), "+f"(d[38]), "+f"(d[39]), "+f"(d[40]), "+f"(d[41]), "+f"(d[42]), "+f"(d[43]), "+f"(d[44]), "+f"(d[45]), "+f"(d[46]), "+f"(d[47]), "+f"(d[48]), "+f"(d[49]), "+f"(d[50]), "+f"(d[51]), "+f"(d[52]), "+f"(d[53]), "+f"(d[54]), "+f"(d[55]), "+f"(d[56]), "+f"(d[57]), "+f"(d[58]), "+f"(d[59]), "+f"(d[60]), "+f"(d[61]), "+f"(d[62]), "+f"(d[63]), "+f"(d[64]), "+f"(d[65]), "+f"(d[66]), "+f"(d[67]), "+f"(d[68]), "+f"(d[69]), "+f"(d[70]), "+f"(d[71]), "+f"(d[72]), "+f"(d[73]), "+f"(d[74]), "+f"(d[75]), "+f"(d[76]), "+f"(d[77]), "+f"(d[78]), "+f"(d[79]), "+f"(d[80]), "+f"(d[81]), "+f"(d[82]), "+f"(d[83]), "+f"(d[84]), "+f"(d[85]), "+f"(d[86]), "+f"(d[87]), "+f"(d[88]), "+f"(d[89]), "+f"(d[90]), "+f"(d[91]), "+f"(d[92]), "+f"(d[93]), "+f"(d[94]), "+f"(d[95]), "+f"(d[96]), "+f"(d[97]), "+f"(d[98]), "+f"(d[99]), "+f"(d[100]), "+f"(d[101]), "+f"(d[102]), "+f"(d[103]), "+f"(d[104]), "+f"(d[105]), "+f"(d[106]), "+f"(d[107]), "+f"(d[108]), "+f"(d[109]), "+f"(d[110]), "+f"(d[111]), "+f"(d[112]), "+f"(d[113]), "+f"(d[114]), "+f"(d[115]), "+f"(d[116]), "+f"(d[117]), "+f"(d[118]), "+f"(d[119]), "+f"(d[120]), "+f"(d[121]), "+f"(d[122]), "+f"(d[123]), "+f"(d[124]), "+f"(d[125]), "+f"(d[126]), "+f"(d[127])
    : "l"(da), "l"(db), "r"(scaleD));
}

__device__ __forceinline__ void wgmma_m64n128k16(float (&d)[64], uint64_t da, uint64_t db, int scaleD) {
  asm volatile(
    "{\n.reg .pred p;\nsetp.ne.b32 p, %66, 0;\n"
    "wgmma.mma_async.sync.aligned.m64n128k16.f32.bf16.bf16 "
    "{%0, %1, %2, %3, %4, %5, %6, %7, %8, %9, %10, %11, %12, %13, %14, %15, %16, %17, %18, %19, %20, %21, %22, %23, %24, %25, %26, %27, %28, %29, %30, %31, %32, %33, %34, %35, %36, %37, %38, %39, %40, %41, %42, %43, %44, %45, %46, %47, %48, %49, %50, %51, %52, %53, %54, %55, %56, %57, %58, %59, %60, %61, %62, %63}, %64, %65, p, 1, 1, 0, 1;\n}\n"
    : "+f"(d[0]), "+f"(d[1]), "+f"(d[2]), "+f"(d[3]), "+f"(d[4]), "+f"(d[5]), "+f"(d[6]), "+f"(d[7]), "+f"(d[8]), "+f"(d[9]), "+f"(d[10]), "+f"(d[11]), "+f"(d[12]), "+f"(d[13]), "+f"(d[14]), "+f"(d[15]), "+f"(d[16]), "+f"(d[17]), "+f"(d[18]), "+f"(d[19]), "+f"(d[20]), "+f"(d[21]), "+f"(d[22]), "+f"(d[23]), "+f"(d[24]), "+f"(d[25]), "+f"(d[26]), "+f"(d[27]), "+f"(d[28]), "+f"(d[29]), "+f"(d[30]), "+f"(d[31]), "+f"(d[32]), "+f"(d[33]), "+f"(d[34]), "+f"(d[35]), "+f"(d[36]), "+f"(d[37]), "+f"(d[38]), "+f"(d[39]), "+f"(d[40]), "+f"(d[41]), "+f"(d[42]), "+f"(d[43]), "+f"(d[44]), "+f"(d[45]), "+f"(d[46]), "+f"(d[47]), "+f"(d[48]), "+f"(d[49]), "+f"(d[50]), "+f"(d[51]), "+f"(d[52]), "+f"(d[53]), "+f"(d[54]), "+f"(d[55]), "+f"(d[56]), "+f"(d[57]), "+f"(d[58]), "+f"(d[59]), "+f"(d[60]), "+f"(d[61]), "+f"(d[62]), "+f"(d[63])
    : "l"(da), "l"(db), "r"(scaleD));
}

template <int BN> struct WG;
template <> struct WG<256> { static __device__ __forceinline__ void mma(float (&d)[128], uint64_t a, uint64_t b, int s) { wgmma_m64n256k16(d, a, b, s); } };
template <> struct WG<128> { static __device__ __forceinline__ void mma(float (&d)[64], uint64_t a, uint64_t b, int s) { wgmma_m64n128k16(d, a, b, s); } };

__global__ void __launch_bounds__(256) ln_kernel(const bf16* __restrict__ x, const bf16* __restrict__ w_r) {
  int warp = threadIdx.x >> 5, lane = threadIdx.x & 31;
  int row = blockIdx.x * 8 + warp;
  const uint4* xp = reinterpret_cast<const uint4*>(x + (size_t)row * DM);
  uint4 v[4];
#pragma unroll
  for (int i = 0; i < 4; i++) v[i] = xp[lane + 32 * i];
  float f[32];
#pragma unroll
  for (int i = 0; i < 4; i++) {
    f[8 * i + 0] = bflo(v[i].x); f[8 * i + 1] = bfhi(v[i].x);
    f[8 * i + 2] = bflo(v[i].y); f[8 * i + 3] = bfhi(v[i].y);
    f[8 * i + 4] = bflo(v[i].z); f[8 * i + 5] = bfhi(v[i].z);
    f[8 * i + 6] = bflo(v[i].w); f[8 * i + 7] = bfhi(v[i].w);
  }
  float s = 0.f;
#pragma unroll
  for (int i = 0; i < 32; i++) s += f[i];
#pragma unroll
  for (int o = 16; o > 0; o >>= 1) s += __shfl_xor_sync(0xffffffffu, s, o);
  float mean = s * (1.0f / DM);
  float q = 0.f;
#pragma unroll
  for (int i = 0; i < 32; i++) { float d = f[i] - mean; q += d * d; }
#pragma unroll
  for (int o = 16; o > 0; o >>= 1) q += __shfl_xor_sync(0xffffffffu, q, o);
  float var = bfr(q * (1.0f / DM));
  float mb = bfr(mean);
  float den = bfr(sqrtf(bfr(var + 1e-5f)));
  const uint4* wp = reinterpret_cast<const uint4*>(w_r);
  uint4* op = reinterpret_cast<uint4*>(g_xn + (size_t)row * DM);
  float r = 0.f;
#pragma unroll
  for (int i = 0; i < 4; i++) {
    uint4 w = wp[lane + 32 * i];
    float y[8];
#pragma unroll
    for (int k = 0; k < 8; k++) y[k] = bfr(bfr(f[8 * i + k] - mb) / den);
    r += y[0] * bflo(w.x) + y[1] * bfhi(w.x) + y[2] * bflo(w.y) + y[3] * bfhi(w.y) + y[4] * bflo(w.z) + y[5] * bfhi(w.z) +
         y[6] * bflo(w.w) + y[7] * bfhi(w.w);
    op[lane + 32 * i] = make_uint4(pack2(y[0], y[1]), pack2(y[2], y[3]), pack2(y[4], y[5]), pack2(y[6], y[7]));
  }
#pragma unroll
  for (int o = 16; o > 0; o >>= 1) r += __shfl_xor_sync(0xffffffffu, r, o);
  if (lane == 0) g_r[row] = bfr(r);
  int gt = blockIdx.x * 256 + threadIdx.x;
  const uint4 sv = make_uint4(SENT, SENT, SENT, SENT);
  uint4* a = &g_bufA[0][0][0];
  for (int i = gt; i < 2 * 128 * 96; i += 65536) a[i] = sv;
  uint4* b = &g_bufB[0][0][0][0];
  for (int i = gt; i < 2 * 128 * 32 * 16; i += 65536) b[i] = sv;
  uint4* c = &g_bufC[0][0];
  for (int i = gt; i < 2 * 1024; i += 65536) c[i] = sv;
  if (gt == 0) g_moe_cnt = 0;
}

template <int BN, int STAGES>
struct GemmSmem {
  static constexpr int A_BYTES = 128 * 64 * 2;
  static constexpr int B_BYTES = 64 * BN * 2;
  static constexpr int STAGE_BYTES = A_BYTES + B_BYTES;
  static constexpr int TOTAL = STAGES * STAGE_BYTES + 1024 + 256;
};

__device__ __forceinline__ void quad_transpose(uint32_t (&v)[4], int c) {
  {
    uint32_t s0 = (c & 1) ? v[0] : v[1];
    uint32_t s1 = (c & 1) ? v[2] : v[3];
    uint32_t r0 = __shfl_xor_sync(0xffffffffu, s0, 1);
    uint32_t r1 = __shfl_xor_sync(0xffffffffu, s1, 1);
    if (c & 1) { v[0] = r0; v[2] = r1; } else { v[1] = r0; v[3] = r1; }
  }
  {
    uint32_t s0 = (c & 2) ? v[0] : v[2];
    uint32_t s1 = (c & 2) ? v[1] : v[3];
    uint32_t r0 = __shfl_xor_sync(0xffffffffu, s0, 2);
    uint32_t r1 = __shfl_xor_sync(0xffffffffu, s1, 2);
    if (c & 2) { v[0] = r0; v[1] = r1; } else { v[2] = r0; v[3] = r1; }
  }
}

__device__ __forceinline__ uint32_t add3(uint32_t a, uint32_t x, uint32_t b) {
  float lo = bfr(bflo(x) + bflo(a)) + bflo(b);
  float hi = bfr(bfhi(x) + bfhi(a)) + bfhi(b);
  return pack2(lo, hi);
}

template <int BN, int STAGES, int EPI>
__global__ void __launch_bounds__(288, 1)
gemm_kernel(const __grid_constant__ CUtensorMap tmA, const __grid_constant__ CUtensorMap tmB0,
            const __grid_constant__ CUtensorMap tmB1, const __grid_constant__ CUtensorMap tmB2,
            int kblocks, int tiles_m, int tiles_total, const bf16* __restrict__ xin, bf16* __restrict__ outp) {
  using SM = GemmSmem<BN, STAGES>;
  extern __shared__ uint8_t smem_raw[];
  uint32_t base = (smem_u32(smem_raw) + 1023) & ~1023u;
  uint32_t bars = base + STAGES * SM::STAGE_BYTES;
  int warp = threadIdx.x >> 5, lane = threadIdx.x & 31;
  if (threadIdx.x == 0) {
    for (int i = 0; i < STAGES; i++) { mbar_init(bars + 8 * i, 1); mbar_init(bars + 8 * (STAGES + i), 8); }
    asm volatile("fence.mbarrier_init.release.cluster;" ::: "memory");
  }
  __syncthreads();
  if (warp == 8) {
    if (lane == 0) {
      int it = 0;
      for (int t = blockIdx.x; t < tiles_total; t += gridDim.x) {
        int tm = t % tiles_m, tn = t / tiles_m;
        int n0 = tn * BN;
        const CUtensorMap* tb = &tmB0;
        if (EPI == 0) { int wsel = n0 >> 12; tb = wsel == 0 ? &tmB0 : (wsel == 1 ? &tmB1 : &tmB2); n0 &= 4095; }
        for (int kb = 0; kb < kblocks; kb++, it++) {
          int st = it % STAGES; uint32_t ph = (it / STAGES) & 1;
          mbar_wait(bars + 8 * (STAGES + st), ph ^ 1);
          uint32_t sa = base + st * SM::STAGE_BYTES, sb = sa + SM::A_BYTES;
          mbar_expect_tx(bars + 8 * st, SM::STAGE_BYTES);
          tma_load2d(sa, &tmA, bars + 8 * st, kb * 64, tm * 128);
#pragma unroll
          for (int i = 0; i < BN / 64; i++) tma_load2d(sb + i * 8192, tb, bars + 8 * st, n0 + i * 64, kb * 64);
        }
      }
    }
  } else {
    int wg = warp >> 2;
    int g = lane >> 2, c = lane & 3;
    int it = 0;
    float acc[BN / 2];
    for (int t = blockIdx.x; t < tiles_total; t += gridDim.x) {
      int tm = t % tiles_m, tn = t / tiles_m;
      for (int kb = 0; kb < kblocks; kb++, it++) {
        int st = it % STAGES; uint32_t ph = (it / STAGES) & 1;
        mbar_wait(bars + 8 * st, ph);
        uint32_t sa = base + st * SM::STAGE_BYTES + wg * 8192, sb = base + st * SM::STAGE_BYTES + SM::A_BYTES;
        wg_fence();
#pragma unroll
        for (int kk = 0; kk < 4; kk++) {
          uint64_t da = make_desc(sa + kk * 32, 16, 1024);
          uint64_t db = make_desc(sb + kk * 2048, 8192, 1024);
          WG<BN>::mma(acc, da, db, (kb | kk) != 0);
        }
        wg_commit();
        if (kb > 0) {
          wg_wait<1>();
          int pst = (it - 1) % STAGES;
          if (lane == 0) mbar_arrive(bars + 8 * (STAGES + pst));
        }
      }
      wg_wait<0>();
      { int pst = (it - 1) % STAGES; if (lane == 0) mbar_arrive(bars + 8 * (STAGES + pst)); }
      int row0 = tm * 128 + wg * 64 + (warp & 3) * 16 + g;
      int sel0 = -1, sel1 = -1;
      if (EPI == 1) { sel0 = g_sel[0]; sel1 = g_sel[1]; }
#pragma unroll
      for (int half = 0; half < 2; half++) {
        int row = row0 + half * 8;
#pragma unroll
        for (int q = 0; q < BN / 32; q++) {
          uint32_t v[4];
#pragma unroll
          for (int tt = 0; tt < 4; tt++) v[tt] = pack2(acc[(q * 4 + tt) * 4 + half * 2], acc[(q * 4 + tt) * 4 + half * 2 + 1]);
          quad_transpose(v, c);
          int col = tn * BN + q * 32 + c * 8;
          if (EPI == 0) {
            *reinterpret_cast<uint4*>(outp + (size_t)row * NQKV + col) = make_uint4(v[0], v[1], v[2], v[3]);
          } else {
            uint4 xv = *reinterpret_cast<const uint4*>(xin + (size_t)row * DM + col);
            uint4 bv = *reinterpret_cast<const uint4*>(g_xn + (size_t)row * DM + col);
            if (row == sel0 || row == sel1) {
              const float* u = &g_upd[row == sel0 ? 0 : 1][col];
              bv.x = pack2(bflo(bv.x) + u[0], bfhi(bv.x) + u[1]);
              bv.y = pack2(bflo(bv.y) + u[2], bfhi(bv.y) + u[3]);
              bv.z = pack2(bflo(bv.z) + u[4], bfhi(bv.z) + u[5]);
              bv.w = pack2(bflo(bv.w) + u[6], bfhi(bv.w) + u[7]);
            }
            uint4 o = make_uint4(add3(v[0], xv.x, bv.x), add3(v[1], xv.y, bv.y), add3(v[2], xv.z, bv.z), add3(v[3], xv.w, bv.w));
            *reinterpret_cast<uint4*>(outp + (size_t)row * DM + col) = o;
          }
        }
      }
    }
  }
}

#define RK 10
#define SK (16 - RK)
#define TP 272
#define OFF_WQS 0
#define OFF_MEMT (OFF_WQS + 8 * SK * 3 * 512)
#define OFF_RED (OFF_MEMT + 16384)
#define OFF_QKVM (OFF_RED + 12288)
#define OFF_TOK (OFF_QKVM + 6144)
#define TOK_BYTES (72 * TP)
#define OFF_SA (OFF_TOK + 2 * TOK_BYTES)
#define OFF_BAR (OFF_SA + 8 * TP)
#define CH_END (OFF_BAR + 64)
#define CH_STG2 (131072)
#define CH_SMEM (196608 + 1024)
static_assert(CH_END <= CH_SMEM, "smem");

__device__ void moe_part(int m, const bf16* __restrict__ wg, const bf16* __restrict__ wu, const bf16* __restrict__ wd, uint8_t* smem);

__device__ __forceinline__ void bulk_copy(uint32_t dst, const void* src, uint32_t bytes, uint32_t bar) {
  asm volatile("cp.async.bulk.shared::cluster.global.mbarrier::complete_tx::bytes [%0],[%1],%2,[%3];"
               ::"r"(dst), "l"(src), "r"(bytes), "r"(bar) : "memory");
}
__device__ __forceinline__ void st_pub128(void* p, uint32_t v) {
  asm volatile("st.relaxed.gpu.global.v4.u32 [%0],{%1,%1,%1,%1};" ::"l"(p), "r"(v) : "memory");
}
__device__ __forceinline__ void sts128(uint32_t addr, const uint4& v) {
  asm volatile("st.shared.v4.u32 [%0],{%1,%2,%3,%4};" ::"r"(addr), "r"(v.x), "r"(v.y), "r"(v.z), "r"(v.w) : "memory");
}

#define POLL_MAX (1 << 22)

template <bool TOK>
__device__ __forceinline__ void attn8(uint32_t sb, uint32_t tok, int lane, int wq4, int tr, bf16* otok_row) {
  const int g = lane >> 2, c = lane & 3;
  float sc[5][4];
#pragma unroll
  for (int n = 0; n < 5; n++)
#pragma unroll
    for (int i = 0; i < 4; i++) sc[n][i] = 0.f;
  const uint32_t tokrow = tok + (lane & 7) * TP + (lane >> 3) * 16;
#pragma unroll
  for (int kp = 0; kp < 4; kp++) {
    uint32_t q[4], km[4], kt[4][4];
    if (TOK) ldsm4(q[0], q[1], q[2], q[3], tokrow + 64 * TP + 64 * kp);
    else ldsm4t(q[0], q[1], q[2], q[3], sb + OFF_QKVM + (32 * kp + lane) * 16);
    ldsm4t(km[0], km[1], km[2], km[3], sb + OFF_QKVM + (128 + 32 * kp + lane) * 16);
#pragma unroll
    for (int n = 0; n < 4; n++) ldsm4(kt[n][0], kt[n][1], kt[n][2], kt[n][3], tokrow + 8 * n * TP + 64 * kp);
    mma16816(sc[0], q[0], 0u, q[1], 0u, km[0], km[1]);
#pragma unroll
    for (int n = 0; n < 4; n++) mma16816(sc[n + 1], q[0], 0u, q[1], 0u, kt[n][0], kt[n][1]);
    mma16816(sc[0], q[2], 0u, q[3], 0u, km[2], km[3]);
#pragma unroll
    for (int n = 0; n < 4; n++) mma16816(sc[n + 1], q[2], 0u, q[3], 0u, kt[n][2], kt[n][3]);
  }
  uint32_t vm[4], vt[4][4];
  ldsm4(vm[0], vm[1], vm[2], vm[3], sb + OFF_QKVM + (256 + 32 * wq4 + lane) * 16);
#pragma unroll
  for (int n = 0; n < 4; n++) ldsm4t(vt[n][0], vt[n][1], vt[n][2], vt[n][3], tok + (32 + lane) * TP + (32 * wq4 + 8 * n) * 2);
  const float scale = 0.08838834764831845f;
  float m0 = -3.0e38f;
#pragma unroll
  for (int n = 0; n < 5; n++) {
    sc[n][0] = bfr(bfr(sc[n][0]) * scale);
    sc[n][1] = bfr(bfr(sc[n][1]) * scale);
    if (TOK && n > 0) {
      int kt = 8 * (n - 1) + 2 * c;
      if (kt > tr) sc[n][0] = -1.0e9f;
      if (kt + 1 > tr) sc[n][1] = -1.0e9f;
    }
    m0 = fmaxf(m0, fmaxf(sc[n][0], sc[n][1]));
  }
  m0 = fmaxf(m0, __shfl_xor_sync(0xffffffffu, m0, 1));
  m0 = fmaxf(m0, __shfl_xor_sync(0xffffffffu, m0, 2));
  float s0 = 0.f;
#pragma unroll
  for (int n = 0; n < 5; n++) {
    sc[n][0] = __expf(sc[n][0] - m0);
    sc[n][1] = __expf(sc[n][1] - m0);
    s0 += sc[n][0] + sc[n][1];
  }
  s0 += __shfl_xor_sync(0xffffffffu, s0, 1);
  s0 += __shfl_xor_sync(0xffffffffu, s0, 2);
  const float i0 = 1.0f / s0;
  uint32_t pa[5];
#pragma unroll
  for (int n = 0; n < 5; n++) pa[n] = pack2(sc[n][0] * i0, sc[n][1] * i0);
#pragma unroll
  for (int n = 0; n < 4; n++) {
    float o[4] = {0.f, 0.f, 0.f, 0.f};
    mma16816(o, pa[0], 0u, pa[1], 0u, vm[n], vt[n][0]);
    mma16816(o, pa[2], 0u, pa[3], 0u, vt[n][1], vt[n][2]);
    mma16816(o, pa[4], 0u, 0u, 0u, vt[n][3], 0u);
    const int e = 32 * wq4 + 8 * n + 2 * c;
    if (TOK) *reinterpret_cast<uint32_t*>(otok_row + e) = pack2(o[0], o[1]);
    else asm volatile("st.shared.u32 [%0],%1;" ::"r"(sb + OFF_SA + g * TP + e * 2), "r"(pack2(o[0], o[1])) : "memory");
  }
}

__global__ void __launch_bounds__(256, 1)
chain_kernel(const bf16* __restrict__ mem0, const bf16* __restrict__ Wq, const bf16* __restrict__ Wk, const bf16* __restrict__ Wv,
             const bf16* __restrict__ Wo, const bf16* __restrict__ wgate, const bf16* __restrict__ wup, const bf16* __restrict__ wdown) {
  extern __shared__ __align__(1024) uint8_t smem[];
  const int cta = blockIdx.x, t = threadIdx.x, warp = t >> 5, lane = t & 31;
  if (cta >= 128) {
    moe_part(cta - 128, wgate, wup, wdown, smem);
    return;
  }
  const int h = cta >> 2, j = cta & 3;
  const int g = lane >> 2, c = lane & 3;
  const uint32_t sb = smem_u32(smem);
  const int mg = warp & 1, kq = warp >> 1;

  uint32_t wq[RK][3][4];
  uint32_t wo[2][8][4];
  {
    for (int i = t; i < 3 * 1024 * 4; i += 256) {
      int which = i >> 12, k = (i >> 2) & 1023, ch = i & 3;
      const bf16* W = which == 0 ? Wq : (which == 1 ? Wk : Wv);
      cp_async16(sb + (which * 1024 + k) * 64 + ch * 16, W + (size_t)k * HD + h * 128 + 32 * j + ch * 8);
    }
    cp_commit(); cp_wait<0>();
    __syncthreads();
    uint32_t tmp[SK][3][4];
#pragma unroll
    for (int ks = 0; ks < 16; ks++) {
#pragma unroll
      for (int tt = 0; tt < 3; tt++) {
        int tile = 3 * mg + tt;
        int which = tile >> 1, ch = tile & 1;
        int k = (16 * kq + ks) * 16 + (lane & 7) + 8 * (lane >> 4);
        uint32_t addr = sb + (which * 1024 + k) * 64 + ch * 32 + 16 * ((lane >> 3) & 1);
        if (ks < RK) ldsm4t(wq[ks][tt][0], wq[ks][tt][1], wq[ks][tt][2], wq[ks][tt][3], addr);
        else ldsm4t(tmp[ks - RK][tt][0], tmp[ks - RK][tt][1], tmp[ks - RK][tt][2], tmp[ks - RK][tt][3], addr);
      }
    }
    __syncthreads();
#pragma unroll
    for (int ks = 0; ks < SK; ks++)
#pragma unroll
      for (int tt = 0; tt < 3; tt++)
        *reinterpret_cast<uint4*>(smem + OFF_WQS + (((warp * SK + ks) * 3 + tt) * 32 + lane) * 16) =
            make_uint4(tmp[ks][tt][0], tmp[ks][tt][1], tmp[ks][tt][2], tmp[ks][tt][3]);
    for (int i = t; i < 128 * 32; i += 256) {
      int e = i >> 5, ch = i & 31;
      cp_async16(sb + CH_STG2 + e * 512 + ch * 16, Wo + (size_t)(h * 128 + e) * DM + 256 * j + ch * 8);
    }
    cp_commit(); cp_wait<0>();
    __syncthreads();
#pragma unroll
    for (int tt = 0; tt < 2; tt++)
#pragma unroll
      for (int ks = 0; ks < 8; ks++) {
        int e = 16 * ks + (lane & 7) + 8 * (lane >> 4);
        uint32_t addr = sb + CH_STG2 + e * 512 + (32 * warp + 16 * tt + 8 * ((lane >> 3) & 1)) * 2;
        ldsm4t(wo[tt][ks][0], wo[tt][ks][1], wo[tt][ks][2], wo[tt][ks][3], addr);
      }
    if (t == 0) {
      mbar_init(sb + OFF_BAR, 1); mbar_init(sb + OFF_BAR + 8, 1);
      asm volatile("fence.mbarrier_init.release.cluster;" ::: "memory");
    }
    __syncthreads();
    asm volatile("fence.proxy.async.shared::cta;" ::: "memory");
  }
  auto prefetch_tok = [&](int s) {
    const int i = t - 192;
    const uint32_t bar = sb + OFF_BAR + 8 * (s & 1);
    const uint32_t dst = sb + OFF_TOK + (s & 1) * TOK_BYTES;
    if (i == 0) mbar_expect_tx(bar, 72 * 256);
    const bf16* src = g_qkv + (size_t)(s * 32 + (i & 31)) * NQKV + (i < 32 ? HD : 2 * HD) + h * 128;
    bulk_copy(dst + i * TP, src, 256, bar);
    if (i < 8) bulk_copy(dst + (64 + i) * TP, g_qkv + (size_t)(s * 32 + 8 * j + i) * NQKV + h * 128, 256, bar);
  };
  if (warp >= 6) prefetch_tok(0);
  for (int i = t; i < 8 * 1024; i += 256) {
    int r = i >> 10, k = i & 1023;
    reinterpret_cast<bf16*>(smem + OFF_MEMT)[k * 8 + r] = mem0[i];
  }
  __syncthreads();
  uint32_t p2dst0, p2dst1;
  {
    int p = t, jj = p / 96, f = p % 96;
    p2dst0 = sb + OFF_QKVM + ((f >> 5) * 128 + 32 * jj + (f & 31)) * 16;
    p = 256 + (t & 127); jj = p / 96; f = p % 96;
    p2dst1 = sb + OFF_QKVM + ((f >> 5) * 128 + 32 * jj + (f & 31)) * 16;
  }
  const int p0idx = 256 * kq + 128 * mg + lane;
  TS(0);
  for (int s = 0; s < NSEG; s++) {
    const int slot = s & 3, slot2 = (s + 2) & 3;
    if (s > 0) {
      const uint4* src = &g_bufC[(s - 1) & 3][p0idx];
      uint4 v[4];
#pragma unroll
      for (int i = 0; i < 4; i++) v[i] = ld_poll(src + 32 * i);
      int it = 0;
      while (!(pkt_ok(v[0]) && pkt_ok(v[1]) && pkt_ok(v[2]) && pkt_ok(v[3])) && ++it < POLL_MAX) {
#pragma unroll
        for (int i = 0; i < 4; i++)
          if (!pkt_ok(v[i])) v[i] = ld_poll(src + 32 * i);
      }
#pragma unroll
      for (int i = 0; i < 4; i++) sts128(sb + OFF_MEMT + (p0idx + 32 * i) * 16, v[i]);
      TS(1);
      asm volatile("bar.sync %0, 64;" ::"r"(1 + kq) : "memory");
      TS(2);
    }
    {
      float acc[2][3][4];
#pragma unroll
      for (int a = 0; a < 2; a++)
#pragma unroll
        for (int tt = 0; tt < 3; tt++)
#pragma unroll
          for (int i = 0; i < 4; i++) acc[a][tt][i] = 0.f;
      uint4 sa[SK][3];
#pragma unroll
      for (int kp = 0; kp < 8; kp++) {
        uint32_t b0, b1, b2, b3;
        ldsm4t(b0, b1, b2, b3, sb + OFF_MEMT + ((16 * kq + 2 * kp) * 16 + lane) * 16);
#pragma unroll
        for (int u = 0; u < 2; u++) {
          int ks = 2 * (kp + 1) + u;
          if (ks >= RK && ks < 16) {
#pragma unroll
            for (int tt = 0; tt < 3; tt++)
              sa[ks - RK][tt] = *reinterpret_cast<const uint4*>(smem + OFF_WQS + (((warp * SK + (ks - RK)) * 3 + tt) * 32 + lane) * 16);
          }
        }
#pragma unroll
        for (int u = 0; u < 2; u++) {
          int ks = 2 * kp + u;
#pragma unroll
          for (int tt = 0; tt < 3; tt++) {
            if (ks < RK) mma16816(acc[u][tt], wq[ks][tt][0], wq[ks][tt][1], wq[ks][tt][2], wq[ks][tt][3], u ? b2 : b0, u ? b3 : b1);
            else mma16816(acc[u][tt], sa[ks - RK][tt].x, sa[ks - RK][tt].y, sa[ks - RK][tt].z, sa[ks - RK][tt].w, u ? b2 : b0, u ? b3 : b1);
          }
        }
      }
#pragma unroll
      for (int tt = 0; tt < 3; tt++)
        *reinterpret_cast<float4*>(smem + OFF_RED + ((kq * 6 + 3 * mg + tt) * 32 + lane) * 16) =
            make_float4(acc[0][tt][0] + acc[1][tt][0], acc[0][tt][1] + acc[1][tt][1], acc[0][tt][2] + acc[1][tt][2], acc[0][tt][3] + acc[1][tt][3]);
    }
    TS(3);
    __syncthreads();
    TS(4);
    if (warp < 6) {
      float4 r = *reinterpret_cast<const float4*>(smem + OFF_RED + ((0 * 6 + warp) * 32 + lane) * 16);
#pragma unroll
      for (int q = 1; q < 4; q++) {
        float4 x = *reinterpret_cast<const float4*>(smem + OFF_RED + ((q * 6 + warp) * 32 + lane) * 16);
        r.x += x.x; r.y += x.y; r.z += x.z; r.w += x.w;
      }
      uint32_t* dst = reinterpret_cast<uint32_t*>(&g_bufA[slot][cta][16 * warp + g]) + c;
      st_pub32(dst, desent(pack2(r.x, r.y)));
      st_pub32(dst + 32, desent(pack2(r.z, r.w)));
    } else {
      const int i = t - 192;
      st_pub128(&g_bufA[slot2][cta][i], SENT);
      if (i < 32) st_pub128(&g_bufA[slot2][cta][64 + i], SENT);
      if (s + 1 < NSEG) prefetch_tok(s + 1);
    }
    {
      const uint4* src = &g_bufA[slot][4 * h][t];
      uint4 v0 = ld_poll(src);
      uint4 v1 = make_uint4(0, 0, 0, 0);
      if (t < 128) v1 = ld_poll(src + 256);
      int it = 0;
      while (!(pkt_ok(v0) && pkt_ok(v1)) && ++it < POLL_MAX) {
        if (!pkt_ok(v0)) v0 = ld_poll(src);
        if (!pkt_ok(v1)) v1 = ld_poll(src + 256);
      }
      sts128(p2dst0, v0);
      if (t < 128) sts128(p2dst1, v1);
    }
    TS(5);
    mbar_wait(sb + OFF_BAR + 8 * (s & 1), (s >> 1) & 1);
    __syncthreads();
    TS(6);
    const uint32_t tok = sb + OFF_TOK + (s & 1) * TOK_BYTES;
    if (s < NSEG - 1) {
      if (warp < 4) attn8<false>(sb, tok, lane, warp, 0, nullptr);
      TS(7);
      __syncthreads();
      TS(8);
      {
        float acc[2][2][4];
#pragma unroll
        for (int a = 0; a < 2; a++)
#pragma unroll
          for (int tt = 0; tt < 2; tt++)
#pragma unroll
            for (int i = 0; i < 4; i++) acc[a][tt][i] = 0.f;
        uint32_t b[4][4];
#pragma unroll
        for (int kp = 0; kp < 4; kp++) ldsm4(b[kp][0], b[kp][1], b[kp][2], b[kp][3], sb + OFF_SA + (lane & 7) * TP + (32 * kp + 8 * (lane >> 3)) * 2);
#pragma unroll
        for (int kp = 0; kp < 4; kp++) {
#pragma unroll
          for (int tt = 0; tt < 2; tt++) {
            mma16816(acc[0][tt], wo[tt][2 * kp][0], wo[tt][2 * kp][1], wo[tt][2 * kp][2], wo[tt][2 * kp][3], b[kp][0], b[kp][1]);
            mma16816(acc[1][tt], wo[tt][2 * kp + 1][0], wo[tt][2 * kp + 1][1], wo[tt][2 * kp + 1][2], wo[tt][2 * kp + 1][3], b[kp][2], b[kp][3]);
          }
        }
        const int off = ((2 * g + (c >> 1)) * 32 + h) * 2 + (c & 1);
#pragma unroll
        for (int tt = 0; tt < 2; tt++) {
          int r0 = 32 * j + 4 * warp + 2 * tt;
          uint32_t x0 = __float_as_uint(acc[0][tt][0] + acc[1][tt][0]), x1 = __float_as_uint(acc[0][tt][1] + acc[1][tt][1]);
          uint32_t x2 = __float_as_uint(acc[0][tt][2] + acc[1][tt][2]), x3 = __float_as_uint(acc[0][tt][3] + acc[1][tt][3]);
          x0 = x0 == SENT ? 0x7FFFFFFFu : x0; x1 = x1 == SENT ? 0x7FFFFFFFu : x1;
          x2 = x2 == SENT ? 0x7FFFFFFFu : x2; x3 = x3 == SENT ? 0x7FFFFFFFu : x3;
          st_pub64(reinterpret_cast<uint2*>(&g_bufB[slot][r0][0][0]) + off, x0, x1);
          st_pub64(reinterpret_cast<uint2*>(&g_bufB[slot][r0 + 1][0][0]) + off, x2, x3);
        }
#pragma unroll
        for (int tt = 0; tt < 4; tt++)
          st_pub64(reinterpret_cast<uint2*>(&g_bufB[slot2][32 * j + 4 * warp + tt][0][0]) + off, SENT, SENT);
      }
      TS(9);
      {
        const uint4* src = &g_bufB[slot][cta][0][0] + 64 * warp + lane;
        uint4 v0 = ld_poll(src), v1 = ld_poll(src + 32);
        int it = 0;
        while (!(pkt_ok(v0) && pkt_ok(v1)) && ++it < POLL_MAX) {
          if (!pkt_ok(v0)) v0 = ld_poll(src);
          if (!pkt_ok(v1)) v1 = ld_poll(src + 32);
        }
        TS(10);
        const bool hi = lane & 16;
        float a0 = __uint_as_float(hi ? v1.x : v0.x), a1 = __uint_as_float(hi ? v1.y : v0.y);
        float a2 = __uint_as_float(hi ? v1.z : v0.z), a3 = __uint_as_float(hi ? v1.w : v0.w);
        float b0 = __uint_as_float(hi ? v0.x : v1.x), b1 = __uint_as_float(hi ? v0.y : v1.y);
        float b2 = __uint_as_float(hi ? v0.z : v1.z), b3 = __uint_as_float(hi ? v0.w : v1.w);
        a0 += __shfl_xor_sync(0xffffffffu, b0, 16); a1 += __shfl_xor_sync(0xffffffffu, b1, 16);
        a2 += __shfl_xor_sync(0xffffffffu, b2, 16); a3 += __shfl_xor_sync(0xffffffffu, b3, 16);
        const bool h8 = lane & 8;
        float k0 = h8 ? a2 : a0, k1 = h8 ? a3 : a1, s0 = h8 ? a0 : a2, s1 = h8 ? a1 : a3;
        k0 += __shfl_xor_sync(0xffffffffu, s0, 8); k1 += __shfl_xor_sync(0xffffffffu, s1, 8);
        const bool h4 = lane & 4;
        float z = h4 ? k1 : k0, zs = h4 ? k0 : k1;
        z += __shfl_xor_sync(0xffffffffu, zs, 4);
        z += __shfl_xor_sync(0xffffffffu, z, 2);
        z += __shfl_xor_sync(0xffffffffu, z, 1);
        float zo = __shfl_xor_sync(0xffffffffu, z, 4);
        if ((lane & 7) == 0) {
          uint32_t* d = reinterpret_cast<uint32_t*>(&g_bufC[slot][8 * cta + warp]) + (lane >> 3);
          st_pub32(d, desent(pack2(z, zo)));
          st_pub32(reinterpret_cast<uint32_t*>(&g_bufC[slot2][8 * cta + warp]) + (lane >> 3), SENT);
        }
      }
    }
    if (warp >= 4) attn8<true>(sb, tok, lane, warp - 4, 8 * j + g, g_otok + (size_t)(s * 32 + 8 * j + g) * HD + h * 128);
    TS(11);
  }
}

__device__ void moe_part(int m, const bf16* __restrict__ wg, const bf16* __restrict__ wu, const bf16* __restrict__ wd, uint8_t* smem) {
  const int t = threadIdx.x, warp = t >> 5, lane = t & 31;
  float* xs = reinterpret_cast<float*>(smem);
  float* red = reinterpret_cast<float*>(smem + 8192);
  float* hs = reinterpret_cast<float*>(smem + 65536);
  __shared__ float bv[8];
  __shared__ int bi[8];
  __shared__ int sel[2];
  int first = -1;
  for (int pass = 0; pass < 2; pass++) {
    float best = -INFINITY; int bidx = 0x7fffffff;
    for (int i = t; i < S_LEN; i += 256) {
      float v = g_r[i];
      if (i == first) continue;
      if (v > best || (v == best && i < bidx) || bidx == 0x7fffffff) { best = v; bidx = i; }
    }
#pragma unroll
    for (int o = 16; o > 0; o >>= 1) {
      float ov = __shfl_xor_sync(0xffffffffu, best, o); int oi = __shfl_xor_sync(0xffffffffu, bidx, o);
      if (oi != 0x7fffffff && (bidx == 0x7fffffff || ov > best || (ov == best && oi < bidx))) { best = ov; bidx = oi; }
    }
    if (lane == 0) { bv[warp] = best; bi[warp] = bidx; }
    __syncthreads();
    if (t == 0) {
      float b = bv[0]; int ix = bi[0];
      for (int w = 1; w < 8; w++) if (bv[w] > b || (bv[w] == b && bi[w] < ix)) { b = bv[w]; ix = bi[w]; }
      sel[pass] = ix;
    }
    __syncthreads();
    first = sel[0];
  }
  const int s0 = sel[0], s1 = sel[1];
  for (int i = t; i < 2048; i += 256) xs[i] = __bfloat162float(g_xn[(size_t)(i < 1024 ? s0 : s1) * DM + (i & 1023)]);
  __syncthreads();
  {
    int cg = t % 112, kh = t / 112;
    float a[2][2][8];
#pragma unroll
    for (int i = 0; i < 8; i++) { a[0][0][i] = a[0][1][i] = a[1][0][i] = a[1][1][i] = 0.f; }
    if (kh < 2) {
      const bf16* pg = wg + (size_t)(kh * 512) * FF + 896 * m + cg * 8;
      const bf16* pu = wu + (size_t)(kh * 512) * FF + 896 * m + cg * 8;
#pragma unroll 8
      for (int k = 0; k < 512; k++) {
        uint4 gv = __ldg(reinterpret_cast<const uint4*>(pg + (size_t)k * FF));
        uint4 uv = __ldg(reinterpret_cast<const uint4*>(pu + (size_t)k * FF));
        float x0 = xs[kh * 512 + k], x1 = xs[1024 + kh * 512 + k];
        float gf[8] = {bflo(gv.x), bfhi(gv.x), bflo(gv.y), bfhi(gv.y), bflo(gv.z), bfhi(gv.z), bflo(gv.w), bfhi(gv.w)};
        float uf[8] = {bflo(uv.x), bfhi(uv.x), bflo(uv.y), bfhi(uv.y), bflo(uv.z), bfhi(uv.z), bflo(uv.w), bfhi(uv.w)};
#pragma unroll
        for (int i = 0; i < 8; i++) {
          a[0][0][i] += x0 * gf[i]; a[0][1][i] += x1 * gf[i];
          a[1][0][i] += x0 * uf[i]; a[1][1][i] += x1 * uf[i];
        }
      }
      if (kh == 1) {
#pragma unroll
        for (int i = 0; i < 8; i++) {
          red[(0 * 2 + 0) * 896 + cg * 8 + i] = a[0][0][i]; red[(0 * 2 + 1) * 896 + cg * 8 + i] = a[0][1][i];
          red[(1 * 2 + 0) * 896 + cg * 8 + i] = a[1][0][i]; red[(1 * 2 + 1) * 896 + cg * 8 + i] = a[1][1][i];
        }
      }
    }
    __syncthreads();
    if (kh == 0) {
#pragma unroll
      for (int i = 0; i < 8; i++) {
#pragma unroll
        for (int tk = 0; tk < 2; tk++) {
          float gq = bfr(a[0][tk][i] + red[(0 * 2 + tk) * 896 + cg * 8 + i]);
          float uq = bfr(a[1][tk][i] + red[(1 * 2 + tk) * 896 + cg * 8 + i]);
          float sg = bfr(gq / (1.0f + __expf(-gq)));
          g_h[tk][896 * m + cg * 8 + i] = __float2bfloat16_rn(sg * uq);
        }
      }
    }
    __threadfence();
    __syncthreads();
    if (t == 0) {
      atomicAdd(&g_moe_cnt, 1u);
      int it = 0;
      while (*reinterpret_cast<volatile unsigned*>(&g_moe_cnt) < 4u && ++it < (1 << 24)) {}
      __threadfence();
    }
    __syncthreads();
  }
  for (int i = t; i < 2 * FF; i += 256) {
    const volatile unsigned short* p = reinterpret_cast<const volatile unsigned short*>(&g_h[0][0]);
    hs[i] = __uint_as_float(((uint32_t)p[i]) << 16);
  }
  __syncthreads();
  {
    int cg = t & 31, ksl = t >> 5;
    float a[2][8];
#pragma unroll
    for (int i = 0; i < 8; i++) a[0][i] = a[1][i] = 0.f;
    const bf16* pd = wd + (size_t)(ksl * 448) * DM + 256 * m + cg * 8;
#pragma unroll 8
    for (int k = 0; k < 448; k++) {
      uint4 dv = __ldg(reinterpret_cast<const uint4*>(pd + (size_t)k * DM));
      float x0 = hs[ksl * 448 + k], x1 = hs[FF + ksl * 448 + k];
      float df[8] = {bflo(dv.x), bfhi(dv.x), bflo(dv.y), bfhi(dv.y), bflo(dv.z), bfhi(dv.z), bflo(dv.w), bfhi(dv.w)};
#pragma unroll
      for (int i = 0; i < 8; i++) { a[0][i] += x0 * df[i]; a[1][i] += x1 * df[i]; }
    }
#pragma unroll
    for (int i = 0; i < 8; i++) { red[(ksl * 2 + 0) * 256 + cg * 8 + i] = a[0][i]; red[(ksl * 2 + 1) * 256 + cg * 8 + i] = a[1][i]; }
    __syncthreads();
    for (int i = t; i < 512; i += 256) {
      int tk = i >> 8, col = i & 255;
      float y = 0.f;
#pragma unroll
      for (int q = 0; q < 8; q++) y += red[(q * 2 + tk) * 256 + col];
      float rr = g_r[tk == 0 ? s0 : s1];
      float sg = bfr(1.0f / (1.0f + __expf(-rr)));
      g_upd[tk][256 * m + col] = bfr(bfr(y) * sg);
    }
    if (m == 0 && t == 0) { g_sel[0] = s0; g_sel[1] = s1; }
  }
}

typedef CUresult (*EncodeFn)(CUtensorMap*, CUtensorMapDataType, cuuint32_t, void*, const cuuint64_t*, const cuuint64_t*,
                             const cuuint32_t*, const cuuint32_t*, CUtensorMapInterleave, CUtensorMapSwizzle,
                             CUtensorMapL2promotion, CUtensorMapFloatOOBfill);

static void make_map(EncodeFn enc, CUtensorMap* m, const void* ptr, uint64_t inner, uint64_t outer, uint32_t bi, uint32_t bo) {
  cuuint64_t dims[2] = {inner, outer};
  cuuint64_t strides[1] = {inner * 2};
  cuuint32_t box[2] = {bi, bo};
  cuuint32_t es[2] = {1, 1};
  enc(m, CU_TENSOR_MAP_DATA_TYPE_BFLOAT16, 2, const_cast<void*>(ptr), dims, strides, box, es, CU_TENSOR_MAP_INTERLEAVE_NONE,
      CU_TENSOR_MAP_SWIZZLE_128B, CU_TENSOR_MAP_L2_PROMOTION_L2_256B, CU_TENSOR_MAP_FLOAT_OOB_FILL_NONE);
}

extern "C" void kernel_launch(void* const* d_in, const int* in_sizes, int n_in, void* d_out, int out_size) {
  const bf16* x = (const bf16*)d_in[0];
  const bf16* mem0 = (const bf16*)d_in[1];
  const bf16* Wq = (const bf16*)d_in[2];
  const bf16* Wk = (const bf16*)d_in[3];
  const bf16* Wv = (const bf16*)d_in[4];
  const bf16* Wo = (const bf16*)d_in[5];
  const bf16* w_r = (const bf16*)d_in[8];
  const bf16* wg = (const bf16*)d_in[9];
  const bf16* wu = (const bf16*)d_in[10];
  const bf16* wd = (const bf16*)d_in[11];
  bf16* out = (bf16*)d_out;

  static EncodeFn enc = nullptr;
  static void *p_xn, *p_qkv, *p_otok;
  if (!enc) {
    cudaDriverEntryPointQueryResult qr;
    void* fn = nullptr;
    cudaGetDriverEntryPoint("cuTensorMapEncodeTiled", &fn, cudaEnableDefault, &qr);
    enc = (EncodeFn)fn;
    cudaGetSymbolAddress(&p_xn, g_xn);
    cudaGetSymbolAddress(&p_qkv, g_qkv);
    cudaGetSymbolAddress(&p_otok, g_otok);
    cudaFuncSetAttribute(gemm_kernel<256, 4, 0>, cudaFuncAttributeMaxDynamicSharedMemorySize, GemmSmem<256, 4>::TOTAL);
    cudaFuncSetAttribute(gemm_kernel<128, 6, 1>, cudaFuncAttributeMaxDynamicSharedMemorySize, GemmSmem<128, 6>::TOTAL);
    cudaFuncSetAttribute(chain_kernel, cudaFuncAttributeMaxDynamicSharedMemorySize, CH_SMEM);
  }
  CUtensorMap mA, mQ, mK, mV, mO, mWo;
  make_map(enc, &mA, p_xn, DM, S_LEN, 64, 128);
  make_map(enc, &mQ, Wq, HD, DM, 64, 64);
  make_map(enc, &mK, Wk, HD, DM, 64, 64);
  make_map(enc, &mV, Wv, HD, DM, 64, 64);
  make_map(enc, &mO, p_otok, HD, S_LEN, 64, 128);
  make_map(enc, &mWo, Wo, DM, HD, 64, 64);

  cudaStream_t st = cudaStreamPerThread;
  ln_kernel<<<256, 256, 0, st>>>(x, w_r);
  gemm_kernel<256, 4, 0><<<132, 288, GemmSmem<256, 4>::TOTAL, st>>>(mA, mQ, mK, mV, 16, 16, 16 * 48, nullptr, (bf16*)p_qkv);
  chain_kernel<<<132, 256, CH_SMEM, st>>>(mem0, Wq, Wk, Wv, Wo, wg, wu, wd);
  gemm_kernel<128, 6, 1><<<128, 288, GemmSmem<128, 6>::TOTAL, st>>>(mO, mWo, mWo, mWo, 64, 16, 16 * 8, x, out);
}
```

```cpp
#include <cuda_runtime.h>
#include <cuda_bf16.h>
#include <cuda.h>
#include <stdint.h>

typedef __nv_bfloat16 bf16;

#define S_LEN 2048
#define DM 1024
#define NH 32
#define DH 128
#define NSEG 64
#define SEGL 32
#define HD 4096
#define NQKV 12288
#define FF 3584
#define SENT 0xFFFFFFFFu

__device__ __align__(1024) bf16 g_xn[S_LEN * DM];
__device__ __align__(1024) bf16 g_qkv[(size_t)S_LEN * NQKV];
__device__ __align__(1024) bf16 g_otok[(size_t)S_LEN * HD];
__device__ float g_r[S_LEN];
__device__ __align__(128) uint4 g_bufA[4][128][96];
__device__ __align__(128) uint4 g_bufB[4][128][16][32];
__device__ __align__(128) uint4 g_bufC[4][1024];
__device__ __align__(128) bf16 g_h[2][FF];
__device__ float g_upd[2][DM];
__device__ int g_sel[2];
__device__ unsigned g_moe_cnt;
#define TS(i)

__device__ __forceinline__ float bfr(float x) { return __bfloat162float(__float2bfloat16_rn(x)); }
__device__ __forceinline__ uint32_t pack2(float lo, float hi) {
  __nv_bfloat162 v = __floats2bfloat162_rn(lo, hi);
  return *reinterpret_cast<uint32_t*>(&v);
}
__device__ __forceinline__ float bflo(uint32_t v) { return __uint_as_float(v << 16); }
__device__ __forceinline__ float bfhi(uint32_t v) { return __uint_as_float(v & 0xFFFF0000u); }
__device__ __forceinline__ uint32_t smem_u32(const void* p) { return (uint32_t)__cvta_generic_to_shared(p); }

__device__ __forceinline__ uint4 ld_poll(const uint4* p) {
  uint4 v;
  asm volatile("ld.relaxed.gpu.global.v4.u32 {%0,%1,%2,%3},[%4];" : "=r"(v.x), "=r"(v.y), "=r"(v.z), "=r"(v.w) : "l"(p) : "memory");
  return v;
}
__device__ __forceinline__ void st_pub32(void* p, uint32_t v) {
  asm volatile("st.relaxed.gpu.global.u32 [%0],%1;" ::"l"(p), "r"(v) : "memory");
}
__device__ __forceinline__ void st_pub64(void* p, uint32_t a, uint32_t b) {
  asm volatile("st.relaxed.gpu.global.v2.u32 [%0],{%1,%2};" ::"l"(p), "r"(a), "r"(b) : "memory");
}
__device__ __forceinline__ bool pkt_ok(const uint4& v) { return v.x != SENT && v.y != SENT && v.z != SENT && v.w != SENT; }
__device__ __forceinline__ uint32_t desent(uint32_t v) { return v == SENT ? 0x7FFF7FFFu : v; }

__device__ __forceinline__ void ldsm4(uint32_t& r0, uint32_t& r1, uint32_t& r2, uint32_t& r3, uint32_t addr) {
  asm volatile("ldmatrix.sync.aligned.m8n8.x4.shared.b16 {%0,%1,%2,%3},[%4];" : "=r"(r0), "=r"(r1), "=r"(r2), "=r"(r3) : "r"(addr) : "memory");
}
__device__ __forceinline__ void ldsm4t(uint32_t& r0, uint32_t& r1, uint32_t& r2, uint32_t& r3, uint32_t addr) {
  asm volatile("ldmatrix.sync.aligned.m8n8.x4.trans.shared.b16 {%0,%1,%2,%3},[%4];" : "=r"(r0), "=r"(r1), "=r"(r2), "=r"(r3) : "r"(addr) : "memory");
}
__device__ __forceinline__ void mma16816(float (&d)[4], uint32_t a0, uint32_t a1, uint32_t a2, uint32_t a3, uint32_t b0, uint32_t b1) {
  asm volatile("mma.sync.aligned.m16n8k16.row.col.f32.bf16.bf16.f32 {%0,%1,%2,%3},{%4,%5,%6,%7},{%8,%9},{%0,%1,%2,%3};"
               : "+f"(d[0]), "+f"(d[1]), "+f"(d[2]), "+f"(d[3])
               : "r"(a0), "r"(a1), "r"(a2), "r"(a3), "r"(b0), "r"(b1));
}
__device__ __forceinline__ void cp_async16(uint32_t dst, const void* src) {
  asm volatile("cp.async.cg.shared.global [%0],[%1],16;" ::"r"(dst), "l"(src) : "memory");
}
__device__ __forceinline__ void cp_commit() { asm volatile("cp.async.commit_group;" ::: "memory"); }
template <int N>
__device__ __forceinline__ void cp_wait() { asm volatile("cp.async.wait_group %0;" ::"n"(N) : "memory"); }

__device__ __forceinline__ void mbar_init(uint32_t bar, uint32_t cnt) { asm volatile("mbarrier.init.shared::cta.b64 [%0],%1;" ::"r"(bar), "r"(cnt) : "memory"); }
__device__ __forceinline__ void mbar_expect_tx(uint32_t bar, uint32_t bytes) {
  asm volatile("mbarrier.arrive.expect_tx.shared::cta.b64 _,[%0],%1;" ::"r"(bar), "r"(bytes) : "memory");
}
__device__ __forceinline__ void mbar_arrive(uint32_t bar) { asm volatile("mbarrier.arrive.shared::cta.b64 _,[%0];" ::"r"(bar) : "memory"); }
__device__ __forceinline__ void mbar_wait(uint32_t bar, uint32_t parity) {
  asm volatile(
      "{\n.reg .pred p;\n"
      "WAIT_LOOP:\n"
      "mbarrier.try_wait.parity.shared::cta.b64 p,[%0],%1;\n"
      "@p bra WAIT_DONE;\n"
      "bra WAIT_LOOP;\n"
      "WAIT_DONE:\n}\n" ::"r"(bar), "r"(parity) : "memory");
}
__device__ __forceinline__ void tma_load2d(uint32_t dst, const CUtensorMap* tm, uint32_t bar, int c0, int c1) {
  asm volatile("cp.async.bulk.tensor.2d.shared::cluster.global.mbarrier::complete_tx::bytes [%0],[%1,{%3,%4}],[%2];"
               ::"r"(dst), "l"(tm), "r"(bar), "r"(c0), "r"(c1) : "memory");
}
__device__ __forceinline__ void wg_fence() { asm volatile("wgmma.fence.sync.aligned;" ::: "memory"); }
__device__ __forceinline__ void wg_commit() { asm volatile("wgmma.commit_group.sync.aligned;" ::: "memory"); }
template <int N>
__device__ __forceinline__ void wg_wait() { asm volatile("wgmma.wait_group.sync.aligned %0;" ::"n"(N) : "memory"); }
__device__ __forceinline__ uint64_t make_desc(uint32_t addr, uint32_t lbo, uint32_t sbo) {
  return (uint64_t)((addr & 0x3FFFF) >> 4) | ((uint64_t)(lbo >> 4) << 16) | ((uint64_t)(sbo >> 4) << 32) | (1ull << 62);
}

__device__ __forceinline__ void wgmma_m64n256k16(float (&d)[128], uint64_t da, uint64_t db, int scaleD) {
  asm volatile(
    "{\n.reg .pred p;\nsetp.ne.b32 p, %130, 0;\n"
    "wgmma.mma_async.sync.aligned.m64n256k16.f32.bf16.bf16 "
    "{%0, %1, %2, %3, %4, %5, %6, %7, %8, %9, %10, %11, %12, %13, %14, %15, %16, %17, %18, %19, %20, %21, %22, %23, %24, %25, %26, %27, %28, %29, %30, %31, %32, %33, %34, %35, %36, %37, %38, %39, %40, %41, %42, %43, %44, %45, %46, %47, %48, %49, %50, %51, %52, %53, %54, %55, %56, %57, %58, %59, %60, %61, %62, %63, %64, %65, %66, %67, %68, %69, %70, %71, %72, %73, %74, %75, %76, %77, %78, %79, %80, %81, %82, %83, %84, %85, %86, %87, %88, %89, %90, %91, %92, %93, %94, %95, %96, %97, %98, %99, %100, %101, %102, %103, %104, %105, %106, %107, %108, %109, %110, %111, %112, %113, %114, %115, %116, %117, %118, %119, %120, %121, %122, %123, %124, %125, %126, %127}, %128, %129, p, 1, 1, 0, 1;\n}\n"
    : "+f"(d[0]), "+f"(d[1]), "+f"(d[2]), "+f"(d[3]), "+f"(d[4]), "+f"(d[5]), "+f"(d[6]), "+f"(d[7]), "+f"(d[8]), "+f"(d[9]), "+f"(d[10]), "+f"(d[11]), "+f"(d[12]), "+f"(d[13]), "+f"(d[14]), "+f"(d[15]), "+f"(d[16]), "+f"(d[17]), "+f"(d[18]), "+f"(d[19]), "+f"(d[20]), "+f"(d[21]), "+f"(d[22]), "+f"(d[23]), "+f"(d[24]), "+f"(d[25]), "+f"(d[26]), "+f"(d[27]), "+f"(d[28]), "+f"(d[29]), "+f"(d[30]), "+f"(d[31]), "+f"(d[32]), "+f"(d[33]), "+f"(d[34]), "+f"(d[35]), "+f"(d[36]), "+f"(d[37]), "+f"(d[38]), "+f"(d[39]), "+f"(d[40]), "+f"(d[41]), "+f"(d[42]), "+f"(d[43]), "+f"(d[44]), "+f"(d[45]), "+f"(d[46]), "+f"(d[47]), "+f"(d[48]), "+f"(d[49]), "+f"(d[50]), "+f"(d[51]), "+f"(d[52]), "+f"(d[53]), "+f"(d[54]), "+f"(d[55]), "+f"(d[56]), "+f"(d[57]), "+f"(d[58]), "+f"(d[59]), "+f"(d[60]), "+f"(d[61]), "+f"(d[62]), "+f"(d[63]), "+f"(d[64]), "+f"(d[65]), "+f"(d[66]), "+f"(d[67]), "+f"(d[68]), "+f"(d[69]), "+f"(d[70]), "+f"(d[71]), "+f"(d[72]), "+f"(d[73]), "+f"(d[74]), "+f"(d[75]), "+f"(d[76]), "+f"(d[77]), "+f"(d[78]), "+f"(d[79]), "+f"(d[80]), "+f"(d[81]), "+f"(d[82]), "+f"(d[83]), "+f"(d[84]), "+f"(d[85]), "+f"(d[86]), "+f"(d[87]), "+f"(d[88]), "+f"(d[89]), "+f"(d[90]), "+f"(d[91]), "+f"(d[92]), "+f"(d[93]), "+f"(d[94]), "+f"(d[95]), "+f"(d[96]), "+f"(d[97]), "+f"(d[98]), "+f"(d[99]), "+f"(d[100]), "+f"(d[101]), "+f"(d[102]), "+f"(d[103]), "+f"(d[104]), "+f"(d[105]), "+f"(d[106]), "+f"(d[107]), "+f"(d[108]), "+f"(d[109]), "+f"(d[110]), "+f"(d[111]), "+f"(d[112]), "+f"(d[113]), "+f"(d[114]), "+f"(d[115]), "+f"(d[116]), "+f"(d[117]), "+f"(d[118]), "+f"(d[119]), "+f"(d[120]), "+f"(d[121]), "+f"(d[122]), "+f"(d[123]), "+f"(d[124]), "+f"(d[125]), "+f"(d[126]), "+f"(d[127])
    : "l"(da), "l"(db), "r"(scaleD));
}

__device__ __forceinline__ void wgmma_m64n128k16(float (&d)[64], uint64_t da, uint64_t db, int scaleD) {
  asm volatile(
    "{\n.reg .pred p;\nsetp.ne.b32 p, %66, 0;\n"
    "wgmma.mma_async.sync.aligned.m64n128k16.f32.bf16.bf16 "
    "{%0, %1, %2, %3, %4, %5, %6, %7, %8, %9, %10, %11, %12, %13, %14, %15, %16, %17, %18, %19, %20, %21, %22, %23, %24, %25, %26, %27, %28, %29, %30, %31, %32, %33, %34, %35, %36, %37, %38, %39, %40, %41, %42, %43, %44, %45, %46, %47, %48, %49, %50, %51, %52, %53, %54, %55, %56, %57, %58, %59, %60, %61, %62, %63}, %64, %65, p, 1, 1, 0, 1;\n}\n"
    : "+f"(d[0]), "+f"(d[1]), "+f"(d[2]), "+f"(d[3]), "+f"(d[4]), "+f"(d[5]), "+f"(d[6]), "+f"(d[7]), "+f"(d[8]), "+f"(d[9]), "+f"(d[10]), "+f"(d[11]), "+f"(d[12]), "+f"(d[13]), "+f"(d[14]), "+f"(d[15]), "+f"(d[16]), "+f"(d[17]), "+f"(d[18]), "+f"(d[19]), "+f"(d[20]), "+f"(d[21]), "+f"(d[22]), "+f"(d[23]), "+f"(d[24]), "+f"(d[25]), "+f"(d[26]), "+f"(d[27]), "+f"(d[28]), "+f"(d[29]), "+f"(d[30]), "+f"(d[31]), "+f"(d[32]), "+f"(d[33]), "+f"(d[34]), "+f"(d[35]), "+f"(d[36]), "+f"(d[37]), "+f"(d[38]), "+f"(d[39]), "+f"(d[40]), "+f"(d[41]), "+f"(d[42]), "+f"(d[43]), "+f"(d[44]), "+f"(d[45]), "+f"(d[46]), "+f"(d[47]), "+f"(d[48]), "+f"(d[49]), "+f"(d[50]), "+f"(d[51]), "+f"(d[52]), "+f"(d[53]), "+f"(d[54]), "+f"(d[55]), "+f"(d[56]), "+f"(d[57]), "+f"(d[58]), "+f"(d[59]), "+f"(d[60]), "+f"(d[61]), "+f"(d[62]), "+f"(d[63])
    : "l"(da), "l"(db), "r"(scaleD));
}

template <int BN> struct WG;
template <> struct WG<256> { static __device__ __forceinline__ void mma(float (&d)[128], uint64_t a, uint64_t b, int s) { wgmma_m64n256k16(d, a, b, s); } };
template <> struct WG<128> { static __device__ __forceinline__ void mma(float (&d)[64], uint64_t a, uint64_t b, int s) { wgmma_m64n128k16(d, a, b, s); } };

__global__ void __launch_bounds__(256) ln_kernel(const bf16* __restrict__ x, const bf16* __restrict__ w_r) {
  int warp = threadIdx.x >> 5, lane = threadIdx.x & 31;
  int row = blockIdx.x * 8 + warp;
  const uint4* xp = reinterpret_cast<const uint4*>(x + (size_t)row * DM);
  uint4 v[4];
#pragma unroll
  for (int i = 0; i < 4; i++) v[i] = xp[lane + 32 * i];
  float f[32];
#pragma unroll
  for (int i = 0; i < 4; i++) {
    f[8 * i + 0] = bflo(v[i].x); f[8 * i + 1] = bfhi(v[i].x);
    f[8 * i + 2] = bflo(v[i].y); f[8 * i + 3] = bfhi(v[i].y);
    f[8 * i + 4] = bflo(v[i].z); f[8 * i + 5] = bfhi(v[i].z);
    f[8 * i + 6] = bflo(v[i].w); f[8 * i + 7] = bfhi(v[i].w);
  }
  float s = 0.f;
#pragma unroll
  for (int i = 0; i < 32; i++) s += f[i];
#pragma unroll
  for (int o = 16; o > 0; o >>= 1) s += __shfl_xor_sync(0xffffffffu, s, o);
  float mean = s * (1.0f / DM);
  float q = 0.f;
#pragma unroll
  for (int i = 0; i < 32; i++) { float d = f[i] - mean; q += d * d; }
#pragma unroll
  for (int o = 16; o > 0; o >>= 1) q += __shfl_xor_sync(0xffffffffu, q, o);
  float var = bfr(q * (1.0f / DM));
  float mb = bfr(mean);
  float den = bfr(sqrtf(bfr(var + 1e-5f)));
  const uint4* wp = reinterpret_cast<const uint4*>(w_r);
  uint4* op = reinterpret_cast<uint4*>(g_xn + (size_t)row * DM);
  float r = 0.f;
#pragma unroll
  for (int i = 0; i < 4; i++) {
    uint4 w = wp[lane + 32 * i];
    float y[8];
#pragma unroll
    for (int k = 0; k < 8; k++) y[k] = bfr(bfr(f[8 * i + k] - mb) / den);
    r += y[0] * bflo(w.x) + y[1] * bfhi(w.x) + y[2] * bflo(w.y) + y[3] * bfhi(w.y) + y[4] * bflo(w.z) + y[5] * bfhi(w.z) +
         y[6] * bflo(w.w) + y[7] * bfhi(w.w);
    op[lane + 32 * i] = make_uint4(pack2(y[0], y[1]), pack2(y[2], y[3]), pack2(y[4], y[5]), pack2(y[6], y[7]));
  }
#pragma unroll
  for (int o = 16; o > 0; o >>= 1) r += __shfl_xor_sync(0xffffffffu, r, o);
  if (lane == 0) g_r[row] = bfr(r);
  int gt = blockIdx.x * 256 + threadIdx.x;
  const uint4 sv = make_uint4(SENT, SENT, SENT, SENT);
  uint4* a = &g_bufA[0][0][0];
  for (int i = gt; i < 2 * 128 * 96; i += 65536) a[i] = sv;
  uint4* b = &g_bufB[0][0][0][0];
  for (int i = gt; i < 2 * 128 * 32 * 16; i += 65536) b[i] = sv;
  uint4* c = &g_bufC[0][0];
  for (int i = gt; i < 2 * 1024; i += 65536) c[i] = sv;
  if (gt == 0) g_moe_cnt = 0;
}

template <int BN, int STAGES>
struct GemmSmem {
  static constexpr int A_BYTES = 128 * 64 * 2;
  static constexpr int B_BYTES = 64 * BN * 2;
  static constexpr int STAGE_BYTES = A_BYTES + B_BYTES;
  static constexpr int TOTAL = STAGES * STAGE_BYTES + 1024 + 256;
};

__device__ __forceinline__ void quad_transpose(uint32_t (&v)[4], int c) {
  {
    uint32_t s0 = (c & 1) ? v[0] : v[1];
    uint32_t s1 = (c & 1) ? v[2] : v[3];
    uint32_t r0 = __shfl_xor_sync(0xffffffffu, s0, 1);
    uint32_t r1 = __shfl_xor_sync(0xffffffffu, s1, 1);
    if (c & 1) { v[0] = r0; v[2] = r1; } else { v[1] = r0; v[3] = r1; }
  }
  {
    uint32_t s0 = (c & 2) ? v[0] : v[2];
    uint32_t s1 = (c & 2) ? v[1] : v[3];
    uint32_t r0 = __shfl_xor_sync(0xffffffffu, s0, 2);
    uint32_t r1 = __shfl_xor_sync(0xffffffffu, s1, 2);
    if (c & 2) { v[0] = r0; v[1] = r1; } else { v[2] = r0; v[3] = r1; }
  }
}

__device__ __forceinline__ uint32_t add3(uint32_t a, uint32_t x, uint32_t b) {
  float lo = bfr(bflo(x) + bflo(a)) + bflo(b);
  float hi = bfr(bfhi(x) + bfhi(a)) + bfhi(b);
  return pack2(lo, hi);
}

template <int BN, int STAGES, int EPI>
__global__ void __launch_bounds__(288, 1)
gemm_kernel(const __grid_constant__ CUtensorMap tmA, const __grid_constant__ CUtensorMap tmB0,
            const __grid_constant__ CUtensorMap tmB1, const __grid_constant__ CUtensorMap tmB2,
            int kblocks, int tiles_m, int tiles_total, const bf16* __restrict__ xin, bf16* __restrict__ outp) {
  using SM = GemmSmem<BN, STAGES>;
  extern __shared__ uint8_t smem_raw[];
  uint32_t base = (smem_u32(smem_raw) + 1023) & ~1023u;
  uint32_t bars = base + STAGES * SM::STAGE_BYTES;
  int warp = threadIdx.x >> 5, lane = threadIdx.x & 31;
  if (threadIdx.x == 0) {
    for (int i = 0; i < STAGES; i++) { mbar_init(bars + 8 * i, 1); mbar_init(bars + 8 * (STAGES + i), 8); }
    asm volatile("fence.mbarrier_init.release.cluster;" ::: "memory");
  }
  __syncthreads();
  if (warp == 8) {
    if (lane == 0) {
      int it = 0;
      for (int t = blockIdx.x; t < tiles_total; t += gridDim.x) {
        int tm = t % tiles_m, tn = t / tiles_m;
        int n0 = tn * BN;
        const CUtensorMap* tb = &tmB0;
        if (EPI == 0) { int wsel = n0 >> 12; tb = wsel == 0 ? &tmB0 : (wsel == 1 ? &tmB1 : &tmB2); n0 &= 4095; }
        for (int kb = 0; kb < kblocks; kb++, it++) {
          int st = it % STAGES; uint32_t ph = (it / STAGES) & 1;
          mbar_wait(bars + 8 * (STAGES + st), ph ^ 1);
          uint32_t sa = base + st * SM::STAGE_BYTES, sb = sa + SM::A_BYTES;
          mbar_expect_tx(bars + 8 * st, SM::STAGE_BYTES);
          tma_load2d(sa, &tmA, bars + 8 * st, kb * 64, tm * 128);
#pragma unroll
          for (int i = 0; i < BN / 64; i++) tma_load2d(sb + i * 8192, tb, bars + 8 * st, n0 + i * 64, kb * 64);
        }
      }
    }
  } else {
    int wg = warp >> 2;
    int g = lane >> 2, c = lane & 3;
    int it = 0;
    float acc[BN / 2];
    for (int t = blockIdx.x; t < tiles_total; t += gridDim.x) {
      int tm = t % tiles_m, tn = t / tiles_m;
      for (int kb = 0; kb < kblocks; kb++, it++) {
        int st = it % STAGES; uint32_t ph = (it / STAGES) & 1;
        mbar_wait(bars + 8 * st, ph);
        uint32_t sa = base + st * SM::STAGE_BYTES + wg * 8192, sb = base + st * SM::STAGE_BYTES + SM::A_BYTES;
        wg_fence();
#pragma unroll
        for (int kk = 0; kk < 4; kk++) {
          uint64_t da = make_desc(sa + kk * 32, 16, 1024);
          uint64_t db = make_desc(sb + kk * 2048, 8192, 1024);
          WG<BN>::mma(acc, da, db, (kb | kk) != 0);
        }
        wg_commit();
        if (kb > 0) {
          wg_wait<1>();
          int pst = (it - 1) % STAGES;
          if (lane == 0) mbar_arrive(bars + 8 * (STAGES + pst));
        }
      }
      wg_wait<0>();
      { int pst = (it - 1) % STAGES; if (lane == 0) mbar_arrive(bars + 8 * (STAGES + pst)); }
      int row0 = tm * 128 + wg * 64 + (warp & 3) * 16 + g;
      int sel0 = -1, sel1 = -1;
      if (EPI == 1) { sel0 = g_sel[0]; sel1 = g_sel[1]; }
#pragma unroll
      for (int half = 0; half < 2; half++) {
        int row = row0 + half * 8;
#pragma unroll
        for (int q = 0; q < BN / 32; q++) {
          uint32_t v[4];
#pragma unroll
          for (int tt = 0; tt < 4; tt++) v[tt] = pack2(acc[(q * 4 + tt) * 4 + half * 2], acc[(q * 4 + tt) * 4 + half * 2 + 1]);
          quad_transpose(v, c);
          int col = tn * BN + q * 32 + c * 8;
          if (EPI == 0) {
            *reinterpret_cast<uint4*>(outp + (size_t)row * NQKV + col) = make_uint4(v[0], v[1], v[2], v[3]);
          } else {
            uint4 xv = *reinterpret_cast<const uint4*>(xin + (size_t)row * DM + col);
            uint4 bv = *reinterpret_cast<const uint4*>(g_xn + (size_t)row * DM + col);
            if (row == sel0 || row == sel1) {
              const float* u = &g_upd[row == sel0 ? 0 : 1][col];
              bv.x = pack2(bflo(bv.x) + u[0], bfhi(bv.x) + u[1]);
              bv.y = pack2(bflo(bv.y) + u[2], bfhi(bv.y) + u[3]);
              bv.z = pack2(bflo(bv.z) + u[4], bfhi(bv.z) + u[5]);
              bv.w = pack2(bflo(bv.w) + u[6], bfhi(bv.w) + u[7]);
            }
            uint4 o = make_uint4(add3(v[0], xv.x, bv.x), add3(v[1], xv.y, bv.y), add3(v[2], xv.z, bv.z), add3(v[3], xv.w, bv.w));
            *reinterpret_cast<uint4*>(outp + (size_t)row * DM + col) = o;
          }
        }
      }
    }
  }
}

#define RK 10
#define SK (16 - RK)
#define TP 272
#define OFF_WQS 0
#define OFF_MEMT (OFF_WQS + 8 * SK * 3 * 512)
#define OFF_RED (OFF_MEMT + 16384)
#define OFF_QKVM (OFF_RED + 12288)
#define OFF_TOK (OFF_QKVM + 6144)
#define TOK_BYTES (72 * TP)
#define OFF_SA (OFF_TOK + 2 * TOK_BYTES)
#define OFF_BAR (OFF_SA + 8 * TP)
#define CH_END (OFF_BAR + 64)
#define CH_STG2 (131072)
#define CH_SMEM (196608 + 1024)
static_assert(CH_END <= CH_SMEM, "smem");

__device__ void moe_part(int m, const bf16* __restrict__ wg, const bf16* __restrict__ wu, const bf16* __restrict__ wd, uint8_t* smem);

__device__ __forceinline__ void bulk_copy(uint32_t dst, const void* src, uint32_t bytes, uint32_t bar) {
  asm volatile("cp.async.bulk.shared::cluster.global.mbarrier::complete_tx::bytes [%0],[%1],%2,[%3];"
               ::"r"(dst), "l"(src), "r"(bytes), "r"(bar) : "memory");
}
__device__ __forceinline__ void st_pub128(void* p, uint32_t v) {
  asm volatile("st.relaxed.gpu.global.v4.u32 [%0],{%1,%1,%1,%1};" ::"l"(p), "r"(v) : "memory");
}
__device__ __forceinline__ void sts128(uint32_t addr, const uint4& v) {
  asm volatile("st.shared.v4.u32 [%0],{%1,%2,%3,%4};" ::"r"(addr), "r"(v.x), "r"(v.y), "r"(v.z), "r"(v.w) : "memory");
}

#define POLL_MAX (1 << 22)

template <bool TOK>
__device__ __forceinline__ void attn8(uint32_t sb, uint32_t tok, int lane, int wq4, int tr, bf16* otok_row) {
  const int g = lane >> 2, c = lane & 3;
  float sc[5][4];
#pragma unroll
  for (int n = 0; n < 5; n++)
#pragma unroll
    for (int i = 0; i < 4; i++) sc[n][i] = 0.f;
  const uint32_t tokrow = tok + (lane & 7) * TP + (lane >> 3) * 16;
  const uint32_t qaddr = TOK ? (tok + (64 + (lane & 7)) * TP + (lane >> 4) * 16) : (sb + OFF_QKVM + ((lane & 7) + 8 * (lane >> 4)) * 16);
#pragma unroll
  for (int kp = 0; kp < 4; kp++) {
    uint32_t q0[4], q1[4], km[4], kt[4][4];
    if (TOK) {
      ldsm4(q0[0], q0[1], q0[2], q0[3], qaddr + 64 * kp);
      ldsm4(q1[0], q1[1], q1[2], q1[3], qaddr + 64 * kp + 32);
    } else {
      ldsm4t(q0[0], q0[1], q0[2], q0[3], qaddr + 512 * kp);
      ldsm4t(q1[0], q1[1], q1[2], q1[3], qaddr + 512 * kp + 256);
    }
    ldsm4t(km[0], km[1], km[2], km[3], sb + OFF_QKVM + (128 + 32 * kp + lane) * 16);
#pragma unroll
    for (int n = 0; n < 4; n++) ldsm4(kt[n][0], kt[n][1], kt[n][2], kt[n][3], tokrow + 8 * n * TP + 64 * kp);
    mma16816(sc[0], q0[0], q0[1], q0[2], q0[3], km[0], km[1]);
#pragma unroll
    for (int n = 0; n < 4; n++) mma16816(sc[n + 1], q0[0], q0[1], q0[2], q0[3], kt[n][0], kt[n][1]);
    mma16816(sc[0], q1[0], q1[1], q1[2], q1[3], km[2], km[3]);
#pragma unroll
    for (int n = 0; n < 4; n++) mma16816(sc[n + 1], q1[0], q1[1], q1[2], q1[3], kt[n][2], kt[n][3]);
  }
  uint32_t vm[4], vt[4][4];
  ldsm4(vm[0], vm[1], vm[2], vm[3], sb + OFF_QKVM + (256 + 32 * wq4 + lane) * 16);
#pragma unroll
  for (int n = 0; n < 4; n++) ldsm4t(vt[n][0], vt[n][1], vt[n][2], vt[n][3], tok + (32 + lane) * TP + (32 * wq4 + 8 * n) * 2);
  const float scale = 0.08838834764831845f;
  float m0 = -3.0e38f;
#pragma unroll
  for (int n = 0; n < 5; n++) {
    sc[n][0] = bfr(bfr(sc[n][0]) * scale);
    sc[n][1] = bfr(bfr(sc[n][1]) * scale);
    if (TOK && n > 0) {
      int kt = 8 * (n - 1) + 2 * c;
      if (kt > tr) sc[n][0] = -1.0e9f;
      if (kt + 1 > tr) sc[n][1] = -1.0e9f;
    }
    m0 = fmaxf(m0, fmaxf(sc[n][0], sc[n][1]));
  }
  m0 = fmaxf(m0, __shfl_xor_sync(0xffffffffu, m0, 1));
  m0 = fmaxf(m0, __shfl_xor_sync(0xffffffffu, m0, 2));
  float s0 = 0.f;
#pragma unroll
  for (int n = 0; n < 5; n++) {
    sc[n][0] = __expf(sc[n][0] - m0);
    sc[n][1] = __expf(sc[n][1] - m0);
    s0 += sc[n][0] + sc[n][1];
  }
  s0 += __shfl_xor_sync(0xffffffffu, s0, 1);
  s0 += __shfl_xor_sync(0xffffffffu, s0, 2);
  const float i0 = __frcp_rn(s0);
  uint32_t pq[3][4];
#pragma unroll
  for (int kk = 0; kk < 3; kk++) {
    pq[kk][0] = pack2(sc[2 * kk][0] * i0, sc[2 * kk][1] * i0);
    pq[kk][1] = 0u;
    pq[kk][2] = kk < 2 ? pack2(sc[2 * kk + 1][0] * i0, sc[2 * kk + 1][1] * i0) : 0u;
    pq[kk][3] = 0u;
  }
  float o[4][4];
#pragma unroll
  for (int n = 0; n < 4; n++) {
#pragma unroll
    for (int i = 0; i < 4; i++) o[n][i] = 0.f;
    mma16816(o[n], pq[0][0], pq[0][1], pq[0][2], pq[0][3], vm[n], vt[n][0]);
  }
#pragma unroll
  for (int n = 0; n < 4; n++) mma16816(o[n], pq[1][0], pq[1][1], pq[1][2], pq[1][3], vt[n][1], vt[n][2]);
#pragma unroll
  for (int n = 0; n < 4; n++) mma16816(o[n], pq[2][0], pq[2][1], pq[2][2], pq[2][3], vt[n][3], 0u);
#pragma unroll
  for (int n = 0; n < 4; n++) {
    const int e = 32 * wq4 + 8 * n + 2 * c;
    if (TOK) *reinterpret_cast<uint32_t*>(otok_row + e) = pack2(o[n][0], o[n][1]);
    else asm volatile("st.shared.u32 [%0],%1;" ::"r"(sb + OFF_SA + g * TP + e * 2), "r"(pack2(o[n][0], o[n][1])) : "memory");
  }
}

__global__ void __launch_bounds__(256, 1)
chain_kernel(const bf16* __restrict__ mem0, const bf16* __restrict__ Wq, const bf16* __restrict__ Wk, const bf16* __restrict__ Wv,
             const bf16* __restrict__ Wo, const bf16* __restrict__ wgate, const bf16* __restrict__ wup, const bf16* __restrict__ wdown) {
  extern __shared__ __align__(1024) uint8_t smem[];
  const int cta = blockIdx.x, t = threadIdx.x, warp = t >> 5, lane = t & 31;
  if (cta >= 128) {
    moe_part(cta - 128, wgate, wup, wdown, smem);
    return;
  }
  const int h = cta >> 2, j = cta & 3;
  const int g = lane >> 2, c = lane & 3;
  const uint32_t sb = smem_u32(smem);
  const int mg = warp & 1, kq = warp >> 1;

  uint32_t wq[RK][3][4];
  uint32_t wo[2][8][4];
  {
    for (int i = t; i < 3 * 1024 * 4; i += 256) {
      int which = i >> 12, k = (i >> 2) & 1023, ch = i & 3;
      const bf16* W = which == 0 ? Wq : (which == 1 ? Wk : Wv);
      cp_async16(sb + (which * 1024 + k) * 64 + ch * 16, W + (size_t)k * HD + h * 128 + 32 * j + ch * 8);
    }
    cp_commit(); cp_wait<0>();
    __syncthreads();
    uint32_t tmp[SK][3][4];
#pragma unroll
    for (int ks = 0; ks < 16; ks++) {
#pragma unroll
      for (int tt = 0; tt < 3; tt++) {
        int tile = 3 * mg + tt;
        int which = tile >> 1, ch = tile & 1;
        int k = (16 * kq + ks) * 16 + (lane & 7) + 8 * (lane >> 4);
        uint32_t addr = sb + (which * 1024 + k) * 64 + ch * 32 + 16 * ((lane >> 3) & 1);
        if (ks < RK) ldsm4t(wq[ks][tt][0], wq[ks][tt][1], wq[ks][tt][2], wq[ks][tt][3], addr);
        else ldsm4t(tmp[ks - RK][tt][0], tmp[ks - RK][tt][1], tmp[ks - RK][tt][2], tmp[ks - RK][tt][3], addr);
      }
    }
    __syncthreads();
#pragma unroll
    for (int ks = 0; ks < SK; ks++)
#pragma unroll
      for (int tt = 0; tt < 3; tt++)
        *reinterpret_cast<uint4*>(smem + OFF_WQS + (((warp * SK + ks) * 3 + tt) * 32 + lane) * 16) =
            make_uint4(tmp[ks][tt][0], tmp[ks][tt][1], tmp[ks][tt][2], tmp[ks][tt][3]);
    for (int i = t; i < 128 * 32; i += 256) {
      int e = i >> 5, ch = i & 31;
      cp_async16(sb + CH_STG2 + e * 512 + ch * 16, Wo + (size_t)(h * 128 + e) * DM + 256 * j + ch * 8);
    }
    cp_commit(); cp_wait<0>();
    __syncthreads();
#pragma unroll
    for (int tt = 0; tt < 2; tt++)
#pragma unroll
      for (int ks = 0; ks < 8; ks++) {
        int e = 16 * ks + (lane & 7) + 8 * (lane >> 4);
        uint32_t addr = sb + CH_STG2 + e * 512 + (32 * warp + 16 * tt + 8 * ((lane >> 3) & 1)) * 2;
        ldsm4t(wo[tt][ks][0], wo[tt][ks][1], wo[tt][ks][2], wo[tt][ks][3], addr);
      }
    if (t == 0) {
      mbar_init(sb + OFF_BAR, 1); mbar_init(sb + OFF_BAR + 8, 1);
      asm volatile("fence.mbarrier_init.release.cluster;" ::: "memory");
    }
    __syncthreads();
    asm volatile("fence.proxy.async.shared::cta;" ::: "memory");
  }
  auto prefetch_tok = [&](int s) {
    const int i = t - 192;
    const uint32_t dst = sb + OFF_TOK + (s & 1) * TOK_BYTES + (i >> 4) * TP + (i & 15) * 16;
    const bf16* src = g_qkv + (size_t)(s * 32 + (i >> 4)) * NQKV + HD + h * 128 + (i & 15) * 8;
#pragma unroll
    for (int r = 0; r < 8; r++) {
      cp_async16(dst + 4 * r * TP, src + (size_t)4 * r * NQKV);
      cp_async16(dst + (32 + 4 * r) * TP, src + (size_t)4 * r * NQKV + HD);
    }
    cp_async16(dst + 64 * TP, src + (size_t)(8 * j) * NQKV - HD);
    cp_async16(dst + 68 * TP, src + (size_t)(8 * j + 4) * NQKV - HD);
    cp_commit();
  };
  if (warp >= 6) prefetch_tok(0);
  for (int i = t; i < 8 * 1024; i += 256) {
    int r = i >> 10, k = i & 1023;
    reinterpret_cast<bf16*>(smem + OFF_MEMT)[k * 8 + r] = mem0[i];
  }
  __syncthreads();
  uint32_t p2dst0, p2dst1;
  {
    int p = t, jj = p / 96, f = p % 96;
    p2dst0 = sb + OFF_QKVM + ((f >> 5) * 128 + 32 * jj + (f & 31)) * 16;
    p = 256 + (t & 127); jj = p / 96; f = p % 96;
    p2dst1 = sb + OFF_QKVM + ((f >> 5) * 128 + 32 * jj + (f & 31)) * 16;
  }
  const int p0idx = 256 * kq + 128 * mg + lane;
  TS(0);
  for (int s = 0; s < NSEG; s++) {
    const int slot = s & 3, slot2 = (s + 2) & 3;
    if (s > 0) {
      const uint4* src = &g_bufC[(s - 1) & 3][p0idx];
      uint4 v[4];
#pragma unroll
      for (int i = 0; i < 4; i++) v[i] = ld_poll(src + 32 * i);
      int it = 0;
      while (!(pkt_ok(v[0]) && pkt_ok(v[1]) && pkt_ok(v[2]) && pkt_ok(v[3])) && ++it < POLL_MAX) {
#pragma unroll
        for (int i = 0; i < 4; i++)
          if (!pkt_ok(v[i])) v[i] = ld_poll(src + 32 * i);
      }
#pragma unroll
      for (int i = 0; i < 4; i++) sts128(sb + OFF_MEMT + (p0idx + 32 * i) * 16, v[i]);
      TS(1);
      asm volatile("bar.sync %0, 64;" ::"r"(1 + kq) : "memory");
      TS(2);
    }
    {
      float acc[2][3][4];
#pragma unroll
      for (int a = 0; a < 2; a++)
#pragma unroll
        for (int tt = 0; tt < 3; tt++)
#pragma unroll
          for (int i = 0; i < 4; i++) acc[a][tt][i] = 0.f;
      uint4 sa[SK][3];
#pragma unroll
      for (int kp = 0; kp < 8; kp++) {
        uint32_t b0, b1, b2, b3;
        ldsm4t(b0, b1, b2, b3, sb + OFF_MEMT + ((16 * kq + 2 * kp) * 16 + lane) * 16);
#pragma unroll
        for (int u = 0; u < 2; u++) {
          int ks = 2 * (kp + 1) + u;
          if (ks >= RK && ks < 16) {
#pragma unroll
            for (int tt = 0; tt < 3; tt++)
              sa[ks - RK][tt] = *reinterpret_cast<const uint4*>(smem + OFF_WQS + (((warp * SK + (ks - RK)) * 3 + tt) * 32 + lane) * 16);
          }
        }
#pragma unroll
        for (int u = 0; u < 2; u++) {
          int ks = 2 * kp + u;
#pragma unroll
          for (int tt = 0; tt < 3; tt++) {
            if (ks < RK) mma16816(acc[u][tt], wq[ks][tt][0], wq[ks][tt][1], wq[ks][tt][2], wq[ks][tt][3], u ? b2 : b0, u ? b3 : b1);
            else mma16816(acc[u][tt], sa[ks - RK][tt].x, sa[ks - RK][tt].y, sa[ks - RK][tt].z, sa[ks - RK][tt].w, u ? b2 : b0, u ? b3 : b1);
          }
        }
      }
#pragma unroll
      for (int tt = 0; tt < 3; tt++)
        *reinterpret_cast<float4*>(smem + OFF_RED + ((kq * 6 + 3 * mg + tt) * 32 + lane) * 16) =
            make_float4(acc[0][tt][0] + acc[1][tt][0], acc[0][tt][1] + acc[1][tt][1], acc[0][tt][2] + acc[1][tt][2], acc[0][tt][3] + acc[1][tt][3]);
    }
    TS(3);
    __syncthreads();
    TS(4);
    if (warp < 6) {
      float4 r = *reinterpret_cast<const float4*>(smem + OFF_RED + ((0 * 6 + warp) * 32 + lane) * 16);
#pragma unroll
      for (int q = 1; q < 4; q++) {
        float4 x = *reinterpret_cast<const float4*>(smem + OFF_RED + ((q * 6 + warp) * 32 + lane) * 16);
        r.x += x.x; r.y += x.y; r.z += x.z; r.w += x.w;
      }
      uint32_t* dst = reinterpret_cast<uint32_t*>(&g_bufA[slot][cta][16 * warp + g]) + c;
      st_pub32(dst, desent(pack2(r.x, r.y)));
      st_pub32(dst + 32, desent(pack2(r.z, r.w)));
    } else {
      const int i = t - 192;
      st_pub128(&g_bufA[slot2][cta][i], SENT);
      if (i < 32) st_pub128(&g_bufA[slot2][cta][64 + i], SENT);
      if (s + 1 < NSEG) prefetch_tok(s + 1); else cp_commit();
    }
    {
      const uint4* src = &g_bufA[slot][4 * h][t];
      uint4 v0 = ld_poll(src);
      uint4 v1 = make_uint4(0, 0, 0, 0);
      if (t < 128) v1 = ld_poll(src + 256);
      int it = 0;
      while (!(pkt_ok(v0) && pkt_ok(v1)) && ++it < POLL_MAX) {
        if (!pkt_ok(v0)) v0 = ld_poll(src);
        if (!pkt_ok(v1)) v1 = ld_poll(src + 256);
      }
      sts128(p2dst0, v0);
      if (t < 128) sts128(p2dst1, v1);
    }
    TS(5);
    if (warp >= 6) cp_wait<1>();
    __syncthreads();
    TS(6);
    const uint32_t tok = sb + OFF_TOK + (s & 1) * TOK_BYTES;
    if (s < NSEG - 1) {
      if (warp < 4) attn8<false>(sb, tok, lane, warp, 0, nullptr);
      TS(7);
      __syncthreads();
      TS(8);
      {
        float acc[2][2][4];
#pragma unroll
        for (int a = 0; a < 2; a++)
#pragma unroll
          for (int tt = 0; tt < 2; tt++)
#pragma unroll
            for (int i = 0; i < 4; i++) acc[a][tt][i] = 0.f;
        uint32_t b[4][4];
#pragma unroll
        for (int kp = 0; kp < 4; kp++) ldsm4(b[kp][0], b[kp][1], b[kp][2], b[kp][3], sb + OFF_SA + (lane & 7) * TP + (32 * kp + 8 * (lane >> 3)) * 2);
#pragma unroll
        for (int kp = 0; kp < 4; kp++) {
#pragma unroll
          for (int tt = 0; tt < 2; tt++) {
            mma16816(acc[0][tt], wo[tt][2 * kp][0], wo[tt][2 * kp][1], wo[tt][2 * kp][2], wo[tt][2 * kp][3], b[kp][0], b[kp][1]);
            mma16816(acc[1][tt], wo[tt][2 * kp + 1][0], wo[tt][2 * kp + 1][1], wo[tt][2 * kp + 1][2], wo[tt][2 * kp + 1][3], b[kp][2], b[kp][3]);
          }
        }
        const int off = h * 32 + lane;
#pragma unroll
        for (int tt = 0; tt < 2; tt++) {
          int r0 = 32 * j + 4 * warp + 2 * tt;
          uint32_t x0 = __float_as_uint(acc[0][tt][0] + acc[1][tt][0]), x1 = __float_as_uint(acc[0][tt][1] + acc[1][tt][1]);
          uint32_t x2 = __float_as_uint(acc[0][tt][2] + acc[1][tt][2]), x3 = __float_as_uint(acc[0][tt][3] + acc[1][tt][3]);
          x0 = x0 == SENT ? 0x7FFFFFFFu : x0; x1 = x1 == SENT ? 0x7FFFFFFFu : x1;
          x2 = x2 == SENT ? 0x7FFFFFFFu : x2; x3 = x3 == SENT ? 0x7FFFFFFFu : x3;
          st_pub64(reinterpret_cast<uint2*>(&g_bufB[slot][r0][0][0]) + off, x0, x1);
          st_pub64(reinterpret_cast<uint2*>(&g_bufB[slot][r0 + 1][0][0]) + off, x2, x3);
        }
#pragma unroll
        for (int tt = 0; tt < 4; tt++)
          st_pub64(reinterpret_cast<uint2*>(&g_bufB[slot2][32 * j + 4 * warp + tt][0][0]) + off, SENT, SENT);
      }
      TS(9);
      {
        const uint4* src = &g_bufB[slot][cta][0][0] + 16 * lane + 2 * warp;
        uint4 v0 = ld_poll(src), v1 = ld_poll(src + 1);
        int it = 0;
        while (!(pkt_ok(v0) && pkt_ok(v1)) && ++it < POLL_MAX) {
          if (!pkt_ok(v0)) v0 = ld_poll(src);
          if (!pkt_ok(v1)) v1 = ld_poll(src + 1);
        }
        TS(10);
        const bool hi = lane & 16;
        float a0 = __uint_as_float(hi ? v1.x : v0.x), a1 = __uint_as_float(hi ? v1.y : v0.y);
        float a2 = __uint_as_float(hi ? v1.z : v0.z), a3 = __uint_as_float(hi ? v1.w : v0.w);
        float b0 = __uint_as_float(hi ? v0.x : v1.x), b1 = __uint_as_float(hi ? v0.y : v1.y);
        float b2 = __uint_as_float(hi ? v0.z : v1.z), b3 = __uint_as_float(hi ? v0.w : v1.w);
        a0 += __shfl_xor_sync(0xffffffffu, b0, 16); a1 += __shfl_xor_sync(0xffffffffu, b1, 16);
        a2 += __shfl_xor_sync(0xffffffffu, b2, 16); a3 += __shfl_xor_sync(0xffffffffu, b3, 16);
        const bool h8 = lane & 8;
        float k0 = h8 ? a2 : a0, k1 = h8 ? a3 : a1, s0 = h8 ? a0 : a2, s1 = h8 ? a1 : a3;
        k0 += __shfl_xor_sync(0xffffffffu, s0, 8); k1 += __shfl_xor_sync(0xffffffffu, s1, 8);
        const bool h4 = lane & 4;
        float z = h4 ? k1 : k0, zs = h4 ? k0 : k1;
        z += __shfl_xor_sync(0xffffffffu, zs, 4);
        z += __shfl_xor_sync(0xffffffffu, z, 2);
        z += __shfl_xor_sync(0xffffffffu, z, 1);
        float zo = __shfl_xor_sync(0xffffffffu, z, 4);
        if ((lane & 7) == 0) {
          uint32_t* d = reinterpret_cast<uint32_t*>(&g_bufC[slot][8 * cta + warp]) + (lane >> 3);
          st_pub32(d, desent(pack2(z, zo)));
          st_pub32(reinterpret_cast<uint32_t*>(&g_bufC[slot2][8 * cta + warp]) + (lane >> 3), SENT);
        }
      }
    }
    if (warp >= 4) attn8<true>(sb, tok, lane, warp - 4, 8 * j + g, g_otok + (size_t)(s * 32 + 8 * j + g) * HD + h * 128);
    TS(11);
  }
}

__device__ void moe_part(int m, const bf16* __restrict__ wg, const bf16* __restrict__ wu, const bf16* __restrict__ wd, uint8_t* smem) {
  const int t = threadIdx.x, warp = t >> 5, lane = t & 31;
  float* xs = reinterpret_cast<float*>(smem);
  float* red = reinterpret_cast<float*>(smem + 8192);
  float* hs = reinterpret_cast<float*>(smem + 65536);
  __shared__ float bv[8];
  __shared__ int bi[8];
  __shared__ int sel[2];
  int first = -1;
  for (int pass = 0; pass < 2; pass++) {
    float best = -INFINITY; int bidx = 0x7fffffff;
    for (int i = t; i < S_LEN; i += 256) {
      float v = g_r[i];
      if (i == first) continue;
      if (v > best || (v == best && i < bidx) || bidx == 0x7fffffff) { best = v; bidx = i; }
    }
#pragma unroll
    for (int o = 16; o > 0; o >>= 1) {
      float ov = __shfl_xor_sync(0xffffffffu, best, o); int oi = __shfl_xor_sync(0xffffffffu, bidx, o);
      if (oi != 0x7fffffff && (bidx == 0x7fffffff || ov > best || (ov == best && oi < bidx))) { best = ov; bidx = oi; }
    }
    if (lane == 0) { bv[warp] = best; bi[warp] = bidx; }
    __syncthreads();
    if (t == 0) {
      float b = bv[0]; int ix = bi[0];
      for (int w = 1; w < 8; w++) if (bv[w] > b || (bv[w] == b && bi[w] < ix)) { b = bv[w]; ix = bi[w]; }
      sel[pass] = ix;
    }
    __syncthreads();
    first = sel[0];
  }
  const int s0 = sel[0], s1 = sel[1];
  for (int i = t; i < 2048; i += 256) xs[i] = __bfloat162float(g_xn[(size_t)(i < 1024 ? s0 : s1) * DM + (i & 1023)]);
  __syncthreads();
  {
    int cg = t % 112, kh = t / 112;
    float a[2][2][8];
#pragma unroll
    for (int i = 0; i < 8; i++) { a[0][0][i] = a[0][1][i] = a[1][0][i] = a[1][1][i] = 0.f; }
    if (kh < 2) {
      const bf16* pg = wg + (size_t)(kh * 512) * FF + 896 * m + cg * 8;
      const bf16* pu = wu + (size_t)(kh * 512) * FF + 896 * m + cg * 8;
#pragma unroll 8
      for (int k = 0; k < 512; k++) {
        uint4 gv = __ldg(reinterpret_cast<const uint4*>(pg + (size_t)k * FF));
        uint4 uv = __ldg(reinterpret_cast<const uint4*>(pu + (size_t)k * FF));
        float x0 = xs[kh * 512 + k], x1 = xs[1024 + kh * 512 + k];
        float gf[8] = {bflo(gv.x), bfhi(gv.x), bflo(gv.y), bfhi(gv.y), bflo(gv.z), bfhi(gv.z), bflo(gv.w), bfhi(gv.w)};
        float uf[8] = {bflo(uv.x), bfhi(uv.x), bflo(uv.y), bfhi(uv.y), bflo(uv.z), bfhi(uv.z), bflo(uv.w), bfhi(uv.w)};
#pragma unroll
        for (int i = 0; i < 8; i++) {
          a[0][0][i] += x0 * gf[i]; a[0][1][i] += x1 * gf[i];
          a[1][0][i] += x0 * uf[i]; a[1][1][i] += x1 * uf[i];
        }
      }
      if (kh == 1) {
#pragma unroll
        for (int i = 0; i < 8; i++) {
          red[(0 * 2 + 0) * 896 + cg * 8 + i] = a[0][0][i]; red[(0 * 2 + 1) * 896 + cg * 8 + i] = a[0][1][i];
          red[(1 * 2 + 0) * 896 + cg * 8 + i] = a[1][0][i]; red[(1 * 2 + 1) * 896 + cg * 8 + i] = a[1][1][i];
        }
      }
    }
    __syncthreads();
    if (kh == 0) {
#pragma unroll
      for (int i = 0; i < 8; i++) {
#pragma unroll
        for (int tk = 0; tk < 2; tk++) {
          float gq = bfr(a[0][tk][i] + red[(0 * 2 + tk) * 896 + cg * 8 + i]);
          float uq = bfr(a[1][tk][i] + red[(1 * 2 + tk) * 896 + cg * 8 + i]);
          float sg = bfr(gq / (1.0f + __expf(-gq)));
          g_h[tk][896 * m + cg * 8 + i] = __float2bfloat16_rn(sg * uq);
        }
      }
    }
    __threadfence();
    __syncthreads();
    if (t == 0) {
      atomicAdd(&g_moe_cnt, 1u);
      int it = 0;
      while (*reinterpret_cast<volatile unsigned*>(&g_moe_cnt) < 4u && ++it < (1 << 24)) {}
      __threadfence();
    }
    __syncthreads();
  }
  for (int i = t; i < 2 * FF; i += 256) {
    const volatile unsigned short* p = reinterpret_cast<const volatile unsigned short*>(&g_h[0][0]);
    hs[i] = __uint_as_float(((uint32_t)p[i]) << 16);
  }
  __syncthreads();
  {
    int cg = t & 31, ksl = t >> 5;
    float a[2][8];
#pragma unroll
    for (int i = 0; i < 8; i++) a[0][i] = a[1][i] = 0.f;
    const bf16* pd = wd + (size_t)(ksl * 448) * DM + 256 * m + cg * 8;
#pragma unroll 8
    for (int k = 0; k < 448; k++) {
      uint4 dv = __ldg(reinterpret_cast<const uint4*>(pd + (size_t)k * DM));
      float x0 = hs[ksl * 448 + k], x1 = hs[FF + ksl * 448 + k];
      float df[8] = {bflo(dv.x), bfhi(dv.x), bflo(dv.y), bfhi(dv.y), bflo(dv.z), bfhi(dv.z), bflo(dv.w), bfhi(dv.w)};
#pragma unroll
      for (int i = 0; i < 8; i++) { a[0][i] += x0 * df[i]; a[1][i] += x1 * df[i]; }
    }
#pragma unroll
    for (int i = 0; i < 8; i++) { red[(ksl * 2 + 0) * 256 + cg * 8 + i] = a[0][i]; red[(ksl * 2 + 1) * 256 + cg * 8 + i] = a[1][i]; }
    __syncthreads();
    for (int i = t; i < 512; i += 256) {
      int tk = i >> 8, col = i & 255;
      float y = 0.f;
#pragma unroll
      for (int q = 0; q < 8; q++) y += red[(q * 2 + tk) * 256 + col];
      float rr = g_r[tk == 0 ? s0 : s1];
      float sg = bfr(1.0f / (1.0f + __expf(-rr)));
      g_upd[tk][256 * m + col] = bfr(bfr(y) * sg);
    }
    if (m == 0 && t == 0) { g_sel[0] = s0; g_sel[1] = s1; }
  }
}

typedef CUresult (*EncodeFn)(CUtensorMap*, CUtensorMapDataType, cuuint32_t, void*, const cuuint64_t*, const cuuint64_t*,
                             const cuuint32_t*, const cuuint32_t*, CUtensorMapInterleave, CUtensorMapSwizzle,
                             CUtensorMapL2promotion, CUtensorMapFloatOOBfill);

static void make_map(EncodeFn enc, CUtensorMap* m, const void* ptr, uint64_t inner, uint64_t outer, uint32_t bi, uint32_t bo) {
  cuuint64_t dims[2] = {inner, outer};
  cuuint64_t strides[1] = {inner * 2};
  cuuint32_t box[2] = {bi, bo};
  cuuint32_t es[2] = {1, 1};
  enc(m, CU_TENSOR_MAP_DATA_TYPE_BFLOAT16, 2, const_cast<void*>(ptr), dims, strides, box, es, CU_TENSOR_MAP_INTERLEAVE_NONE,
      CU_TENSOR_MAP_SWIZZLE_128B, CU_TENSOR_MAP_L2_PROMOTION_L2_256B, CU_TENSOR_MAP_FLOAT_OOB_FILL_NONE);
}

extern "C" void kernel_launch(void* const* d_in, const int* in_sizes, int n_in, void* d_out, int out_size) {
  const bf16* x = (const bf16*)d_in[0];
  const bf16* mem0 = (const bf16*)d_in[1];
  const bf16* Wq = (const bf16*)d_in[2];
  const bf16* Wk = (const bf16*)d_in[3];
  const bf16* Wv = (const bf16*)d_in[4];
  const bf16* Wo = (const bf16*)d_in[5];
  const bf16* w_r = (const bf16*)d_in[8];
  const bf16* wg = (const bf16*)d_in[9];
  const bf16* wu = (const bf16*)d_in[10];
  const bf16* wd = (const bf16*)d_in[11];
  bf16* out = (bf16*)d_out;

  static EncodeFn enc = nullptr;
  static void *p_xn, *p_qkv, *p_otok;
  if (!enc) {
    cudaDriverEntryPointQueryResult qr;
    void* fn = nullptr;
    cudaGetDriverEntryPoint("cuTensorMapEncodeTiled", &fn, cudaEnableDefault, &qr);
    enc = (EncodeFn)fn;
    cudaGetSymbolAddress(&p_xn, g_xn);
    cudaGetSymbolAddress(&p_qkv, g_qkv);
    cudaGetSymbolAddress(&p_otok, g_otok);
    cudaFuncSetAttribute(gemm_kernel<256, 4, 0>, cudaFuncAttributeMaxDynamicSharedMemorySize, GemmSmem<256, 4>::TOTAL);
    cudaFuncSetAttribute(gemm_kernel<128, 6, 1>, cudaFuncAttributeMaxDynamicSharedMemorySize, GemmSmem<128, 6>::TOTAL);
    cudaFuncSetAttribute(chain_kernel, cudaFuncAttributeMaxDynamicSharedMemorySize, CH_SMEM);
  }
  CUtensorMap mA, mQ, mK, mV, mO, mWo;
  make_map(enc, &mA, p_xn, DM, S_LEN, 64, 128);
  make_map(enc, &mQ, Wq, HD, DM, 64, 64);
  make_map(enc, &mK, Wk, HD, DM, 64, 64);
  make_map(enc, &mV, Wv, HD, DM, 64, 64);
  make_map(enc, &mO, p_otok, HD, S_LEN, 64, 128);
  make_map(enc, &mWo, Wo, DM, HD, 64, 64);

  cudaStream_t st = cudaStreamPerThread;
  ln_kernel<<<256, 256, 0, st>>>(x, w_r);
  gemm_kernel<256, 4, 0><<<132, 288, GemmSmem<256, 4>::TOTAL, st>>>(mA, mQ, mK, mV, 16, 16, 16 * 48, nullptr, (bf16*)p_qkv);
  chain_kernel<<<132, 256, CH_SMEM, st>>>(mem0, Wq, Wk, Wv, Wo, wg, wu, wd);
  gemm_kernel<128, 6, 1><<<128, 288, GemmSmem<128, 6>::TOTAL, st>>>(mO, mWo, mWo, mWo, 64, 16, 16 * 8, x, out);
}
```

```cpp
#include <cuda_runtime.h>
#include <cuda_bf16.h>
#include <cuda.h>
#include <stdint.h>

typedef __nv_bfloat16 bf16;

#define S_LEN 2048
#define DM 1024
#define NH 32
#define DH 128
#define NSEG 64
#define SEGL 32
#define HD 4096
#define NQKV 12288
#define FF 3584
#define SENT 0xFFFFFFFFu

__device__ __align__(1024) bf16 g_xn[S_LEN * DM];
__device__ __align__(1024) bf16 g_qkv[(size_t)S_LEN * NQKV];
__device__ __align__(1024) bf16 g_otok[(size_t)S_LEN * HD];
__device__ float g_r[S_LEN];
__device__ __align__(128) uint4 g_bufA[4][128][96];
__device__ __align__(128) uint4 g_bufB[4][128][16][32];
__device__ __align__(128) uint4 g_bufC[4][1024];
__device__ __align__(128) bf16 g_h[2][FF];
__device__ float g_upd[2][DM];
__device__ int g_sel[2];
__device__ unsigned g_moe_cnt;
#define TS(i)

__device__ __forceinline__ float bfr(float x) { return __bfloat162float(__float2bfloat16_rn(x)); }
__device__ __forceinline__ uint32_t pack2(float lo, float hi) {
  __nv_bfloat162 v = __floats2bfloat162_rn(lo, hi);
  return *reinterpret_cast<uint32_t*>(&v);
}
__device__ __forceinline__ float bflo(uint32_t v) { return __uint_as_float(v << 16); }
__device__ __forceinline__ float bfhi(uint32_t v) { return __uint_as_float(v & 0xFFFF0000u); }
__device__ __forceinline__ uint32_t smem_u32(const void* p) { return (uint32_t)__cvta_generic_to_shared(p); }

__device__ __forceinline__ uint4 ld_poll(const uint4* p) {
  uint4 v;
  asm volatile("ld.relaxed.gpu.global.v4.u32 {%0,%1,%2,%3},[%4];" : "=r"(v.x), "=r"(v.y), "=r"(v.z), "=r"(v.w) : "l"(p) : "memory");
  return v;
}
__device__ __forceinline__ void st_pub32(void* p, uint32_t v) {
  asm volatile("st.relaxed.gpu.global.u32 [%0],%1;" ::"l"(p), "r"(v) : "memory");
}
__device__ __forceinline__ void st_pub64(void* p, uint32_t a, uint32_t b) {
  asm volatile("st.relaxed.gpu.global.v2.u32 [%0],{%1,%2};" ::"l"(p), "r"(a), "r"(b) : "memory");
}
__device__ __forceinline__ bool pkt_ok(const uint4& v) { return v.x != SENT && v.y != SENT && v.z != SENT && v.w != SENT; }
__device__ __forceinline__ uint32_t desent(uint32_t v) { return v == SENT ? 0x7FFF7FFFu : v; }

__device__ __forceinline__ void ldsm4(uint32_t& r0, uint32_t& r1, uint32_t& r2, uint32_t& r3, uint32_t addr) {
  asm volatile("ldmatrix.sync.aligned.m8n8.x4.shared.b16 {%0,%1,%2,%3},[%4];" : "=r"(r0), "=r"(r1), "=r"(r2), "=r"(r3) : "r"(addr) : "memory");
}
__device__ __forceinline__ void ldsm4t(uint32_t& r0, uint32_t& r1, uint32_t& r2, uint32_t& r3, uint32_t addr) {
  asm volatile("ldmatrix.sync.aligned.m8n8.x4.trans.shared.b16 {%0,%1,%2,%3},[%4];" : "=r"(r0), "=r"(r1), "=r"(r2), "=r"(r3) : "r"(addr) : "memory");
}
__device__ __forceinline__ void mma16816(float (&d)[4], uint32_t a0, uint32_t a1, uint32_t a2, uint32_t a3, uint32_t b0, uint32_t b1) {
  asm volatile("mma.sync.aligned.m16n8k16.row.col.f32.bf16.bf16.f32 {%0,%1,%2,%3},{%4,%5,%6,%7},{%8,%9},{%0,%1,%2,%3};"
               : "+f"(d[0]), "+f"(d[1]), "+f"(d[2]), "+f"(d[3])
               : "r"(a0), "r"(a1), "r"(a2), "r"(a3), "r"(b0), "r"(b1));
}
__device__ __forceinline__ void cp_async16(uint32_t dst, const void* src) {
  asm volatile("cp.async.cg.shared.global [%0],[%1],16;" ::"r"(dst), "l"(src) : "memory");
}
__device__ __forceinline__ void cp_commit() { asm volatile("cp.async.commit_group;" ::: "memory"); }
template <int N>
__device__ __forceinline__ void cp_wait() { asm volatile("cp.async.wait_group %0;" ::"n"(N) : "memory"); }

__device__ __forceinline__ void mbar_init(uint32_t bar, uint32_t cnt) { asm volatile("mbarrier.init.shared::cta.b64 [%0],%1;" ::"r"(bar), "r"(cnt) : "memory"); }
__device__ __forceinline__ void mbar_expect_tx(uint32_t bar, uint32_t bytes) {
  asm volatile("mbarrier.arrive.expect_tx.shared::cta.b64 _,[%0],%1;" ::"r"(bar), "r"(bytes) : "memory");
}
__device__ __forceinline__ void mbar_arrive(uint32_t bar) { asm volatile("mbarrier.arrive.shared::cta.b64 _,[%0];" ::"r"(bar) : "memory"); }
__device__ __forceinline__ void mbar_wait(uint32_t bar, uint32_t parity) {
  asm volatile(
      "{\n.reg .pred p;\n"
      "WAIT_LOOP:\n"
      "mbarrier.try_wait.parity.shared::cta.b64 p,[%0],%1;\n"
      "@p bra WAIT_DONE;\n"
      "bra WAIT_LOOP;\n"
      "WAIT_DONE:\n}\n" ::"r"(bar), "r"(parity) : "memory");
}
__device__ __forceinline__ void tma_load2d(uint32_t dst, const CUtensorMap* tm, uint32_t bar, int c0, int c1) {
  asm volatile("cp.async.bulk.tensor.2d.shared::cluster.global.mbarrier::complete_tx::bytes [%0],[%1,{%3,%4}],[%2];"
               ::"r"(dst), "l"(tm), "r"(bar), "r"(c0), "r"(c1) : "memory");
}
__device__ __forceinline__ void wg_fence() { asm volatile("wgmma.fence.sync.aligned;" ::: "memory"); }
__device__ __forceinline__ void wg_commit() { asm volatile("wgmma.commit_group.sync.aligned;" ::: "memory"); }
template <int N>
__device__ __forceinline__ void wg_wait() { asm volatile("wgmma.wait_group.sync.aligned %0;" ::"n"(N) : "memory"); }
__device__ __forceinline__ uint64_t make_desc(uint32_t addr, uint32_t lbo, uint32_t sbo) {
  return (uint64_t)((addr & 0x3FFFF) >> 4) | ((uint64_t)(lbo >> 4) << 16) | ((uint64_t)(sbo >> 4) << 32) | (1ull << 62);
}

__device__ __forceinline__ void wgmma_m64n256k16(float (&d)[128], uint64_t da, uint64_t db, int scaleD) {
  asm volatile(
    "{\n.reg .pred p;\nsetp.ne.b32 p, %130, 0;\n"
    "wgmma.mma_async.sync.aligned.m64n256k16.f32.bf16.bf16 "
    "{%0, %1, %2, %3, %4, %5, %6, %7, %8, %9, %10, %11, %12, %13, %14, %15, %16, %17, %18, %19, %20, %21, %22, %23, %24, %25, %26, %27, %28, %29, %30, %31, %32, %33, %34, %35, %36, %37, %38, %39, %40, %41, %42, %43, %44, %45, %46, %47, %48, %49, %50, %51, %52, %53, %54, %55, %56, %57, %58, %59, %60, %61, %62, %63, %64, %65, %66, %67, %68, %69, %70, %71, %72, %73, %74, %75, %76, %77, %78, %79, %80, %81, %82, %83, %84, %85, %86, %87, %88, %89, %90, %91, %92, %93, %94, %95, %96, %97, %98, %99, %100, %101, %102, %103, %104, %105, %106, %107, %108, %109, %110, %111, %112, %113, %114, %115, %116, %117, %118, %119, %120, %121, %122, %123, %124, %125, %126, %127}, %128, %129, p, 1, 1, 0, 1;\n}\n"
    : "+f"(d[0]), "+f"(d[1]), "+f"(d[2]), "+f"(d[3]), "+f"(d[4]), "+f"(d[5]), "+f"(d[6]), "+f"(d[7]), "+f"(d[8]), "+f"(d[9]), "+f"(d[10]), "+f"(d[11]), "+f"(d[12]), "+f"(d[13]), "+f"(d[14]), "+f"(d[15]), "+f"(d[16]), "+f"(d[17]), "+f"(d[18]), "+f"(d[19]), "+f"(d[20]), "+f"(d[21]), "+f"(d[22]), "+f"(d[23]), "+f"(d[24]), "+f"(d[25]), "+f"(d[26]), "+f"(d[27]), "+f"(d[28]), "+f"(d[29]), "+f"(d[30]), "+f"(d[31]), "+f"(d[32]), "+f"(d[33]), "+f"(d[34]), "+f"(d[35]), "+f"(d[36]), "+f"(d[37]), "+f"(d[38]), "+f"(d[39]), "+f"(d[40]), "+f"(d[41]), "+f"(d[42]), "+f"(d[43]), "+f"(d[44]), "+f"(d[45]), "+f"(d[46]), "+f"(d[47]), "+f"(d[48]), "+f"(d[49]), "+f"(d[50]), "+f"(d[51]), "+f"(d[52]), "+f"(d[53]), "+f"(d[54]), "+f"(d[55]), "+f"(d[56]), "+f"(d[57]), "+f"(d[58]), "+f"(d[59]), "+f"(d[60]), "+f"(d[61]), "+f"(d[62]), "+f"(d[63]), "+f"(d[64]), "+f"(d[65]), "+f"(d[66]), "+f"(d[67]), "+f"(d[68]), "+f"(d[69]), "+f"(d[70]), "+f"(d[71]), "+f"(d[72]), "+f"(d[73]), "+f"(d[74]), "+f"(d[75]), "+f"(d[76]), "+f"(d[77]), "+f"(d[78]), "+f"(d[79]), "+f"(d[80]), "+f"(d[81]), "+f"(d[82]), "+f"(d[83]), "+f"(d[84]), "+f"(d[85]), "+f"(d[86]), "+f"(d[87]), "+f"(d[88]), "+f"(d[89]), "+f"(d[90]), "+f"(d[91]), "+f"(d[92]), "+f"(d[93]), "+f"(d[94]), "+f"(d[95]), "+f"(d[96]), "+f"(d[97]), "+f"(d[98]), "+f"(d[99]), "+f"(d[100]), "+f"(d[101]), "+f"(d[102]), "+f"(d[103]), "+f"(d[104]), "+f"(d[105]), "+f"(d[106]), "+f"(d[107]), "+f"(d[108]), "+f"(d[109]), "+f"(d[110]), "+f"(d[111]), "+f"(d[112]), "+f"(d[113]), "+f"(d[114]), "+f"(d[115]), "+f"(d[116]), "+f"(d[117]), "+f"(d[118]), "+f"(d[119]), "+f"(d[120]), "+f"(d[121]), "+f"(d[122]), "+f"(d[123]), "+f"(d[124]), "+f"(d[125]), "+f"(d[126]), "+f"(d[127])
    : "l"(da), "l"(db), "r"(scaleD));
}

__device__ __forceinline__ void wgmma_m64n128k16(float (&d)[64], uint64_t da, uint64_t db, int scaleD) {
  asm volatile(
    "{\n.reg .pred p;\nsetp.ne.b32 p, %66, 0;\n"
    "wgmma.mma_async.sync.aligned.m64n128k16.f32.bf16.bf16 "
    "{%0, %1, %2, %3, %4, %5, %6, %7, %8, %9, %10, %11, %12, %13, %14, %15, %16, %17, %18, %19, %20, %21, %22, %23, %24, %25, %26, %27, %28, %29, %30, %31, %32, %33, %34, %35, %36, %37, %38, %39, %40, %41, %42, %43, %44, %45, %46, %47, %48, %49, %50, %51, %52, %53, %54, %55, %56, %57, %58, %59, %60, %61, %62, %63}, %64, %65, p, 1, 1, 0, 1;\n}\n"
    : "+f"(d[0]), "+f"(d[1]), "+f"(d[2]), "+f"(d[3]), "+f"(d[4]), "+f"(d[5]), "+f"(d[6]), "+f"(d[7]), "+f"(d[8]), "+f"(d[9]), "+f"(d[10]), "+f"(d[11]), "+f"(d[12]), "+f"(d[13]), "+f"(d[14]), "+f"(d[15]), "+f"(d[16]), "+f"(d[17]), "+f"(d[18]), "+f"(d[19]), "+f"(d[20]), "+f"(d[21]), "+f"(d[22]), "+f"(d[23]), "+f"(d[24]), "+f"(d[25]), "+f"(d[26]), "+f"(d[27]), "+f"(d[28]), "+f"(d[29]), "+f"(d[30]), "+f"(d[31]), "+f"(d[32]), "+f"(d[33]), "+f"(d[34]), "+f"(d[35]), "+f"(d[36]), "+f"(d[37]), "+f"(d[38]), "+f"(d[39]), "+f"(d[40]), "+f"(d[41]), "+f"(d[42]), "+f"(d[43]), "+f"(d[44]), "+f"(d[45]), "+f"(d[46]), "+f"(d[47]), "+f"(d[48]), "+f"(d[49]), "+f"(d[50]), "+f"(d[51]), "+f"(d[52]), "+f"(d[53]), "+f"(d[54]), "+f"(d[55]), "+f"(d[56]), "+f"(d[57]), "+f"(d[58]), "+f"(d[59]), "+f"(d[60]), "+f"(d[61]), "+f"(d[62]), "+f"(d[63])
    : "l"(da), "l"(db), "r"(scaleD));
}

template <int BN> struct WG;
template <> struct WG<256> { static __device__ __forceinline__ void mma(float (&d)[128], uint64_t a, uint64_t b, int s) { wgmma_m64n256k16(d, a, b, s); } };
template <> struct WG<128> { static __device__ __forceinline__ void mma(float (&d)[64], uint64_t a, uint64_t b, int s) { wgmma_m64n128k16(d, a, b, s); } };

__global__ void __launch_bounds__(256) ln_kernel(const bf16* __restrict__ x, const bf16* __restrict__ w_r) {
  int warp = threadIdx.x >> 5, lane = threadIdx.x & 31;
  int row = blockIdx.x * 8 + warp;
  const uint4* xp = reinterpret_cast<const uint4*>(x + (size_t)row * DM);
  uint4 v[4];
#pragma unroll
  for (int i = 0; i < 4; i++) v[i] = xp[lane + 32 * i];
  float f[32];
#pragma unroll
  for (int i = 0; i < 4; i++) {
    f[8 * i + 0] = bflo(v[i].x); f[8 * i + 1] = bfhi(v[i].x);
    f[8 * i + 2] = bflo(v[i].y); f[8 * i + 3] = bfhi(v[i].y);
    f[8 * i + 4] = bflo(v[i].z); f[8 * i + 5] = bfhi(v[i].z);
    f[8 * i + 6] = bflo(v[i].w); f[8 * i + 7] = bfhi(v[i].w);
  }
  float s = 0.f;
#pragma unroll
  for (int i = 0; i < 32; i++) s += f[i];
#pragma unroll
  for (int o = 16; o > 0; o >>= 1) s += __shfl_xor_sync(0xffffffffu, s, o);
  float mean = s * (1.0f / DM);
  float q = 0.f;
#pragma unroll
  for (int i = 0; i < 32; i++) { float d = f[i] - mean; q += d * d; }
#pragma unroll
  for (int o = 16; o > 0; o >>= 1) q += __shfl_xor_sync(0xffffffffu, q, o);
  float var = bfr(q * (1.0f / DM));
  float mb = bfr(mean);
  float den = bfr(sqrtf(bfr(var + 1e-5f)));
  const uint4* wp = reinterpret_cast<const uint4*>(w_r);
  uint4* op = reinterpret_cast<uint4*>(g_xn + (size_t)row * DM);
  float r = 0.f;
#pragma unroll
  for (int i = 0; i < 4; i++) {
    uint4 w = wp[lane + 32 * i];
    float y[8];
#pragma unroll
    for (int k = 0; k < 8; k++) y[k] = bfr(bfr(f[8 * i + k] - mb) / den);
    r += y[0] * bflo(w.x) + y[1] * bfhi(w.x) + y[2] * bflo(w.y) + y[3] * bfhi(w.y) + y[4] * bflo(w.z) + y[5] * bfhi(w.z) +
         y[6] * bflo(w.w) + y[7] * bfhi(w.w);
    op[lane + 32 * i] = make_uint4(pack2(y[0], y[1]), pack2(y[2], y[3]), pack2(y[4], y[5]), pack2(y[6], y[7]));
  }
#pragma unroll
  for (int o = 16; o > 0; o >>= 1) r += __shfl_xor_sync(0xffffffffu, r, o);
  if (lane == 0) g_r[row] = bfr(r);
  int gt = blockIdx.x * 256 + threadIdx.x;
  const uint4 sv = make_uint4(SENT, SENT, SENT, SENT);
  uint4* a = &g_bufA[0][0][0];
  for (int i = gt; i < 2 * 128 * 96; i += 65536) a[i] = sv;
  uint4* b = &g_bufB[0][0][0][0];
  for (int i = gt; i < 2 * 128 * 32 * 16; i += 65536) b[i] = sv;
  uint4* c = &g_bufC[0][0];
  for (int i = gt; i < 2 * 1024; i += 65536) c[i] = sv;
  if (gt == 0) g_moe_cnt = 0;
}

template <int BN, int STAGES>
struct GemmSmem {
  static constexpr int A_BYTES = 128 * 64 * 2;
  static constexpr int B_BYTES = 64 * BN * 2;
  static constexpr int STAGE_BYTES = A_BYTES + B_BYTES;
  static constexpr int TOTAL = STAGES * STAGE_BYTES + 1024 + 256;
};

__device__ __forceinline__ void quad_transpose(uint32_t (&v)[4], int c) {
  {
    uint32_t s0 = (c & 1) ? v[0] : v[1];
    uint32_t s1 = (c & 1) ? v[2] : v[3];
    uint32_t r0 = __shfl_xor_sync(0xffffffffu, s0, 1);
    uint32_t r1 = __shfl_xor_sync(0xffffffffu, s1, 1);
    if (c & 1) { v[0] = r0; v[2] = r1; } else { v[1] = r0; v[3] = r1; }
  }
  {
    uint32_t s0 = (c & 2) ? v[0] : v[2];
    uint32_t s1 = (c & 2) ? v[1] : v[3];
    uint32_t r0 = __shfl_xor_sync(0xffffffffu, s0, 2);
    uint32_t r1 = __shfl_xor_sync(0xffffffffu, s1, 2);
    if (c & 2) { v[0] = r0; v[1] = r1; } else { v[2] = r0; v[3] = r1; }
  }
}

__device__ __forceinline__ uint32_t add3(uint32_t a, uint32_t x, uint32_t b) {
  float lo = bfr(bflo(x) + bflo(a)) + bflo(b);
  float hi = bfr(bfhi(x) + bfhi(a)) + bfhi(b);
  return pack2(lo, hi);
}

template <int BN, int STAGES, int EPI>
__global__ void __launch_bounds__(288, 1)
gemm_kernel(const __grid_constant__ CUtensorMap tmA, const __grid_constant__ CUtensorMap tmB0,
            const __grid_constant__ CUtensorMap tmB1, const __grid_constant__ CUtensorMap tmB2,
            int kblocks, int tiles_m, int tiles_total, const bf16* __restrict__ xin, bf16* __restrict__ outp) {
  using SM = GemmSmem<BN, STAGES>;
  extern __shared__ uint8_t smem_raw[];
  uint32_t base = (smem_u32(smem_raw) + 1023) & ~1023u;
  uint32_t bars = base + STAGES * SM::STAGE_BYTES;
  int warp = threadIdx.x >> 5, lane = threadIdx.x & 31;
  if (threadIdx.x == 0) {
    for (int i = 0; i < STAGES; i++) { mbar_init(bars + 8 * i, 1); mbar_init(bars + 8 * (STAGES + i), 8); }
    asm volatile("fence.mbarrier_init.release.cluster;" ::: "memory");
  }
  __syncthreads();
  if (warp == 8) {
    if (lane == 0) {
      int it = 0;
      for (int t = blockIdx.x; t < tiles_total; t += gridDim.x) {
        int tm = t % tiles_m, tn = t / tiles_m;
        int n0 = tn * BN;
        const CUtensorMap* tb = &tmB0;
        if (EPI == 0) { int wsel = n0 >> 12; tb = wsel == 0 ? &tmB0 : (wsel == 1 ? &tmB1 : &tmB2); n0 &= 4095; }
        for (int kb = 0; kb < kblocks; kb++, it++) {
          int st = it % STAGES; uint32_t ph = (it / STAGES) & 1;
          mbar_wait(bars + 8 * (STAGES + st), ph ^ 1);
          uint32_t sa = base + st * SM::STAGE_BYTES, sb = sa + SM::A_BYTES;
          mbar_expect_tx(bars + 8 * st, SM::STAGE_BYTES);
          tma_load2d(sa, &tmA, bars + 8 * st, kb * 64, tm * 128);
#pragma unroll
          for (int i = 0; i < BN / 64; i++) tma_load2d(sb + i * 8192, tb, bars + 8 * st, n0 + i * 64, kb * 64);
        }
      }
    }
  } else {
    int wg = warp >> 2;
    int g = lane >> 2, c = lane & 3;
    int it = 0;
    float acc[BN / 2];
    for (int t = blockIdx.x; t < tiles_total; t += gridDim.x) {
      int tm = t % tiles_m, tn = t / tiles_m;
      for (int kb = 0; kb < kblocks; kb++, it++) {
        int st = it % STAGES; uint32_t ph = (it / STAGES) & 1;
        mbar_wait(bars + 8 * st, ph);
        uint32_t sa = base + st * SM::STAGE_BYTES + wg * 8192, sb = base + st * SM::STAGE_BYTES + SM::A_BYTES;
        wg_fence();
#pragma unroll
        for (int kk = 0; kk < 4; kk++) {
          uint64_t da = make_desc(sa + kk * 32, 16, 1024);
          uint64_t db = make_desc(sb + kk * 2048, 8192, 1024);
          WG<BN>::mma(acc, da, db, (kb | kk) != 0);
        }
        wg_commit();
        if (kb > 0) {
          wg_wait<1>();
          int pst = (it - 1) % STAGES;
          if (lane == 0) mbar_arrive(bars + 8 * (STAGES + pst));
        }
      }
      wg_wait<0>();
      { int pst = (it - 1) % STAGES; if (lane == 0) mbar_arrive(bars + 8 * (STAGES + pst)); }
      int row0 = tm * 128 + wg * 64 + (warp & 3) * 16 + g;
      int sel0 = -1, sel1 = -1;
      if (EPI == 1) { sel0 = g_sel[0]; sel1 = g_sel[1]; }
#pragma unroll
      for (int half = 0; half < 2; half++) {
        int row = row0 + half * 8;
#pragma unroll
        for (int q = 0; q < BN / 32; q++) {
          uint32_t v[4];
#pragma unroll
          for (int tt = 0; tt < 4; tt++) v[tt] = pack2(acc[(q * 4 + tt) * 4 + half * 2], acc[(q * 4 + tt) * 4 + half * 2 + 1]);
          quad_transpose(v, c);
          int col = tn * BN + q * 32 + c * 8;
          if (EPI == 0) {
            *reinterpret_cast<uint4*>(outp + (size_t)row * NQKV + col) = make_uint4(v[0], v[1], v[2], v[3]);
          } else {
            uint4 xv = *reinterpret_cast<const uint4*>(xin + (size_t)row * DM + col);
            uint4 bv = *reinterpret_cast<const uint4*>(g_xn + (size_t)row * DM + col);
            if (row == sel0 || row == sel1) {
              const float* u = &g_upd[row == sel0 ? 0 : 1][col];
              bv.x = pack2(bflo(bv.x) + u[0], bfhi(bv.x) + u[1]);
              bv.y = pack2(bflo(bv.y) + u[2], bfhi(bv.y) + u[3]);
              bv.z = pack2(bflo(bv.z) + u[4], bfhi(bv.z) + u[5]);
              bv.w = pack2(bflo(bv.w) + u[6], bfhi(bv.w) + u[7]);
            }
            uint4 o = make_uint4(add3(v[0], xv.x, bv.x), add3(v[1], xv.y, bv.y), add3(v[2], xv.z, bv.z), add3(v[3], xv.w, bv.w));
            *reinterpret_cast<uint4*>(outp + (size_t)row * DM + col) = o;
          }
        }
      }
    }
  }
}

#define RK 10
#define SK (16 - RK)
#define TP 272
#define OFF_WQS 0
#define OFF_MEMT (OFF_WQS + 8 * SK * 3 * 512)
#define OFF_RED (OFF_MEMT + 16384)
#define OFF_QKVM (OFF_RED + 12288)
#define OFF_TOK (OFF_QKVM + 6144)
#define TOK_BYTES (72 * TP)
#define OFF_SA (OFF_TOK + 2 * TOK_BYTES)
#define OFF_BAR (OFF_SA + 8 * TP)
#define CH_END (OFF_BAR + 64)
#define CH_STG2 (131072)
#define CH_SMEM (196608 + 1024)
static_assert(CH_END <= CH_SMEM, "smem");

__device__ void moe_part(int m, const bf16* __restrict__ wg, const bf16* __restrict__ wu, const bf16* __restrict__ wd, uint8_t* smem);

__device__ __forceinline__ void bulk_copy(uint32_t dst, const void* src, uint32_t bytes, uint32_t bar) {
  asm volatile("cp.async.bulk.shared::cluster.global.mbarrier::complete_tx::bytes [%0],[%1],%2,[%3];"
               ::"r"(dst), "l"(src), "r"(bytes), "r"(bar) : "memory");
}
__device__ __forceinline__ void st_pub128(void* p, uint32_t v) {
  asm volatile("st.relaxed.gpu.global.v4.u32 [%0],{%1,%1,%1,%1};" ::"l"(p), "r"(v) : "memory");
}
__device__ __forceinline__ void sts128(uint32_t addr, const uint4& v) {
  asm volatile("st.shared.v4.u32 [%0],{%1,%2,%3,%4};" ::"r"(addr), "r"(v.x), "r"(v.y), "r"(v.z), "r"(v.w) : "memory");
}

#define POLL_MAX (1 << 22)

__device__ __forceinline__ float ex2f(float x) { float y; asm("ex2.approx.ftz.f32 %0,%1;" : "=f"(y) : "f"(x)); return y; }
__device__ __forceinline__ float rcpf(float x) { float y; asm("rcp.approx.ftz.f32 %0,%1;" : "=f"(y) : "f"(x)); return y; }
template <bool TOK>
__device__ __forceinline__ void attn8(uint32_t sb, uint32_t tok, int lane, int wq4, int tr, bf16* otok_row) {
  const int g = lane >> 2, c = lane & 3;
  float sc[5][4];
#pragma unroll
  for (int n = 0; n < 5; n++)
#pragma unroll
    for (int i = 0; i < 4; i++) sc[n][i] = 0.f;
  const uint32_t tokrow = tok + (lane & 7) * TP + (lane >> 3) * 16;
  const uint32_t qaddr = TOK ? (tok + (64 + (lane & 7)) * TP + (lane >> 4) * 16) : (sb + OFF_QKVM + ((lane & 7) + 8 * (lane >> 4)) * 16);
#pragma unroll
  for (int kp = 0; kp < 4; kp++) {
    uint32_t q0[4], q1[4], km[4], kt[4][4];
    if (TOK) {
      ldsm4(q0[0], q0[1], q0[2], q0[3], qaddr + 64 * kp);
      ldsm4(q1[0], q1[1], q1[2], q1[3], qaddr + 64 * kp + 32);
    } else {
      ldsm4t(q0[0], q0[1], q0[2], q0[3], qaddr + 512 * kp);
      ldsm4t(q1[0], q1[1], q1[2], q1[3], qaddr + 512 * kp + 256);
    }
    ldsm4t(km[0], km[1], km[2], km[3], sb + OFF_QKVM + (128 + 32 * kp + lane) * 16);
#pragma unroll
    for (int n = 0; n < 4; n++) ldsm4(kt[n][0], kt[n][1], kt[n][2], kt[n][3], tokrow + 8 * n * TP + 64 * kp);
    mma16816(sc[0], q0[0], q0[1], q0[2], q0[3], km[0], km[1]);
#pragma unroll
    for (int n = 0; n < 4; n++) mma16816(sc[n + 1], q0[0], q0[1], q0[2], q0[3], kt[n][0], kt[n][1]);
    mma16816(sc[0], q1[0], q1[1], q1[2], q1[3], km[2], km[3]);
#pragma unroll
    for (int n = 0; n < 4; n++) mma16816(sc[n + 1], q1[0], q1[1], q1[2], q1[3], kt[n][2], kt[n][3]);
  }
  uint32_t vma[4], vmb[4], vt[4][4];
  ldsm4(vma[0], vma[1], vma[2], vma[3], sb + OFF_QKVM + (256 + 32 * wq4 + lane) * 16);
  ldsm4(vmb[0], vmb[1], vmb[2], vmb[3], sb + OFF_QKVM + (256 + 32 * wq4 + (lane ^ 8)) * 16);
#pragma unroll
  for (int n = 0; n < 4; n++) ldsm4t(vt[n][0], vt[n][1], vt[n][2], vt[n][3], tok + (32 + lane) * TP + (32 * wq4 + 8 * n) * 2);
  const float scale = 0.08838834764831845f;
  float m0 = -3.0e38f;
#pragma unroll
  for (int n = 0; n < 5; n++) {
    uint32_t p1 = pack2(sc[n][0], sc[n][1]);
    uint32_t p2 = pack2(bflo(p1) * scale, bfhi(p1) * scale);
    sc[n][0] = bflo(p2);
    sc[n][1] = bfhi(p2);
    if (TOK && n > 0) {
      int kt = 8 * (n - 1) + 2 * c;
      if (kt > tr) sc[n][0] = -1.0e9f;
      if (kt + 1 > tr) sc[n][1] = -1.0e9f;
    }
    m0 = fmaxf(m0, fmaxf(sc[n][0], sc[n][1]));
  }
  m0 = fmaxf(m0, __shfl_xor_sync(0xffffffffu, m0, 1));
  m0 = fmaxf(m0, __shfl_xor_sync(0xffffffffu, m0, 2));
  const float l2e = 1.4426950408889634f;
  float s0 = 0.f;
#pragma unroll
  for (int n = 0; n < 5; n++) {
    sc[n][0] = ex2f((sc[n][0] - m0) * l2e);
    sc[n][1] = ex2f((sc[n][1] - m0) * l2e);
    s0 += sc[n][0] + sc[n][1];
  }
  s0 += __shfl_xor_sync(0xffffffffu, s0, 1);
  s0 += __shfl_xor_sync(0xffffffffu, s0, 2);
  const float i0 = rcpf(s0);
  uint32_t pp[5];
#pragma unroll
  for (int n = 0; n < 5; n++) pp[n] = pack2(sc[n][0] * i0, sc[n][1] * i0);
  float o[4][4];
#pragma unroll
  for (int n = 0; n < 4; n++) {
#pragma unroll
    for (int i = 0; i < 4; i++) o[n][i] = 0.f;
    mma16816(o[n], pp[1], pp[1], pp[2], pp[2], vt[n][0], vt[n][1]);
  }
#pragma unroll
  for (int n = 0; n < 4; n++) mma16816(o[n], pp[3], pp[3], pp[4], pp[4], vt[n][2], vt[n][3]);
  mma16816(o[0], pp[0], 0u, 0u, 0u, vma[0], vma[1]);
  mma16816(o[1], pp[0], 0u, 0u, 0u, vmb[0], vmb[1]);
  mma16816(o[2], pp[0], 0u, 0u, 0u, vma[2], vma[3]);
  mma16816(o[3], pp[0], 0u, 0u, 0u, vmb[2], vmb[3]);
#pragma unroll
  for (int n = 0; n < 4; n++) {
    const int e = 32 * wq4 + 8 * n + 2 * c;
    if (TOK) *reinterpret_cast<uint32_t*>(otok_row + e) = pack2(o[n][0], o[n][1]);
    else asm volatile("st.shared.u32 [%0],%1;" ::"r"(sb + OFF_SA + g * TP + e * 2), "r"(pack2(o[n][0], o[n][1])) : "memory");
  }
}

__global__ void __launch_bounds__(256, 1)
chain_kernel(const bf16* __restrict__ mem0, const bf16* __restrict__ Wq, const bf16* __restrict__ Wk, const bf16* __restrict__ Wv,
             const bf16* __restrict__ Wo, const bf16* __restrict__ wgate, const bf16* __restrict__ wup, const bf16* __restrict__ wdown) {
  extern __shared__ __align__(1024) uint8_t smem[];
  const int cta = blockIdx.x, t = threadIdx.x, warp = t >> 5, lane = t & 31;
  if (cta >= 128) {
    moe_part(cta - 128, wgate, wup, wdown, smem);
    return;
  }
  const int h = cta >> 2, j = cta & 3;
  const int g = lane >> 2, c = lane & 3;
  const uint32_t sb = smem_u32(smem);
  const int mg = warp & 1, kq = warp >> 1;

  uint32_t wq[RK][3][4];
  uint32_t wo[2][8][4];
  {
    for (int i = t; i < 3 * 1024 * 4; i += 256) {
      int which = i >> 12, k = (i >> 2) & 1023, ch = i & 3;
      const bf16* W = which == 0 ? Wq : (which == 1 ? Wk : Wv);
      cp_async16(sb + (which * 1024 + k) * 64 + ch * 16, W + (size_t)k * HD + h * 128 + 32 * j + ch * 8);
    }
    cp_commit(); cp_wait<0>();
    __syncthreads();
    uint32_t tmp[SK][3][4];
#pragma unroll
    for (int ks = 0; ks < 16; ks++) {
#pragma unroll
      for (int tt = 0; tt < 3; tt++) {
        int tile = 3 * mg + tt;
        int which = tile >> 1, ch = tile & 1;
        int k = (16 * kq + ks) * 16 + (lane & 7) + 8 * (lane >> 4);
        uint32_t addr = sb + (which * 1024 + k) * 64 + ch * 32 + 16 * ((lane >> 3) & 1);
        if (ks < RK) ldsm4t(wq[ks][tt][0], wq[ks][tt][1], wq[ks][tt][2], wq[ks][tt][3], addr);
        else ldsm4t(tmp[ks - RK][tt][0], tmp[ks - RK][tt][1], tmp[ks - RK][tt][2], tmp[ks - RK][tt][3], addr);
      }
    }
    __syncthreads();
#pragma unroll
    for (int ks = 0; ks < SK; ks++)
#pragma unroll
      for (int tt = 0; tt < 3; tt++)
        *reinterpret_cast<uint4*>(smem + OFF_WQS + (((warp * SK + ks) * 3 + tt) * 32 + lane) * 16) =
            make_uint4(tmp[ks][tt][0], tmp[ks][tt][1], tmp[ks][tt][2], tmp[ks][tt][3]);
    for (int i = t; i < 128 * 32; i += 256) {
      int e = i >> 5, ch = i & 31;
      cp_async16(sb + CH_STG2 + e * 512 + ch * 16, Wo + (size_t)(h * 128 + e) * DM + 256 * j + ch * 8);
    }
    cp_commit(); cp_wait<0>();
    __syncthreads();
#pragma unroll
    for (int tt = 0; tt < 2; tt++)
#pragma unroll
      for (int ks = 0; ks < 8; ks++) {
        int e = 16 * ks + (lane & 7) + 8 * (lane >> 4);
        uint32_t addr = sb + CH_STG2 + e * 512 + (32 * warp + 16 * tt + 8 * ((lane >> 3) & 1)) * 2;
        ldsm4t(wo[tt][ks][0], wo[tt][ks][1], wo[tt][ks][2], wo[tt][ks][3], addr);
      }
    if (t == 0) {
      mbar_init(sb + OFF_BAR, 1); mbar_init(sb + OFF_BAR + 8, 1);
      asm volatile("fence.mbarrier_init.release.cluster;" ::: "memory");
    }
    __syncthreads();
    asm volatile("fence.proxy.async.shared::cta;" ::: "memory");
  }
  auto prefetch_tok = [&](int s) {
    const int i = t - 192;
    const uint32_t dst = sb + OFF_TOK + (s & 1) * TOK_BYTES + (i >> 4) * TP + (i & 15) * 16;
    const bf16* src = g_qkv + (size_t)(s * 32 + (i >> 4)) * NQKV + HD + h * 128 + (i & 15) * 8;
#pragma unroll
    for (int r = 0; r < 8; r++) {
      cp_async16(dst + 4 * r * TP, src + (size_t)4 * r * NQKV);
      cp_async16(dst + (32 + 4 * r) * TP, src + (size_t)4 * r * NQKV + HD);
    }
    cp_async16(dst + 64 * TP, src + (size_t)(8 * j) * NQKV - HD);
    cp_async16(dst + 68 * TP, src + (size_t)(8 * j + 4) * NQKV - HD);
    cp_commit();
  };
  if (warp >= 6) prefetch_tok(0);
  for (int i = t; i < 8 * 1024; i += 256) {
    int r = i >> 10, k = i & 1023;
    reinterpret_cast<bf16*>(smem + OFF_MEMT)[k * 8 + r] = mem0[i];
  }
  __syncthreads();
  uint32_t p2dst0, p2dst1;
  {
    int p = t, jj = p / 96, f = p % 96;
    p2dst0 = sb + OFF_QKVM + ((f >> 5) * 128 + 32 * jj + (f & 31)) * 16;
    p = 256 + (t & 127); jj = p / 96; f = p % 96;
    p2dst1 = sb + OFF_QKVM + ((f >> 5) * 128 + 32 * jj + (f & 31)) * 16;
  }
  const int p0idx = 256 * kq + 128 * mg + lane;
  TS(0);
  for (int s = 0; s < NSEG; s++) {
    const int slot = s & 3, slot2 = (s + 2) & 3;
    if (s > 0) {
      const uint4* src = &g_bufC[(s - 1) & 3][p0idx];
      uint4 v[4];
#pragma unroll
      for (int i = 0; i < 4; i++) v[i] = ld_poll(src + 32 * i);
      int it = 0;
      while (!(pkt_ok(v[0]) && pkt_ok(v[1]) && pkt_ok(v[2]) && pkt_ok(v[3])) && ++it < POLL_MAX) {
#pragma unroll
        for (int i = 0; i < 4; i++)
          if (!pkt_ok(v[i])) v[i] = ld_poll(src + 32 * i);
      }
#pragma unroll
      for (int i = 0; i < 4; i++) sts128(sb + OFF_MEMT + (p0idx + 32 * i) * 16, v[i]);
      TS(1);
      asm volatile("bar.sync %0, 64;" ::"r"(1 + kq) : "memory");
      TS(2);
    }
    {
      float acc[2][3][4];
#pragma unroll
      for (int a = 0; a < 2; a++)
#pragma unroll
        for (int tt = 0; tt < 3; tt++)
#pragma unroll
          for (int i = 0; i < 4; i++) acc[a][tt][i] = 0.f;
      uint4 sa[SK][3];
#pragma unroll
      for (int kp = 0; kp < 8; kp++) {
        uint32_t b0, b1, b2, b3;
        ldsm4t(b0, b1, b2, b3, sb + OFF_MEMT + ((16 * kq + 2 * kp) * 16 + lane) * 16);
#pragma unroll
        for (int u = 0; u < 2; u++) {
          int ks = 2 * (kp + 1) + u;
          if (ks >= RK && ks < 16) {
#pragma unroll
            for (int tt = 0; tt < 3; tt++)
              sa[ks - RK][tt] = *reinterpret_cast<const uint4*>(smem + OFF_WQS + (((warp * SK + (ks - RK)) * 3 + tt) * 32 + lane) * 16);
          }
        }
#pragma unroll
        for (int u = 0; u < 2; u++) {
          int ks = 2 * kp + u;
#pragma unroll
          for (int tt = 0; tt < 3; tt++) {
            if (ks < RK) mma16816(acc[u][tt], wq[ks][tt][0], wq[ks][tt][1], wq[ks][tt][2], wq[ks][tt][3], u ? b2 : b0, u ? b3 : b1);
            else mma16816(acc[u][tt], sa[ks - RK][tt].x, sa[ks - RK][tt].y, sa[ks - RK][tt].z, sa[ks - RK][tt].w, u ? b2 : b0, u ? b3 : b1);
          }
        }
      }
#pragma unroll
      for (int tt = 0; tt < 3; tt++)
        *reinterpret_cast<float4*>(smem + OFF_RED + ((kq * 6 + 3 * mg + tt) * 32 + lane) * 16) =
            make_float4(acc[0][tt][0] + acc[1][tt][0], acc[0][tt][1] + acc[1][tt][1], acc[0][tt][2] + acc[1][tt][2], acc[0][tt][3] + acc[1][tt][3]);
    }
    TS(3);
    __syncthreads();
    TS(4);
    if (warp < 6) {
      float4 r = *reinterpret_cast<const float4*>(smem + OFF_RED + ((0 * 6 + warp) * 32 + lane) * 16);
#pragma unroll
      for (int q = 1; q < 4; q++) {
        float4 x = *reinterpret_cast<const float4*>(smem + OFF_RED + ((q * 6 + warp) * 32 + lane) * 16);
        r.x += x.x; r.y += x.y; r.z += x.z; r.w += x.w;
      }
      uint32_t* dst = reinterpret_cast<uint32_t*>(&g_bufA[slot][cta][16 * warp + g]) + c;
      st_pub32(dst, desent(pack2(r.x, r.y)));
      st_pub32(dst + 32, desent(pack2(r.z, r.w)));
    } else {
      const int i = t - 192;
      st_pub128(&g_bufA[slot2][cta][i], SENT);
      if (i < 32) st_pub128(&g_bufA[slot2][cta][64 + i], SENT);
    }
    {
      const uint4* src = &g_bufA[slot][4 * h][t];
      uint4 v0 = ld_poll(src);
      uint4 v1 = make_uint4(0, 0, 0, 0);
      if (t < 128) v1 = ld_poll(src + 256);
      int it = 0;
      while (!(pkt_ok(v0) && pkt_ok(v1)) && ++it < POLL_MAX) {
        if (!pkt_ok(v0)) v0 = ld_poll(src);
        if (!pkt_ok(v1)) v1 = ld_poll(src + 256);
      }
      sts128(p2dst0, v0);
      if (t < 128) sts128(p2dst1, v1);
    }
    TS(5);
    if (warp >= 6) cp_wait<0>();
    __syncthreads();
    TS(6);
    const uint32_t tok = sb + OFF_TOK + (s & 1) * TOK_BYTES;
    if (s < NSEG - 1) {
      if (warp < 4) attn8<false>(sb, tok, lane, warp, 0, nullptr);
      else if (warp >= 6) prefetch_tok(s + 1);
      TS(7);
      __syncthreads();
      TS(8);
      {
        float acc[2][2][4];
#pragma unroll
        for (int a = 0; a < 2; a++)
#pragma unroll
          for (int tt = 0; tt < 2; tt++)
#pragma unroll
            for (int i = 0; i < 4; i++) acc[a][tt][i] = 0.f;
        uint32_t b[4][4];
#pragma unroll
        for (int kp = 0; kp < 4; kp++) ldsm4(b[kp][0], b[kp][1], b[kp][2], b[kp][3], sb + OFF_SA + (lane & 7) * TP + (32 * kp + 8 * (lane >> 3)) * 2);
#pragma unroll
        for (int kp = 0; kp < 4; kp++) {
#pragma unroll
          for (int tt = 0; tt < 2; tt++) {
            mma16816(acc[0][tt], wo[tt][2 * kp][0], wo[tt][2 * kp][1], wo[tt][2 * kp][2], wo[tt][2 * kp][3], b[kp][0], b[kp][1]);
            mma16816(acc[1][tt], wo[tt][2 * kp + 1][0], wo[tt][2 * kp + 1][1], wo[tt][2 * kp + 1][2], wo[tt][2 * kp + 1][3], b[kp][2], b[kp][3]);
          }
        }
        const int off = h * 32 + lane;
#pragma unroll
        for (int tt = 0; tt < 2; tt++) {
          int r0 = 32 * j + 4 * warp + 2 * tt;
          uint32_t x0 = __float_as_uint(acc[0][tt][0] + acc[1][tt][0]), x1 = __float_as_uint(acc[0][tt][1] + acc[1][tt][1]);
          uint32_t x2 = __float_as_uint(acc[0][tt][2] + acc[1][tt][2]), x3 = __float_as_uint(acc[0][tt][3] + acc[1][tt][3]);
          x0 = x0 == SENT ? 0x7FFFFFFFu : x0; x1 = x1 == SENT ? 0x7FFFFFFFu : x1;
          x2 = x2 == SENT ? 0x7FFFFFFFu : x2; x3 = x3 == SENT ? 0x7FFFFFFFu : x3;
          st_pub64(reinterpret_cast<uint2*>(&g_bufB[slot][r0][0][0]) + off, x0, x1);
          st_pub64(reinterpret_cast<uint2*>(&g_bufB[slot][r0 + 1][0][0]) + off, x2, x3);
        }
#pragma unroll
        for (int tt = 0; tt < 4; tt++)
          st_pub64(reinterpret_cast<uint2*>(&g_bufB[slot2][32 * j + 4 * warp + tt][0][0]) + off, SENT, SENT);
      }
      TS(9);
      {
        const uint4* src = &g_bufB[slot][cta][0][0] + 16 * lane + 2 * warp;
        uint4 v0 = ld_poll(src), v1 = ld_poll(src + 1);
        int it = 0;
        while (!(pkt_ok(v0) && pkt_ok(v1)) && ++it < POLL_MAX) {
          if (!pkt_ok(v0)) v0 = ld_poll(src);
          if (!pkt_ok(v1)) v1 = ld_poll(src + 1);
        }
        TS(10);
        const bool hi = lane & 16;
        float a0 = __uint_as_float(hi ? v1.x : v0.x), a1 = __uint_as_float(hi ? v1.y : v0.y);
        float a2 = __uint_as_float(hi ? v1.z : v0.z), a3 = __uint_as_float(hi ? v1.w : v0.w);
        float b0 = __uint_as_float(hi ? v0.x : v1.x), b1 = __uint_as_float(hi ? v0.y : v1.y);
        float b2 = __uint_as_float(hi ? v0.z : v1.z), b3 = __uint_as_float(hi ? v0.w : v1.w);
        a0 += __shfl_xor_sync(0xffffffffu, b0, 16); a1 += __shfl_xor_sync(0xffffffffu, b1, 16);
        a2 += __shfl_xor_sync(0xffffffffu, b2, 16); a3 += __shfl_xor_sync(0xffffffffu, b3, 16);
        const bool h8 = lane & 8;
        float k0 = h8 ? a2 : a0, k1 = h8 ? a3 : a1, s0 = h8 ? a0 : a2, s1 = h8 ? a1 : a3;
        k0 += __shfl_xor_sync(0xffffffffu, s0, 8); k1 += __shfl_xor_sync(0xffffffffu, s1, 8);
        const bool h4 = lane & 4;
        float z = h4 ? k1 : k0, zs = h4 ? k0 : k1;
        z += __shfl_xor_sync(0xffffffffu, zs, 4);
        z += __shfl_xor_sync(0xffffffffu, z, 2);
        z += __shfl_xor_sync(0xffffffffu, z, 1);
        float zo = __shfl_xor_sync(0xffffffffu, z, 4);
        if ((lane & 7) == 0) {
          uint32_t* d = reinterpret_cast<uint32_t*>(&g_bufC[slot][8 * cta + warp]) + (lane >> 3);
          st_pub32(d, desent(pack2(z, zo)));
          st_pub32(reinterpret_cast<uint32_t*>(&g_bufC[slot2][8 * cta + warp]) + (lane >> 3), SENT);
        }
      }
    }
    if (warp >= 4) attn8<true>(sb, tok, lane, warp - 4, 8 * j + g, g_otok + (size_t)(s * 32 + 8 * j + g) * HD + h * 128);
    TS(11);
  }
}

__device__ void moe_part(int m, const bf16* __restrict__ wg, const bf16* __restrict__ wu, const bf16* __restrict__ wd, uint8_t* smem) {
  const int t = threadIdx.x, warp = t >> 5, lane = t & 31;
  float* xs = reinterpret_cast<float*>(smem);
  float* red = reinterpret_cast<float*>(smem + 8192);
  float* hs = reinterpret_cast<float*>(smem + 65536);
  __shared__ float bv[8];
  __shared__ int bi[8];
  __shared__ int sel[2];
  int first = -1;
  for (int pass = 0; pass < 2; pass++) {
    float best = -INFINITY; int bidx = 0x7fffffff;
    for (int i = t; i < S_LEN; i += 256) {
      float v = g_r[i];
      if (i == first) continue;
      if (v > best || (v == best && i < bidx) || bidx == 0x7fffffff) { best = v; bidx = i; }
    }
#pragma unroll
    for (int o = 16; o > 0; o >>= 1) {
      float ov = __shfl_xor_sync(0xffffffffu, best, o); int oi = __shfl_xor_sync(0xffffffffu, bidx, o);
      if (oi != 0x7fffffff && (bidx == 0x7fffffff || ov > best || (ov == best && oi < bidx))) { best = ov; bidx = oi; }
    }
    if (lane == 0) { bv[warp] = best; bi[warp] = bidx; }
    __syncthreads();
    if (t == 0) {
      float b = bv[0]; int ix = bi[0];
      for (int w = 1; w < 8; w++) if (bv[w] > b || (bv[w] == b && bi[w] < ix)) { b = bv[w]; ix = bi[w]; }
      sel[pass] = ix;
    }
    __syncthreads();
    first = sel[0];
  }
  const int s0 = sel[0], s1 = sel[1];
  for (int i = t; i < 2048; i += 256) xs[i] = __bfloat162float(g_xn[(size_t)(i < 1024 ? s0 : s1) * DM + (i & 1023)]);
  __syncthreads();
  {
    int cg = t % 112, kh = t / 112;
    float a[2][2][8];
#pragma unroll
    for (int i = 0; i < 8; i++) { a[0][0][i] = a[0][1][i] = a[1][0][i] = a[1][1][i] = 0.f; }
    if (kh < 2) {
      const bf16* pg = wg + (size_t)(kh * 512) * FF + 896 * m + cg * 8;
      const bf16* pu = wu + (size_t)(kh * 512) * FF + 896 * m + cg * 8;
#pragma unroll 8
      for (int k = 0; k < 512; k++) {
        uint4 gv = __ldg(reinterpret_cast<const uint4*>(pg + (size_t)k * FF));
        uint4 uv = __ldg(reinterpret_cast<const uint4*>(pu + (size_t)k * FF));
        float x0 = xs[kh * 512 + k], x1 = xs[1024 + kh * 512 + k];
        float gf[8] = {bflo(gv.x), bfhi(gv.x), bflo(gv.y), bfhi(gv.y), bflo(gv.z), bfhi(gv.z), bflo(gv.w), bfhi(gv.w)};
        float uf[8] = {bflo(uv.x), bfhi(uv.x), bflo(uv.y), bfhi(uv.y), bflo(uv.z), bfhi(uv.z), bflo(uv.w), bfhi(uv.w)};
#pragma unroll
        for (int i = 0; i < 8; i++) {
          a[0][0][i] += x0 * gf[i]; a[0][1][i] += x1 * gf[i];
          a[1][0][i] += x0 * uf[i]; a[1][1][i] += x1 * uf[i];
        }
      }
      if (kh == 1) {
#pragma unroll
        for (int i = 0; i < 8; i++) {
          red[(0 * 2 + 0) * 896 + cg * 8 + i] = a[0][0][i]; red[(0 * 2 + 1) * 896 + cg * 8 + i] = a[0][1][i];
          red[(1 * 2 + 0) * 896 + cg * 8 + i] = a[1][0][i]; red[(1 * 2 + 1) * 896 + cg * 8 + i] = a[1][1][i];
        }
      }
    }
    __syncthreads();
    if (kh == 0) {
#pragma unroll
      for (int i = 0; i < 8; i++) {
#pragma unroll
        for (int tk = 0; tk < 2; tk++) {
          float gq = bfr(a[0][tk][i] + red[(0 * 2 + tk) * 896 + cg * 8 + i]);
          float uq = bfr(a[1][tk][i] + red[(1 * 2 + tk) * 896 + cg * 8 + i]);
          float sg = bfr(gq / (1.0f + __expf(-gq)));
          g_h[tk][896 * m + cg * 8 + i] = __float2bfloat16_rn(sg * uq);
        }
      }
    }
    __threadfence();
    __syncthreads();
    if (t == 0) {
      atomicAdd(&g_moe_cnt, 1u);
      int it = 0;
      while (*reinterpret_cast<volatile unsigned*>(&g_moe_cnt) < 4u && ++it < (1 << 24)) {}
      __threadfence();
    }
    __syncthreads();
  }
  for (int i = t; i < 2 * FF; i += 256) {
    const volatile unsigned short* p = reinterpret_cast<const volatile unsigned short*>(&g_h[0][0]);
    hs[i] = __uint_as_float(((uint32_t)p[i]) << 16);
  }
  __syncthreads();
  {
    int cg = t & 31, ksl = t >> 5;
    float a[2][8];
#pragma unroll
    for (int i = 0; i < 8; i++) a[0][i] = a[1][i] = 0.f;
    const bf16* pd = wd + (size_t)(ksl * 448) * DM + 256 * m + cg * 8;
#pragma unroll 8
    for (int k = 0; k < 448; k++) {
      uint4 dv = __ldg(reinterpret_cast<const uint4*>(pd + (size_t)k * DM));
      float x0 = hs[ksl * 448 + k], x1 = hs[FF + ksl * 448 + k];
      float df[8] = {bflo(dv.x), bfhi(dv.x), bflo(dv.y), bfhi(dv.y), bflo(dv.z), bfhi(dv.z), bflo(dv.w), bfhi(dv.w)};
#pragma unroll
      for (int i = 0; i < 8; i++) { a[0][i] += x0 * df[i]; a[1][i] += x1 * df[i]; }
    }
#pragma unroll
    for (int i = 0; i < 8; i++) { red[(ksl * 2 + 0) * 256 + cg * 8 + i] = a[0][i]; red[(ksl * 2 + 1) * 256 + cg * 8 + i] = a[1][i]; }
    __syncthreads();
    for (int i = t; i < 512; i += 256) {
      int tk = i >> 8, col = i & 255;
      float y = 0.f;
#pragma unroll
      for (int q = 0; q < 8; q++) y += red[(q * 2 + tk) * 256 + col];
      float rr = g_r[tk == 0 ? s0 : s1];
      float sg = bfr(1.0f / (1.0f + __expf(-rr)));
      g_upd[tk][256 * m + col] = bfr(bfr(y) * sg);
    }
    if (m == 0 && t == 0) { g_sel[0] = s0; g_sel[1] = s1; }
  }
}

typedef CUresult (*EncodeFn)(CUtensorMap*, CUtensorMapDataType, cuuint32_t, void*, const cuuint64_t*, const cuuint64_t*,
                             const cuuint32_t*, const cuuint32_t*, CUtensorMapInterleave, CUtensorMapSwizzle,
                             CUtensorMapL2promotion, CUtensorMapFloatOOBfill);

static void make_map(EncodeFn enc, CUtensorMap* m, const void* ptr, uint64_t inner, uint64_t outer, uint32_t bi, uint32_t bo) {
  cuuint64_t dims[2] = {inner, outer};
  cuuint64_t strides[1] = {inner * 2};
  cuuint32_t box[2] = {bi, bo};
  cuuint32_t es[2] = {1, 1};
  enc(m, CU_TENSOR_MAP_DATA_TYPE_BFLOAT16, 2, const_cast<void*>(ptr), dims, strides, box, es, CU_TENSOR_MAP_INTERLEAVE_NONE,
      CU_TENSOR_MAP_SWIZZLE_128B, CU_TENSOR_MAP_L2_PROMOTION_L2_256B, CU_TENSOR_MAP_FLOAT_OOB_FILL_NONE);
}

extern "C" void kernel_launch(void* const* d_in, const int* in_sizes, int n_in, void* d_out, int out_size) {
  const bf16* x = (const bf16*)d_in[0];
  const bf16* mem0 = (const bf16*)d_in[1];
  const bf16* Wq = (const bf16*)d_in[2];
  const bf16* Wk = (const bf16*)d_in[3];
  const bf16* Wv = (const bf16*)d_in[4];
  const bf16* Wo = (const bf16*)d_in[5];
  const bf16* w_r = (const bf16*)d_in[8];
  const bf16* wg = (const bf16*)d_in[9];
  const bf16* wu = (const bf16*)d_in[10];
  const bf16* wd = (const bf16*)d_in[11];
  bf16* out = (bf16*)d_out;

  static EncodeFn enc = nullptr;
  static void *p_xn, *p_qkv, *p_otok;
  if (!enc) {
    cudaDriverEntryPointQueryResult qr;
    void* fn = nullptr;
    cudaGetDriverEntryPoint("cuTensorMapEncodeTiled", &fn, cudaEnableDefault, &qr);
    enc = (EncodeFn)fn;
    cudaGetSymbolAddress(&p_xn, g_xn);
    cudaGetSymbolAddress(&p_qkv, g_qkv);
    cudaGetSymbolAddress(&p_otok, g_otok);
    cudaFuncSetAttribute(gemm_kernel<256, 4, 0>, cudaFuncAttributeMaxDynamicSharedMemorySize, GemmSmem<256, 4>::TOTAL);
    cudaFuncSetAttribute(gemm_kernel<128, 6, 1>, cudaFuncAttributeMaxDynamicSharedMemorySize, GemmSmem<128, 6>::TOTAL);
    cudaFuncSetAttribute(chain_kernel, cudaFuncAttributeMaxDynamicSharedMemorySize, CH_SMEM);
  }
  CUtensorMap mA, mQ, mK, mV, mO, mWo;
  make_map(enc, &mA, p_xn, DM, S_LEN, 64, 128);
  make_map(enc, &mQ, Wq, HD, DM, 64, 64);
  make_map(enc, &mK, Wk, HD, DM, 64, 64);
  make_map(enc, &mV, Wv, HD, DM, 64, 64);
  make_map(enc, &mO, p_otok, HD, S_LEN, 64, 128);
  make_map(enc, &mWo, Wo, DM, HD, 64, 64);

  cudaStream_t st = cudaStreamPerThread;
  ln_kernel<<<256, 256, 0, st>>>(x, w_r);
  gemm_kernel<256, 4, 0><<<132, 288, GemmSmem<256, 4>::TOTAL, st>>>(mA, mQ, mK, mV, 16, 16, 16 * 48, nullptr, (bf16*)p_qkv);
  chain_kernel<<<132, 256, CH_SMEM, st>>>(mem0, Wq, Wk, Wv, Wo, wg, wu, wd);
  gemm_kernel<128, 6, 1><<<128, 288, GemmSmem<128, 6>::TOTAL, st>>>(mO, mWo, mWo, mWo, 64, 16, 16 * 8, x, out);
}
```

```cpp
#include <cuda_runtime.h>
#include <cuda_bf16.h>
#include <cuda.h>
#include <stdint.h>

typedef __nv_bfloat16 bf16;

#define S_LEN 2048
#define DM 1024
#define NH 32
#define DH 128
#define NSEG 64
#define SEGL 32
#define HD 4096
#define NQKV 12288
#define FF 3584
#define SENT 0xFFFFFFFFu

__device__ __align__(1024) bf16 g_xn[S_LEN * DM];
__device__ __align__(1024) bf16 g_qkv[(size_t)S_LEN * NQKV];
__device__ __align__(1024) bf16 g_otok[(size_t)S_LEN * HD];
__device__ float g_r[S_LEN];
__device__ __align__(128) uint4 g_bufA[4][128][96];
__device__ __align__(128) uint4 g_bufB[4][128][16][32];
__device__ __align__(128) uint4 g_bufC[4][1024];
__device__ __align__(128) bf16 g_h[2][FF];
__device__ float g_upd[2][DM];
__device__ int g_sel[2];
__device__ unsigned g_moe_cnt;
#define TS(i)

__device__ __forceinline__ float bfr(float x) { return __bfloat162float(__float2bfloat16_rn(x)); }
__device__ __forceinline__ uint32_t pack2(float lo, float hi) {
  __nv_bfloat162 v = __floats2bfloat162_rn(lo, hi);
  return *reinterpret_cast<uint32_t*>(&v);
}
__device__ __forceinline__ float bflo(uint32_t v) { return __uint_as_float(v << 16); }
__device__ __forceinline__ float bfhi(uint32_t v) { return __uint_as_float(v & 0xFFFF0000u); }
__device__ __forceinline__ uint32_t smem_u32(const void* p) { return (uint32_t)__cvta_generic_to_shared(p); }

__device__ __forceinline__ uint4 ld_poll(const uint4* p) {
  uint4 v;
  asm volatile("ld.relaxed.gpu.global.v4.u32 {%0,%1,%2,%3},[%4];" : "=r"(v.x), "=r"(v.y), "=r"(v.z), "=r"(v.w) : "l"(p) : "memory");
  return v;
}
__device__ __forceinline__ void st_pub32(void* p, uint32_t v) {
  asm volatile("st.relaxed.gpu.global.u32 [%0],%1;" ::"l"(p), "r"(v) : "memory");
}
__device__ __forceinline__ void st_pub64(void* p, uint32_t a, uint32_t b) {
  asm volatile("st.relaxed.gpu.global.v2.u32 [%0],{%1,%2};" ::"l"(p), "r"(a), "r"(b) : "memory");
}
__device__ __forceinline__ bool pkt_ok(const uint4& v) { return v.x != SENT && v.y != SENT && v.z != SENT && v.w != SENT; }
__device__ __forceinline__ uint32_t desent(uint32_t v) { return v == SENT ? 0x7FFF7FFFu : v; }

__device__ __forceinline__ void ldsm4(uint32_t& r0, uint32_t& r1, uint32_t& r2, uint32_t& r3, uint32_t addr) {
  asm volatile("ldmatrix.sync.aligned.m8n8.x4.shared.b16 {%0,%1,%2,%3},[%4];" : "=r"(r0), "=r"(r1), "=r"(r2), "=r"(r3) : "r"(addr) : "memory");
}
__device__ __forceinline__ void ldsm4t(uint32_t& r0, uint32_t& r1, uint32_t& r2, uint32_t& r3, uint32_t addr) {
  asm volatile("ldmatrix.sync.aligned.m8n8.x4.trans.shared.b16 {%0,%1,%2,%3},[%4];" : "=r"(r0), "=r"(r1), "=r"(r2), "=r"(r3) : "r"(addr) : "memory");
}
__device__ __forceinline__ void mma16816(float (&d)[4], uint32_t a0, uint32_t a1, uint32_t a2, uint32_t a3, uint32_t b0, uint32_t b1) {
  asm volatile("mma.sync.aligned.m16n8k16.row.col.f32.bf16.bf16.f32 {%0,%1,%2,%3},{%4,%5,%6,%7},{%8,%9},{%0,%1,%2,%3};"
               : "+f"(d[0]), "+f"(d[1]), "+f"(d[2]), "+f"(d[3])
               : "r"(a0), "r"(a1), "r"(a2), "r"(a3), "r"(b0), "r"(b1));
}
__device__ __forceinline__ void cp_async16(uint32_t dst, const void* src) {
  asm volatile("cp.async.cg.shared.global [%0],[%1],16;" ::"r"(dst), "l"(src) : "memory");
}
__device__ __forceinline__ void cp_commit() { asm volatile("cp.async.commit_group;" ::: "memory"); }
template <int N>
__device__ __forceinline__ void cp_wait() { asm volatile("cp.async.wait_group %0;" ::"n"(N) : "memory"); }

__device__ __forceinline__ void mbar_init(uint32_t bar, uint32_t cnt) { asm volatile("mbarrier.init.shared::cta.b64 [%0],%1;" ::"r"(bar), "r"(cnt) : "memory"); }
__device__ __forceinline__ void mbar_expect_tx(uint32_t bar, uint32_t bytes) {
  asm volatile("mbarrier.arrive.expect_tx.shared::cta.b64 _,[%0],%1;" ::"r"(bar), "r"(bytes) : "memory");
}
__device__ __forceinline__ void mbar_arrive(uint32_t bar) { asm volatile("mbarrier.arrive.shared::cta.b64 _,[%0];" ::"r"(bar) : "memory"); }
__device__ __forceinline__ void mbar_wait(uint32_t bar, uint32_t parity) {
  asm volatile(
      "{\n.reg .pred p;\n"
      "WAIT_LOOP:\n"
      "mbarrier.try_wait.parity.shared::cta.b64 p,[%0],%1;\n"
      "@p bra WAIT_DONE;\n"
      "bra WAIT_LOOP;\n"
      "WAIT_DONE:\n}\n" ::"r"(bar), "r"(parity) : "memory");
}
__device__ __forceinline__ void tma_load2d(uint32_t dst, const CUtensorMap* tm, uint32_t bar, int c0, int c1) {
  asm volatile("cp.async.bulk.tensor.2d.shared::cluster.global.mbarrier::complete_tx::bytes [%0],[%1,{%3,%4}],[%2];"
               ::"r"(dst), "l"(tm), "r"(bar), "r"(c0), "r"(c1) : "memory");
}
__device__ __forceinline__ void wg_fence() { asm volatile("wgmma.fence.sync.aligned;" ::: "memory"); }
__device__ __forceinline__ void wg_commit() { asm volatile("wgmma.commit_group.sync.aligned;" ::: "memory"); }
template <int N>
__device__ __forceinline__ void wg_wait() { asm volatile("wgmma.wait_group.sync.aligned %0;" ::"n"(N) : "memory"); }
__device__ __forceinline__ uint64_t make_desc(uint32_t addr, uint32_t lbo, uint32_t sbo) {
  return (uint64_t)((addr & 0x3FFFF) >> 4) | ((uint64_t)(lbo >> 4) << 16) | ((uint64_t)(sbo >> 4) << 32) | (1ull << 62);
}

__device__ __forceinline__ void wgmma_m64n256k16(float (&d)[128], uint64_t da, uint64_t db, int scaleD) {
  asm volatile(
    "{\n.reg .pred p;\nsetp.ne.b32 p, %130, 0;\n"
    "wgmma.mma_async.sync.aligned.m64n256k16.f32.bf16.bf16 "
    "{%0, %1, %2, %3, %4, %5, %6, %7, %8, %9, %10, %11, %12, %13, %14, %15, %16, %17, %18, %19, %20, %21, %22, %23, %24, %25, %26, %27, %28, %29, %30, %31, %32, %33, %34, %35, %36, %37, %38, %39, %40, %41, %42, %43, %44, %45, %46, %47, %48, %49, %50, %51, %52, %53, %54, %55, %56, %57, %58, %59, %60, %61, %62, %63, %64, %65, %66, %67, %68, %69, %70, %71, %72, %73, %74, %75, %76, %77, %78, %79, %80, %81, %82, %83, %84, %85, %86, %87, %88, %89, %90, %91, %92, %93, %94, %95, %96, %97, %98, %99, %100, %101, %102, %103, %104, %105, %106, %107, %108, %109, %110, %111, %112, %113, %114, %115, %116, %117, %118, %119, %120, %121, %122, %123, %124, %125, %126, %127}, %128, %129, p, 1, 1, 0, 1;\n}\n"
    : "+f"(d[0]), "+f"(d[1]), "+f"(d[2]), "+f"(d[3]), "+f"(d[4]), "+f"(d[5]), "+f"(d[6]), "+f"(d[7]), "+f"(d[8]), "+f"(d[9]), "+f"(d[10]), "+f"(d[11]), "+f"(d[12]), "+f"(d[13]), "+f"(d[14]), "+f"(d[15]), "+f"(d[16]), "+f"(d[17]), "+f"(d[18]), "+f"(d[19]), "+f"(d[20]), "+f"(d[21]), "+f"(d[22]), "+f"(d[23]), "+f"(d[24]), "+f"(d[25]), "+f"(d[26]), "+f"(d[27]), "+f"(d[28]), "+f"(d[29]), "+f"(d[30]), "+f"(d[31]), "+f"(d[32]), "+f"(d[33]), "+f"(d[34]), "+f"(d[35]), "+f"(d[36]), "+f"(d[37]), "+f"(d[38]), "+f"(d[39]), "+f"(d[40]), "+f"(d[41]), "+f"(d[42]), "+f"(d[43]), "+f"(d[44]), "+f"(d[45]), "+f"(d[46]), "+f"(d[47]), "+f"(d[48]), "+f"(d[49]), "+f"(d[50]), "+f"(d[51]), "+f"(d[52]), "+f"(d[53]), "+f"(d[54]), "+f"(d[55]), "+f"(d[56]), "+f"(d[57]), "+f"(d[58]), "+f"(d[59]), "+f"(d[60]), "+f"(d[61]), "+f"(d[62]), "+f"(d[63]), "+f"(d[64]), "+f"(d[65]), "+f"(d[66]), "+f"(d[67]), "+f"(d[68]), "+f"(d[69]), "+f"(d[70]), "+f"(d[71]), "+f"(d[72]), "+f"(d[73]), "+f"(d[74]), "+f"(d[75]), "+f"(d[76]), "+f"(d[77]), "+f"(d[78]), "+f"(d[79]), "+f"(d[80]), "+f"(d[81]), "+f"(d[82]), "+f"(d[83]), "+f"(d[84]), "+f"(d[85]), "+f"(d[86]), "+f"(d[87]), "+f"(d[88]), "+f"(d[89]), "+f"(d[90]), "+f"(d[91]), "+f"(d[92]), "+f"(d[93]), "+f"(d[94]), "+f"(d[95]), "+f"(d[96]), "+f"(d[97]), "+f"(d[98]), "+f"(d[99]), "+f"(d[100]), "+f"(d[101]), "+f"(d[102]), "+f"(d[103]), "+f"(d[104]), "+f"(d[105]), "+f"(d[106]), "+f"(d[107]), "+f"(d[108]), "+f"(d[109]), "+f"(d[110]), "+f"(d[111]), "+f"(d[112]), "+f"(d[113]), "+f"(d[114]), "+f"(d[115]), "+f"(d[116]), "+f"(d[117]), "+f"(d[118]), "+f"(d[119]), "+f"(d[120]), "+f"(d[121]), "+f"(d[122]), "+f"(d[123]), "+f"(d[124]), "+f"(d[125]), "+f"(d[126]), "+f"(d[127])
    : "l"(da), "l"(db), "r"(scaleD));
}

__device__ __forceinline__ void wgmma_m64n128k16(float (&d)[64], uint64_t da, uint64_t db, int scaleD) {
  asm volatile(
    "{\n.reg .pred p;\nsetp.ne.b32 p, %66, 0;\n"
    "wgmma.mma_async.sync.aligned.m64n128k16.f32.bf16.bf16 "
    "{%0, %1, %2, %3, %4, %5, %6, %7, %8, %9, %10, %11, %12, %13, %14, %15, %16, %17, %18, %19, %20, %21, %22, %23, %24, %25, %26, %27, %28, %29, %30, %31, %32, %33, %34, %35, %36, %37, %38, %39, %40, %41, %42, %43, %44, %45, %46, %47, %48, %49, %50, %51, %52, %53, %54, %55, %56, %57, %58, %59, %60, %61, %62, %63}, %64, %65, p, 1, 1, 0, 1;\n}\n"
    : "+f"(d[0]), "+f"(d[1]), "+f"(d[2]), "+f"(d[3]), "+f"(d[4]), "+f"(d[5]), "+f"(d[6]), "+f"(d[7]), "+f"(d[8]), "+f"(d[9]), "+f"(d[10]), "+f"(d[11]), "+f"(d[12]), "+f"(d[13]), "+f"(d[14]), "+f"(d[15]), "+f"(d[16]), "+f"(d[17]), "+f"(d[18]), "+f"(d[19]), "+f"(d[20]), "+f"(d[21]), "+f"(d[22]), "+f"(d[23]), "+f"(d[24]), "+f"(d[25]), "+f"(d[26]), "+f"(d[27]), "+f"(d[28]), "+f"(d[29]), "+f"(d[30]), "+f"(d[31]), "+f"(d[32]), "+f"(d[33]), "+f"(d[34]), "+f"(d[35]), "+f"(d[36]), "+f"(d[37]), "+f"(d[38]), "+f"(d[39]), "+f"(d[40]), "+f"(d[41]), "+f"(d[42]), "+f"(d[43]), "+f"(d[44]), "+f"(d[45]), "+f"(d[46]), "+f"(d[47]), "+f"(d[48]), "+f"(d[49]), "+f"(d[50]), "+f"(d[51]), "+f"(d[52]), "+f"(d[53]), "+f"(d[54]), "+f"(d[55]), "+f"(d[56]), "+f"(d[57]), "+f"(d[58]), "+f"(d[59]), "+f"(d[60]), "+f"(d[61]), "+f"(d[62]), "+f"(d[63])
    : "l"(da), "l"(db), "r"(scaleD));
}

template <int BN> struct WG;
template <> struct WG<256> { static __device__ __forceinline__ void mma(float (&d)[128], uint64_t a, uint64_t b, int s) { wgmma_m64n256k16(d, a, b, s); } };
template <> struct WG<128> { static __device__ __forceinline__ void mma(float (&d)[64], uint64_t a, uint64_t b, int s) { wgmma_m64n128k16(d, a, b, s); } };

__global__ void __launch_bounds__(256) ln_kernel(const bf16* __restrict__ x, const bf16* __restrict__ w_r) {
  int warp = threadIdx.x >> 5, lane = threadIdx.x & 31;
  int row = blockIdx.x * 8 + warp;
  const uint4* xp = reinterpret_cast<const uint4*>(x + (size_t)row * DM);
  uint4 v[4];
#pragma unroll
  for (int i = 0; i < 4; i++) v[i] = xp[lane + 32 * i];
  float f[32];
#pragma unroll
  for (int i = 0; i < 4; i++) {
    f[8 * i + 0] = bflo(v[i].x); f[8 * i + 1] = bfhi(v[i].x);
    f[8 * i + 2] = bflo(v[i].y); f[8 * i + 3] = bfhi(v[i].y);
    f[8 * i + 4] = bflo(v[i].z); f[8 * i + 5] = bfhi(v[i].z);
    f[8 * i + 6] = bflo(v[i].w); f[8 * i + 7] = bfhi(v[i].w);
  }
  float s = 0.f;
#pragma unroll
  for (int i = 0; i < 32; i++) s += f[i];
#pragma unroll
  for (int o = 16; o > 0; o >>= 1) s += __shfl_xor_sync(0xffffffffu, s, o);
  float mean = s * (1.0f / DM);
  float q = 0.f;
#pragma unroll
  for (int i = 0; i < 32; i++) { float d = f[i] - mean; q += d * d; }
#pragma unroll
  for (int o = 16; o > 0; o >>= 1) q += __shfl_xor_sync(0xffffffffu, q, o);
  float var = bfr(q * (1.0f / DM));
  float mb = bfr(mean);
  float den = bfr(sqrtf(bfr(var + 1e-5f)));
  const uint4* wp = reinterpret_cast<const uint4*>(w_r);
  uint4* op = reinterpret_cast<uint4*>(g_xn + (size_t)row * DM);
  float r = 0.f;
#pragma unroll
  for (int i = 0; i < 4; i++) {
    uint4 w = wp[lane + 32 * i];
    float y[8];
#pragma unroll
    for (int k = 0; k < 8; k++) y[k] = bfr(bfr(f[8 * i + k] - mb) / den);
    r += y[0] * bflo(w.x) + y[1] * bfhi(w.x) + y[2] * bflo(w.y) + y[3] * bfhi(w.y) + y[4] * bflo(w.z) + y[5] * bfhi(w.z) +
         y[6] * bflo(w.w) + y[7] * bfhi(w.w);
    op[lane + 32 * i] = make_uint4(pack2(y[0], y[1]), pack2(y[2], y[3]), pack2(y[4], y[5]), pack2(y[6], y[7]));
  }
#pragma unroll
  for (int o = 16; o > 0; o >>= 1) r += __shfl_xor_sync(0xffffffffu, r, o);
  if (lane == 0) g_r[row] = bfr(r);
  int gt = blockIdx.x * 256 + threadIdx.x;
  const uint4 sv = make_uint4(SENT, SENT, SENT, SENT);
  uint4* a = &g_bufA[0][0][0];
  for (int i = gt; i < 2 * 128 * 96; i += 65536) a[i] = sv;
  uint4* b = &g_bufB[0][0][0][0];
  for (int i = gt; i < 2 * 128 * 32 * 16; i += 65536) b[i] = sv;
  uint4* c = &g_bufC[0][0];
  for (int i = gt; i < 2 * 1024; i += 65536) c[i] = sv;
  if (gt == 0) g_moe_cnt = 0;
}

template <int BN, int STAGES>
struct GemmSmem {
  static constexpr int A_BYTES = 128 * 64 * 2;
  static constexpr int B_BYTES = 64 * BN * 2;
  static constexpr int STAGE_BYTES = A_BYTES + B_BYTES;
  static constexpr int TOTAL = STAGES * STAGE_BYTES + 1024 + 256;
};

__device__ __forceinline__ void quad_transpose(uint32_t (&v)[4], int c) {
  {
    uint32_t s0 = (c & 1) ? v[0] : v[1];
    uint32_t s1 = (c & 1) ? v[2] : v[3];
    uint32_t r0 = __shfl_xor_sync(0xffffffffu, s0, 1);
    uint32_t r1 = __shfl_xor_sync(0xffffffffu, s1, 1);
    if (c & 1) { v[0] = r0; v[2] = r1; } else { v[1] = r0; v[3] = r1; }
  }
  {
    uint32_t s0 = (c & 2) ? v[0] : v[2];
    uint32_t s1 = (c & 2) ? v[1] : v[3];
    uint32_t r0 = __shfl_xor_sync(0xffffffffu, s0, 2);
    uint32_t r1 = __shfl_xor_sync(0xffffffffu, s1, 2);
    if (c & 2) { v[0] = r0; v[1] = r1; } else { v[2] = r0; v[3] = r1; }
  }
}

__device__ __forceinline__ uint32_t add3(uint32_t a, uint32_t x, uint32_t b) {
  float lo = bfr(bflo(x) + bflo(a)) + bflo(b);
  float hi = bfr(bfhi(x) + bfhi(a)) + bfhi(b);
  return pack2(lo, hi);
}

template <int BN, int STAGES, int EPI>
__global__ void __launch_bounds__(288, 1)
gemm_kernel(const __grid_constant__ CUtensorMap tmA, const __grid_constant__ CUtensorMap tmB0,
            const __grid_constant__ CUtensorMap tmB1, const __grid_constant__ CUtensorMap tmB2,
            int kblocks, int tiles_m, int tiles_total, const bf16* __restrict__ xin, bf16* __restrict__ outp) {
  using SM = GemmSmem<BN, STAGES>;
  extern __shared__ uint8_t smem_raw[];
  uint32_t base = (smem_u32(smem_raw) + 1023) & ~1023u;
  uint32_t bars = base + STAGES * SM::STAGE_BYTES;
  int warp = threadIdx.x >> 5, lane = threadIdx.x & 31;
  if (threadIdx.x == 0) {
    for (int i = 0; i < STAGES; i++) { mbar_init(bars + 8 * i, 1); mbar_init(bars + 8 * (STAGES + i), 8); }
    asm volatile("fence.mbarrier_init.release.cluster;" ::: "memory");
  }
  __syncthreads();
  if (warp == 8) {
    if (lane == 0) {
      int it = 0;
      for (int t = blockIdx.x; t < tiles_total; t += gridDim.x) {
        int tm = t % tiles_m, tn = t / tiles_m;
        int n0 = tn * BN;
        const CUtensorMap* tb = &tmB0;
        if (EPI == 0) { int wsel = n0 >> 12; tb = wsel == 0 ? &tmB0 : (wsel == 1 ? &tmB1 : &tmB2); n0 &= 4095; }
        for (int kb = 0; kb < kblocks; kb++, it++) {
          int st = it % STAGES; uint32_t ph = (it / STAGES) & 1;
          mbar_wait(bars + 8 * (STAGES + st), ph ^ 1);
          uint32_t sa = base + st * SM::STAGE_BYTES, sb = sa + SM::A_BYTES;
          mbar_expect_tx(bars + 8 * st, SM::STAGE_BYTES);
          tma_load2d(sa, &tmA, bars + 8 * st, kb * 64, tm * 128);
#pragma unroll
          for (int i = 0; i < BN / 64; i++) tma_load2d(sb + i * 8192, tb, bars + 8 * st, n0 + i * 64, kb * 64);
        }
      }
    }
  } else {
    int wg = warp >> 2;
    int g = lane >> 2, c = lane & 3;
    int it = 0;
    float acc[BN / 2];
    for (int t = blockIdx.x; t < tiles_total; t += gridDim.x) {
      int tm = t % tiles_m, tn = t / tiles_m;
      for (int kb = 0; kb < kblocks; kb++, it++) {
        int st = it % STAGES; uint32_t ph = (it / STAGES) & 1;
        mbar_wait(bars + 8 * st, ph);
        uint32_t sa = base + st * SM::STAGE_BYTES + wg * 8192, sb = base + st * SM::STAGE_BYTES + SM::A_BYTES;
        wg_fence();
#pragma unroll
        for (int kk = 0; kk < 4; kk++) {
          uint64_t da = make_desc(sa + kk * 32, 16, 1024);
          uint64_t db = make_desc(sb + kk * 2048, 8192, 1024);
          WG<BN>::mma(acc, da, db, (kb | kk) != 0);
        }
        wg_commit();
        if (kb > 0) {
          wg_wait<1>();
          int pst = (it - 1) % STAGES;
          if (lane == 0) mbar_arrive(bars + 8 * (STAGES + pst));
        }
      }
      wg_wait<0>();
      { int pst = (it - 1) % STAGES; if (lane == 0) mbar_arrive(bars + 8 * (STAGES + pst)); }
      int row0 = tm * 128 + wg * 64 + (warp & 3) * 16 + g;
      int sel0 = -1, sel1 = -1;
      if (EPI == 1) { sel0 = g_sel[0]; sel1 = g_sel[1]; }
#pragma unroll
      for (int half = 0; half < 2; half++) {
        int row = row0 + half * 8;
#pragma unroll
        for (int q = 0; q < BN / 32; q++) {
          uint32_t v[4];
#pragma unroll
          for (int tt = 0; tt < 4; tt++) v[tt] = pack2(acc[(q * 4 + tt) * 4 + half * 2], acc[(q * 4 + tt) * 4 + half * 2 + 1]);
          quad_transpose(v, c);
          int col = tn * BN + q * 32 + c * 8;
          if (EPI == 0) {
            *reinterpret_cast<uint4*>(outp + (size_t)row * NQKV + col) = make_uint4(v[0], v[1], v[2], v[3]);
          } else {
            uint4 xv = *reinterpret_cast<const uint4*>(xin + (size_t)row * DM + col);
            uint4 bv = *reinterpret_cast<const uint4*>(g_xn + (size_t)row * DM + col);
            if (row == sel0 || row == sel1) {
              const float* u = &g_upd[row == sel0 ? 0 : 1][col];
              bv.x = pack2(bflo(bv.x) + u[0], bfhi(bv.x) + u[1]);
              bv.y = pack2(bflo(bv.y) + u[2], bfhi(bv.y) + u[3]);
              bv.z = pack2(bflo(bv.z) + u[4], bfhi(bv.z) + u[5]);
              bv.w = pack2(bflo(bv.w) + u[6], bfhi(bv.w) + u[7]);
            }
            uint4 o = make_uint4(add3(v[0], xv.x, bv.x), add3(v[1], xv.y, bv.y), add3(v[2], xv.z, bv.z), add3(v[3], xv.w, bv.w));
            *reinterpret_cast<uint4*>(outp + (size_t)row * DM + col) = o;
          }
        }
      }
    }
  }
}

#define RK 10
#define SK (16 - RK)
#define TP 272
#define OFF_WQS 0
#define OFF_MEMT (OFF_WQS + 8 * SK * 3 * 512)
#define OFF_RED (OFF_MEMT + 16384)
#define OFF_QKVM (OFF_RED + 12288)
#define OFF_TOK (OFF_QKVM + 6144)
#define TOK_BYTES (72 * TP)
#define OFF_SA (OFF_TOK + 2 * TOK_BYTES)
#define OFF_BAR (OFF_SA + 8 * TP)
#define CH_END (OFF_BAR + 64)
#define CH_STG2 (131072)
#define CH_SMEM (196608 + 1024)
static_assert(CH_END <= CH_SMEM, "smem");

__device__ void moe_part(int m, const bf16* __restrict__ wg, const bf16* __restrict__ wu, const bf16* __restrict__ wd, uint8_t* smem);

__device__ __forceinline__ void bulk_copy(uint32_t dst, const void* src, uint32_t bytes, uint32_t bar) {
  asm volatile("cp.async.bulk.shared::cluster.global.mbarrier::complete_tx::bytes [%0],[%1],%2,[%3];"
               ::"r"(dst), "l"(src), "r"(bytes), "r"(bar) : "memory");
}
__device__ __forceinline__ void st_pub128(void* p, uint32_t v) {
  asm volatile("st.relaxed.gpu.global.v4.u32 [%0],{%1,%1,%1,%1};" ::"l"(p), "r"(v) : "memory");
}
__device__ __forceinline__ void sts128(uint32_t addr, const uint4& v) {
  asm volatile("st.shared.v4.u32 [%0],{%1,%2,%3,%4};" ::"r"(addr), "r"(v.x), "r"(v.y), "r"(v.z), "r"(v.w) : "memory");
}

#define POLL_MAX (1 << 22)
__device__ __forceinline__ uint32_t clk32() { uint32_t c; asm volatile("mov.u32 %0,%%clock;" : "=r"(c)); return c; }
__device__ __forceinline__ void wait_until(uint32_t t0, uint32_t d) { while (clk32() - t0 < d) {} }
#define DLY_DEC 48u

__device__ __forceinline__ float ex2f(float x) { float y; asm("ex2.approx.ftz.f32 %0,%1;" : "=f"(y) : "f"(x)); return y; }
__device__ __forceinline__ float rcpf(float x) { float y; asm("rcp.approx.ftz.f32 %0,%1;" : "=f"(y) : "f"(x)); return y; }
template <bool TOK>
__device__ __forceinline__ void attn8(uint32_t sb, uint32_t tok, int lane, int wq4, int tr, bf16* otok_row) {
  const int g = lane >> 2, c = lane & 3;
  float sc[5][4];
#pragma unroll
  for (int n = 0; n < 5; n++)
#pragma unroll
    for (int i = 0; i < 4; i++) sc[n][i] = 0.f;
  const uint32_t tokrow = tok + (lane & 7) * TP + (lane >> 3) * 16;
  const uint32_t qaddr = TOK ? (tok + (64 + (lane & 7)) * TP + (lane >> 4) * 16) : (sb + OFF_QKVM + ((lane & 7) + 8 * (lane >> 4)) * 16);
#pragma unroll
  for (int kp = 0; kp < 4; kp++) {
    uint32_t q0[4], q1[4], km[4], kt[4][4];
    if (TOK) {
      ldsm4(q0[0], q0[1], q0[2], q0[3], qaddr + 64 * kp);
      ldsm4(q1[0], q1[1], q1[2], q1[3], qaddr + 64 * kp + 32);
    } else {
      ldsm4t(q0[0], q0[1], q0[2], q0[3], qaddr + 512 * kp);
      ldsm4t(q1[0], q1[1], q1[2], q1[3], qaddr + 512 * kp + 256);
    }
    ldsm4t(km[0], km[1], km[2], km[3], sb + OFF_QKVM + (128 + 32 * kp + lane) * 16);
#pragma unroll
    for (int n = 0; n < 4; n++) ldsm4(kt[n][0], kt[n][1], kt[n][2], kt[n][3], tokrow + 8 * n * TP + 64 * kp);
    mma16816(sc[0], q0[0], q0[1], q0[2], q0[3], km[0], km[1]);
#pragma unroll
    for (int n = 0; n < 4; n++) mma16816(sc[n + 1], q0[0], q0[1], q0[2], q0[3], kt[n][0], kt[n][1]);
    mma16816(sc[0], q1[0], q1[1], q1[2], q1[3], km[2], km[3]);
#pragma unroll
    for (int n = 0; n < 4; n++) mma16816(sc[n + 1], q1[0], q1[1], q1[2], q1[3], kt[n][2], kt[n][3]);
  }
  uint32_t vma[4], vmb[4], vt[4][4];
  ldsm4(vma[0], vma[1], vma[2], vma[3], sb + OFF_QKVM + (256 + 32 * wq4 + lane) * 16);
  ldsm4(vmb[0], vmb[1], vmb[2], vmb[3], sb + OFF_QKVM + (256 + 32 * wq4 + (lane ^ 8)) * 16);
#pragma unroll
  for (int n = 0; n < 4; n++) ldsm4t(vt[n][0], vt[n][1], vt[n][2], vt[n][3], tok + (32 + lane) * TP + (32 * wq4 + 8 * n) * 2);
  const float scale = 0.08838834764831845f;
  float m0 = -3.0e38f;
#pragma unroll
  for (int n = 0; n < 5; n++) {
    uint32_t p1 = pack2(sc[n][0], sc[n][1]);
    uint32_t p2 = pack2(bflo(p1) * scale, bfhi(p1) * scale);
    sc[n][0] = bflo(p2);
    sc[n][1] = bfhi(p2);
    if (TOK && n > 0) {
      int kt = 8 * (n - 1) + 2 * c;
      if (kt > tr) sc[n][0] = -1.0e9f;
      if (kt + 1 > tr) sc[n][1] = -1.0e9f;
    }
    m0 = fmaxf(m0, fmaxf(sc[n][0], sc[n][1]));
  }
  m0 = fmaxf(m0, __shfl_xor_sync(0xffffffffu, m0, 1));
  m0 = fmaxf(m0, __shfl_xor_sync(0xffffffffu, m0, 2));
  const float l2e = 1.4426950408889634f;
  float s0 = 0.f;
#pragma unroll
  for (int n = 0; n < 5; n++) {
    sc[n][0] = ex2f((sc[n][0] - m0) * l2e);
    sc[n][1] = ex2f((sc[n][1] - m0) * l2e);
    s0 += sc[n][0] + sc[n][1];
  }
  s0 += __shfl_xor_sync(0xffffffffu, s0, 1);
  s0 += __shfl_xor_sync(0xffffffffu, s0, 2);
  const float i0 = rcpf(s0);
  uint32_t pp[5];
#pragma unroll
  for (int n = 0; n < 5; n++) pp[n] = pack2(sc[n][0] * i0, sc[n][1] * i0);
  float o[4][4];
#pragma unroll
  for (int n = 0; n < 4; n++) {
#pragma unroll
    for (int i = 0; i < 4; i++) o[n][i] = 0.f;
    mma16816(o[n], pp[1], pp[1], pp[2], pp[2], vt[n][0], vt[n][1]);
  }
#pragma unroll
  for (int n = 0; n < 4; n++) mma16816(o[n], pp[3], pp[3], pp[4], pp[4], vt[n][2], vt[n][3]);
  mma16816(o[0], pp[0], 0u, 0u, 0u, vma[0], vma[1]);
  mma16816(o[1], pp[0], 0u, 0u, 0u, vmb[0], vmb[1]);
  mma16816(o[2], pp[0], 0u, 0u, 0u, vma[2], vma[3]);
  mma16816(o[3], pp[0], 0u, 0u, 0u, vmb[2], vmb[3]);
#pragma unroll
  for (int n = 0; n < 4; n++) {
    const int e = 32 * wq4 + 8 * n + 2 * c;
    if (TOK) *reinterpret_cast<uint32_t*>(otok_row + e) = pack2(o[n][0], o[n][1]);
    else asm volatile("st.shared.u32 [%0],%1;" ::"r"(sb + OFF_SA + g * TP + e * 2), "r"(pack2(o[n][0], o[n][1])) : "memory");
  }
}

__global__ void __launch_bounds__(256, 1)
chain_kernel(const bf16* __restrict__ mem0, const bf16* __restrict__ Wq, const bf16* __restrict__ Wk, const bf16* __restrict__ Wv,
             const bf16* __restrict__ Wo, const bf16* __restrict__ wgate, const bf16* __restrict__ wup, const bf16* __restrict__ wdown) {
  extern __shared__ __align__(1024) uint8_t smem[];
  const int cta = blockIdx.x, t = threadIdx.x, warp = t >> 5, lane = t & 31;
  if (cta >= 128) {
    moe_part(cta - 128, wgate, wup, wdown, smem);
    return;
  }
  const int h = cta >> 2, j = cta & 3;
  const int g = lane >> 2, c = lane & 3;
  const uint32_t sb = smem_u32(smem);
  const int mg = warp & 1, kq = warp >> 1;

  uint32_t wq[RK][3][4];
  uint32_t wo[2][8][4];
  {
    for (int i = t; i < 3 * 1024 * 4; i += 256) {
      int which = i >> 12, k = (i >> 2) & 1023, ch = i & 3;
      const bf16* W = which == 0 ? Wq : (which == 1 ? Wk : Wv);
      cp_async16(sb + (which * 1024 + k) * 64 + ch * 16, W + (size_t)k * HD + h * 128 + 32 * j + ch * 8);
    }
    cp_commit(); cp_wait<0>();
    __syncthreads();
    uint32_t tmp[SK][3][4];
#pragma unroll
    for (int ks = 0; ks < 16; ks++) {
#pragma unroll
      for (int tt = 0; tt < 3; tt++) {
        int tile = 3 * mg + tt;
        int which = tile >> 1, ch = tile & 1;
        int k = (16 * kq + ks) * 16 + (lane & 7) + 8 * (lane >> 4);
        uint32_t addr = sb + (which * 1024 + k) * 64 + ch * 32 + 16 * ((lane >> 3) & 1);
        if (ks < RK) ldsm4t(wq[ks][tt][0], wq[ks][tt][1], wq[ks][tt][2], wq[ks][tt][3], addr);
        else ldsm4t(tmp[ks - RK][tt][0], tmp[ks - RK][tt][1], tmp[ks - RK][tt][2], tmp[ks - RK][tt][3], addr);
      }
    }
    __syncthreads();
#pragma unroll
    for (int ks = 0; ks < SK; ks++)
#pragma unroll
      for (int tt = 0; tt < 3; tt++)
        *reinterpret_cast<uint4*>(smem + OFF_WQS + (((warp * SK + ks) * 3 + tt) * 32 + lane) * 16) =
            make_uint4(tmp[ks][tt][0], tmp[ks][tt][1], tmp[ks][tt][2], tmp[ks][tt][3]);
    for (int i = t; i < 128 * 32; i += 256) {
      int e = i >> 5, ch = i & 31;
      cp_async16(sb + CH_STG2 + e * 512 + ch * 16, Wo + (size_t)(h * 128 + e) * DM + 256 * j + ch * 8);
    }
    cp_commit(); cp_wait<0>();
    __syncthreads();
#pragma unroll
    for (int tt = 0; tt < 2; tt++)
#pragma unroll
      for (int ks = 0; ks < 8; ks++) {
        int e = 16 * ks + (lane & 7) + 8 * (lane >> 4);
        uint32_t addr = sb + CH_STG2 + e * 512 + (32 * warp + 16 * tt + 8 * ((lane >> 3) & 1)) * 2;
        ldsm4t(wo[tt][ks][0], wo[tt][ks][1], wo[tt][ks][2], wo[tt][ks][3], addr);
      }
    if (t == 0) {
      mbar_init(sb + OFF_BAR, 1); mbar_init(sb + OFF_BAR + 8, 1);
      asm volatile("fence.mbarrier_init.release.cluster;" ::: "memory");
    }
    __syncthreads();
    asm volatile("fence.proxy.async.shared::cta;" ::: "memory");
  }
  auto prefetch_tok = [&](int s) {
    const int i = t - 192;
    const uint32_t dst = sb + OFF_TOK + (s & 1) * TOK_BYTES + (i >> 4) * TP + (i & 15) * 16;
    const bf16* src = g_qkv + (size_t)(s * 32 + (i >> 4)) * NQKV + HD + h * 128 + (i & 15) * 8;
#pragma unroll
    for (int r = 0; r < 8; r++) {
      cp_async16(dst + 4 * r * TP, src + (size_t)4 * r * NQKV);
      cp_async16(dst + (32 + 4 * r) * TP, src + (size_t)4 * r * NQKV + HD);
    }
    cp_async16(dst + 64 * TP, src + (size_t)(8 * j) * NQKV - HD);
    cp_async16(dst + 68 * TP, src + (size_t)(8 * j + 4) * NQKV - HD);
    cp_commit();
  };
  if (warp >= 6) prefetch_tok(0);
  for (int i = t; i < 8 * 1024; i += 256) {
    int r = i >> 10, k = i & 1023;
    reinterpret_cast<bf16*>(smem + OFF_MEMT)[k * 8 + r] = mem0[i];
  }
  __syncthreads();
  uint32_t p2dst0, p2dst1;
  {
    int p = t, jj = p / 96, f = p % 96;
    p2dst0 = sb + OFF_QKVM + ((f >> 5) * 128 + 32 * jj + (f & 31)) * 16;
    p = 256 + (t & 127); jj = p / 96; f = p % 96;
    p2dst1 = sb + OFF_QKVM + ((f >> 5) * 128 + 32 * jj + (f & 31)) * 16;
  }
  const int p0idx = 256 * kq + 128 * mg + lane;
  uint32_t tpub = 0, dA = 0, dB = 0, dC = 0;
  TS(0);
  for (int s = 0; s < NSEG; s++) {
    const int slot = s & 3, slot2 = (s + 2) & 3;
    if (s > 0) {
      const uint4* src = &g_bufC[(s - 1) & 3][p0idx];
      uint4 v[4];
      wait_until(tpub, dC);
#pragma unroll
      for (int i = 0; i < 4; i++) v[i] = ld_poll(src + 32 * i);
      int it = 0;
      uint32_t tiss = 0;
      while (!__all_sync(0xffffffffu, pkt_ok(v[0]) && pkt_ok(v[1]) && pkt_ok(v[2]) && pkt_ok(v[3])) && ++it < POLL_MAX) {
        tiss = clk32();
#pragma unroll
        for (int i = 0; i < 4; i++)
          if (!pkt_ok(v[i])) v[i] = ld_poll(src + 32 * i);
      }
      dC = it ? (tiss - tpub) : (dC > DLY_DEC ? dC - DLY_DEC : 0u);
#pragma unroll
      for (int i = 0; i < 4; i++) sts128(sb + OFF_MEMT + (p0idx + 32 * i) * 16, v[i]);
      TS(1);
      asm volatile("bar.sync %0, 64;" ::"r"(1 + kq) : "memory");
      TS(2);
    }
    {
      float acc[2][3][4];
#pragma unroll
      for (int a = 0; a < 2; a++)
#pragma unroll
        for (int tt = 0; tt < 3; tt++)
#pragma unroll
          for (int i = 0; i < 4; i++) acc[a][tt][i] = 0.f;
      uint4 sa[SK][3];
#pragma unroll
      for (int kp = 0; kp < 8; kp++) {
        uint32_t b0, b1, b2, b3;
        ldsm4t(b0, b1, b2, b3, sb + OFF_MEMT + ((16 * kq + 2 * kp) * 16 + lane) * 16);
#pragma unroll
        for (int u = 0; u < 2; u++) {
          int ks = 2 * (kp + 1) + u;
          if (ks >= RK && ks < 16) {
#pragma unroll
            for (int tt = 0; tt < 3; tt++)
              sa[ks - RK][tt] = *reinterpret_cast<const uint4*>(smem + OFF_WQS + (((warp * SK + (ks - RK)) * 3 + tt) * 32 + lane) * 16);
          }
        }
#pragma unroll
        for (int u = 0; u < 2; u++) {
          int ks = 2 * kp + u;
#pragma unroll
          for (int tt = 0; tt < 3; tt++) {
            if (ks < RK) mma16816(acc[u][tt], wq[ks][tt][0], wq[ks][tt][1], wq[ks][tt][2], wq[ks][tt][3], u ? b2 : b0, u ? b3 : b1);
            else mma16816(acc[u][tt], sa[ks - RK][tt].x, sa[ks - RK][tt].y, sa[ks - RK][tt].z, sa[ks - RK][tt].w, u ? b2 : b0, u ? b3 : b1);
          }
        }
      }
#pragma unroll
      for (int tt = 0; tt < 3; tt++)
        *reinterpret_cast<float4*>(smem + OFF_RED + ((kq * 6 + 3 * mg + tt) * 32 + lane) * 16) =
            make_float4(acc[0][tt][0] + acc[1][tt][0], acc[0][tt][1] + acc[1][tt][1], acc[0][tt][2] + acc[1][tt][2], acc[0][tt][3] + acc[1][tt][3]);
    }
    TS(3);
    __syncthreads();
    TS(4);
    if (warp < 6) {
      float4 r = *reinterpret_cast<const float4*>(smem + OFF_RED + ((0 * 6 + warp) * 32 + lane) * 16);
#pragma unroll
      for (int q = 1; q < 4; q++) {
        float4 x = *reinterpret_cast<const float4*>(smem + OFF_RED + ((q * 6 + warp) * 32 + lane) * 16);
        r.x += x.x; r.y += x.y; r.z += x.z; r.w += x.w;
      }
      uint32_t* dst = reinterpret_cast<uint32_t*>(&g_bufA[slot][cta][16 * warp + g]) + c;
      st_pub32(dst, desent(pack2(r.x, r.y)));
      st_pub32(dst + 32, desent(pack2(r.z, r.w)));
    }
    tpub = clk32();
    {
      const uint4* src = &g_bufA[slot][4 * h][t];
      wait_until(tpub, dA);
      uint4 v0 = ld_poll(src);
      uint4 v1 = make_uint4(0, 0, 0, 0);
      if (t < 128) v1 = ld_poll(src + 256);
      int it = 0;
      uint32_t tiss = 0;
      while (!__all_sync(0xffffffffu, pkt_ok(v0) && pkt_ok(v1)) && ++it < POLL_MAX) {
        tiss = clk32();
        if (!pkt_ok(v0)) v0 = ld_poll(src);
        if (!pkt_ok(v1)) v1 = ld_poll(src + 256);
      }
      dA = it ? (tiss - tpub) : (dA > DLY_DEC ? dA - DLY_DEC : 0u);
      sts128(p2dst0, v0);
      if (t < 128) sts128(p2dst1, v1);
    }
    TS(5);
    if (warp >= 6) cp_wait<0>();
    __syncthreads();
    TS(6);
    const uint32_t tok = sb + OFF_TOK + (s & 1) * TOK_BYTES;
    if (s < NSEG - 1) {
      if (warp < 4) attn8<false>(sb, tok, lane, warp, 0, nullptr);
      else if (warp >= 6) prefetch_tok(s + 1);
      else {
        const int i = t - 128;
        st_pub128(&g_bufA[slot2][cta][i], SENT);
        if (i < 32) st_pub128(&g_bufA[slot2][cta][64 + i], SENT);
        if (i < 8) st_pub128(&g_bufC[slot2][8 * cta + i], SENT);
        uint4* bb = &g_bufB[slot2][32 * j + (i >> 1)][0][0] + 2 * h + (i & 1);
#pragma unroll
        for (int col = 0; col < 8; col++) st_pub128(bb + 64 * col, SENT);
      }
      TS(7);
      __syncthreads();
      TS(8);
      {
        float acc[2][2][4];
#pragma unroll
        for (int a = 0; a < 2; a++)
#pragma unroll
          for (int tt = 0; tt < 2; tt++)
#pragma unroll
            for (int i = 0; i < 4; i++) acc[a][tt][i] = 0.f;
        uint32_t b[4][4];
#pragma unroll
        for (int kp = 0; kp < 4; kp++) ldsm4(b[kp][0], b[kp][1], b[kp][2], b[kp][3], sb + OFF_SA + (lane & 7) * TP + (32 * kp + 8 * (lane >> 3)) * 2);
#pragma unroll
        for (int kp = 0; kp < 4; kp++) {
#pragma unroll
          for (int tt = 0; tt < 2; tt++) {
            mma16816(acc[0][tt], wo[tt][2 * kp][0], wo[tt][2 * kp][1], wo[tt][2 * kp][2], wo[tt][2 * kp][3], b[kp][0], b[kp][1]);
            mma16816(acc[1][tt], wo[tt][2 * kp + 1][0], wo[tt][2 * kp + 1][1], wo[tt][2 * kp + 1][2], wo[tt][2 * kp + 1][3], b[kp][2], b[kp][3]);
          }
        }
        const int off = (g * 32 + h) * 4 + c;
#pragma unroll
        for (int tt = 0; tt < 2; tt++) {
          int r0 = 32 * j + 4 * warp + 2 * tt;
          uint32_t x0 = __float_as_uint(acc[0][tt][0] + acc[1][tt][0]), x1 = __float_as_uint(acc[0][tt][1] + acc[1][tt][1]);
          uint32_t x2 = __float_as_uint(acc[0][tt][2] + acc[1][tt][2]), x3 = __float_as_uint(acc[0][tt][3] + acc[1][tt][3]);
          x0 = x0 == SENT ? 0x7FFFFFFFu : x0; x1 = x1 == SENT ? 0x7FFFFFFFu : x1;
          x2 = x2 == SENT ? 0x7FFFFFFFu : x2; x3 = x3 == SENT ? 0x7FFFFFFFu : x3;
          st_pub64(reinterpret_cast<uint2*>(&g_bufB[slot][r0][0][0]) + off, x0, x1);
          st_pub64(reinterpret_cast<uint2*>(&g_bufB[slot][r0 + 1][0][0]) + off, x2, x3);
        }
        tpub = clk32();
      }
      TS(9);
      {
        const uint4* src = &g_bufB[slot][cta][0][0] + 64 * warp + 2 * lane;
        wait_until(tpub, dB);
        uint4 v0 = ld_poll(src), v1 = ld_poll(src + 1);
        int it = 0;
        uint32_t tiss = 0;
        while (!__all_sync(0xffffffffu, pkt_ok(v0) && pkt_ok(v1)) && ++it < POLL_MAX) {
          tiss = clk32();
          if (!pkt_ok(v0)) v0 = ld_poll(src);
          if (!pkt_ok(v1)) v1 = ld_poll(src + 1);
        }
        dB = it ? (tiss - tpub) : (dB > DLY_DEC ? dB - DLY_DEC : 0u);
        TS(10);
        const bool hi = lane & 16;
        float a0 = __uint_as_float(hi ? v1.x : v0.x), a1 = __uint_as_float(hi ? v1.y : v0.y);
        float a2 = __uint_as_float(hi ? v1.z : v0.z), a3 = __uint_as_float(hi ? v1.w : v0.w);
        float b0 = __uint_as_float(hi ? v0.x : v1.x), b1 = __uint_as_float(hi ? v0.y : v1.y);
        float b2 = __uint_as_float(hi ? v0.z : v1.z), b3 = __uint_as_float(hi ? v0.w : v1.w);
        a0 += __shfl_xor_sync(0xffffffffu, b0, 16); a1 += __shfl_xor_sync(0xffffffffu, b1, 16);
        a2 += __shfl_xor_sync(0xffffffffu, b2, 16); a3 += __shfl_xor_sync(0xffffffffu, b3, 16);
        const bool h8 = lane & 8;
        float k0 = h8 ? a2 : a0, k1 = h8 ? a3 : a1, s0 = h8 ? a0 : a2, s1 = h8 ? a1 : a3;
        k0 += __shfl_xor_sync(0xffffffffu, s0, 8); k1 += __shfl_xor_sync(0xffffffffu, s1, 8);
        const bool h4 = lane & 4;
        float z = h4 ? k1 : k0, zs = h4 ? k0 : k1;
        z += __shfl_xor_sync(0xffffffffu, zs, 4);
        z += __shfl_xor_sync(0xffffffffu, z, 2);
        z += __shfl_xor_sync(0xffffffffu, z, 1);
        float zo = __shfl_xor_sync(0xffffffffu, z, 4);
        if ((lane & 7) == 0) {
          uint32_t* d = reinterpret_cast<uint32_t*>(&g_bufC[slot][8 * cta + warp]) + (lane >> 3);
          st_pub32(d, desent(pack2(z, zo)));
        }
        tpub = clk32();
      }
    }
    if (warp >= 4) attn8<true>(sb, tok, lane, warp - 4, 8 * j + g, g_otok + (size_t)(s * 32 + 8 * j + g) * HD + h * 128);
    TS(11);
  }
}

__device__ void moe_part(int m, const bf16* __restrict__ wg, const bf16* __restrict__ wu, const bf16* __restrict__ wd, uint8_t* smem) {
  const int t = threadIdx.x, warp = t >> 5, lane = t & 31;
  float* xs = reinterpret_cast<float*>(smem);
  float* red = reinterpret_cast<float*>(smem + 8192);
  float* hs = reinterpret_cast<float*>(smem + 65536);
  __shared__ float bv[8];
  __shared__ int bi[8];
  __shared__ int sel[2];
  int first = -1;
  for (int pass = 0; pass < 2; pass++) {
    float best = -INFINITY; int bidx = 0x7fffffff;
    for (int i = t; i < S_LEN; i += 256) {
      float v = g_r[i];
      if (i == first) continue;
      if (v > best || (v == best && i < bidx) || bidx == 0x7fffffff) { best = v; bidx = i; }
    }
#pragma unroll
    for (int o = 16; o > 0; o >>= 1) {
      float ov = __shfl_xor_sync(0xffffffffu, best, o); int oi = __shfl_xor_sync(0xffffffffu, bidx, o);
      if (oi != 0x7fffffff && (bidx == 0x7fffffff || ov > best || (ov == best && oi < bidx))) { best = ov; bidx = oi; }
    }
    if (lane == 0) { bv[warp] = best; bi[warp] = bidx; }
    __syncthreads();
    if (t == 0) {
      float b = bv[0]; int ix = bi[0];
      for (int w = 1; w < 8; w++) if (bv[w] > b || (bv[w] == b && bi[w] < ix)) { b = bv[w]; ix = bi[w]; }
      sel[pass] = ix;
    }
    __syncthreads();
    first = sel[0];
  }
  const int s0 = sel[0], s1 = sel[1];
  for (int i = t; i < 2048; i += 256) xs[i] = __bfloat162float(g_xn[(size_t)(i < 1024 ? s0 : s1) * DM + (i & 1023)]);
  __syncthreads();
  {
    int cg = t % 112, kh = t / 112;
    float a[2][2][8];
#pragma unroll
    for (int i = 0; i < 8; i++) { a[0][0][i] = a[0][1][i] = a[1][0][i] = a[1][1][i] = 0.f; }
    if (kh < 2) {
      const bf16* pg = wg + (size_t)(kh * 512) * FF + 896 * m + cg * 8;
      const bf16* pu = wu + (size_t)(kh * 512) * FF + 896 * m + cg * 8;
#pragma unroll 8
      for (int k = 0; k < 512; k++) {
        uint4 gv = __ldg(reinterpret_cast<const uint4*>(pg + (size_t)k * FF));
        uint4 uv = __ldg(reinterpret_cast<const uint4*>(pu + (size_t)k * FF));
        float x0 = xs[kh * 512 + k], x1 = xs[1024 + kh * 512 + k];
        float gf[8] = {bflo(gv.x), bfhi(gv.x), bflo(gv.y), bfhi(gv.y), bflo(gv.z), bfhi(gv.z), bflo(gv.w), bfhi(gv.w)};
        float uf[8] = {bflo(uv.x), bfhi(uv.x), bflo(uv.y), bfhi(uv.y), bflo(uv.z), bfhi(uv.z), bflo(uv.w), bfhi(uv.w)};
#pragma unroll
        for (int i = 0; i < 8; i++) {
          a[0][0][i] += x0 * gf[i]; a[0][1][i] += x1 * gf[i];
          a[1][0][i] += x0 * uf[i]; a[1][1][i] += x1 * uf[i];
        }
      }
      if (kh == 1) {
#pragma unroll
        for (int i = 0; i < 8; i++) {
          red[(0 * 2 + 0) * 896 + cg * 8 + i] = a[0][0][i]; red[(0 * 2 + 1) * 896 + cg * 8 + i] = a[0][1][i];
          red[(1 * 2 + 0) * 896 + cg * 8 + i] = a[1][0][i]; red[(1 * 2 + 1) * 896 + cg * 8 + i] = a[1][1][i];
        }
      }
    }
    __syncthreads();
    if (kh == 0) {
#pragma unroll
      for (int i = 0; i < 8; i++) {
#pragma unroll
        for (int tk = 0; tk < 2; tk++) {
          float gq = bfr(a[0][tk][i] + red[(0 * 2 + tk) * 896 + cg * 8 + i]);
          float uq = bfr(a[1][tk][i] + red[(1 * 2 + tk) * 896 + cg * 8 + i]);
          float sg = bfr(gq / (1.0f + __expf(-gq)));
          g_h[tk][896 * m + cg * 8 + i] = __float2bfloat16_rn(sg * uq);
        }
      }
    }
    __threadfence();
    __syncthreads();
    if (t == 0) {
      atomicAdd(&g_moe_cnt, 1u);
      int it = 0;
      while (*reinterpret_cast<volatile unsigned*>(&g_moe_cnt) < 4u && ++it < (1 << 24)) {}
      __threadfence();
    }
    __syncthreads();
  }
  for (int i = t; i < 2 * FF; i += 256) {
    const volatile unsigned short* p = reinterpret_cast<const volatile unsigned short*>(&g_h[0][0]);
    hs[i] = __uint_as_float(((uint32_t)p[i]) << 16);
  }
  __syncthreads();
  {
    int cg = t & 31, ksl = t >> 5;
    float a[2][8];
#pragma unroll
    for (int i = 0; i < 8; i++) a[0][i] = a[1][i] = 0.f;
    const bf16* pd = wd + (size_t)(ksl * 448) * DM + 256 * m + cg * 8;
#pragma unroll 8
    for (int k = 0; k < 448; k++) {
      uint4 dv = __ldg(reinterpret_cast<const uint4*>(pd + (size_t)k * DM));
      float x0 = hs[ksl * 448 + k], x1 = hs[FF + ksl * 448 + k];
      float df[8] = {bflo(dv.x), bfhi(dv.x), bflo(dv.y), bfhi(dv.y), bflo(dv.z), bfhi(dv.z), bflo(dv.w), bfhi(dv.w)};
#pragma unroll
      for (int i = 0; i < 8; i++) { a[0][i] += x0 * df[i]; a[1][i] += x1 * df[i]; }
    }
#pragma unroll
    for (int i = 0; i < 8; i++) { red[(ksl * 2 + 0) * 256 + cg * 8 + i] = a[0][i]; red[(ksl * 2 + 1) * 256 + cg * 8 + i] = a[1][i]; }
    __syncthreads();
    for (int i = t; i < 512; i += 256) {
      int tk = i >> 8, col = i & 255;
      float y = 0.f;
#pragma unroll
      for (int q = 0; q < 8; q++) y += red[(q * 2 + tk) * 256 + col];
      float rr = g_r[tk == 0 ? s0 : s1];
      float sg = bfr(1.0f / (1.0f + __expf(-rr)));
      g_upd[tk][256 * m + col] = bfr(bfr(y) * sg);
    }
    if (m == 0 && t == 0) { g_sel[0] = s0; g_sel[1] = s1; }
  }
}

typedef CUresult (*EncodeFn)(CUtensorMap*, CUtensorMapDataType, cuuint32_t, void*, const cuuint64_t*, const cuuint64_t*,
                             const cuuint32_t*, const cuuint32_t*, CUtensorMapInterleave, CUtensorMapSwizzle,
                             CUtensorMapL2promotion, CUtensorMapFloatOOBfill);

static void make_map(EncodeFn enc, CUtensorMap* m, const void* ptr, uint64_t inner, uint64_t outer, uint32_t bi, uint32_t bo) {
  cuuint64_t dims[2] = {inner, outer};
  cuuint64_t strides[1] = {inner * 2};
  cuuint32_t box[2] = {bi, bo};
  cuuint32_t es[2] = {1, 1};
  enc(m, CU_TENSOR_MAP_DATA_TYPE_BFLOAT16, 2, const_cast<void*>(ptr), dims, strides, box, es, CU_TENSOR_MAP_INTERLEAVE_NONE,
      CU_TENSOR_MAP_SWIZZLE_128B, CU_TENSOR_MAP_L2_PROMOTION_L2_256B, CU_TENSOR_MAP_FLOAT_OOB_FILL_NONE);
}

extern "C" void kernel_launch(void* const* d_in, const int* in_sizes, int n_in, void* d_out, int out_size) {
  const bf16* x = (const bf16*)d_in[0];
  const bf16* mem0 = (const bf16*)d_in[1];
  const bf16* Wq = (const bf16*)d_in[2];
  const bf16* Wk = (const bf16*)d_in[3];
  const bf16* Wv = (const bf16*)d_in[4];
  const bf16* Wo = (const bf16*)d_in[5];
  const bf16* w_r = (const bf16*)d_in[8];
  const bf16* wg = (const bf16*)d_in[9];
  const bf16* wu = (const bf16*)d_in[10];
  const bf16* wd = (const bf16*)d_in[11];
  bf16* out = (bf16*)d_out;

  static EncodeFn enc = nullptr;
  static void *p_xn, *p_qkv, *p_otok;
  if (!enc) {
    cudaDriverEntryPointQueryResult qr;
    void* fn = nullptr;
    cudaGetDriverEntryPoint("cuTensorMapEncodeTiled", &fn, cudaEnableDefault, &qr);
    enc = (EncodeFn)fn;
    cudaGetSymbolAddress(&p_xn, g_xn);
    cudaGetSymbolAddress(&p_qkv, g_qkv);
    cudaGetSymbolAddress(&p_otok, g_otok);
    cudaFuncSetAttribute(gemm_kernel<256, 4, 0>, cudaFuncAttributeMaxDynamicSharedMemorySize, GemmSmem<256, 4>::TOTAL);
    cudaFuncSetAttribute(gemm_kernel<128, 6, 1>, cudaFuncAttributeMaxDynamicSharedMemorySize, GemmSmem<128, 6>::TOTAL);
    cudaFuncSetAttribute(chain_kernel, cudaFuncAttributeMaxDynamicSharedMemorySize, CH_SMEM);
  }
  CUtensorMap mA, mQ, mK, mV, mO, mWo;
  make_map(enc, &mA, p_xn, DM, S_LEN, 64, 128);
  make_map(enc, &mQ, Wq, HD, DM, 64, 64);
  make_map(enc, &mK, Wk, HD, DM, 64, 64);
  make_map(enc, &mV, Wv, HD, DM, 64, 64);
  make_map(enc, &mO, p_otok, HD, S_LEN, 64, 128);
  make_map(enc, &mWo, Wo, DM, HD, 64, 64);

  cudaStream_t st = cudaStreamPerThread;
  ln_kernel<<<256, 256, 0, st>>>(x, w_r);
  gemm_kernel<256, 4, 0><<<132, 288, GemmSmem<256, 4>::TOTAL, st>>>(mA, mQ, mK, mV, 16, 16, 16 * 48, nullptr, (bf16*)p_qkv);
  chain_kernel<<<132, 256, CH_SMEM, st>>>(mem0, Wq, Wk, Wv, Wo, wg, wu, wd);
  gemm_kernel<128, 6, 1><<<128, 288, GemmSmem<128, 6>::TOTAL, st>>>(mO, mWo, mWo, mWo, 64, 16, 16 * 8, x, out);
}
```

```cpp
#include <cuda_runtime.h>
#include <cuda_bf16.h>
#include <cuda.h>
#include <stdint.h>

typedef __nv_bfloat16 bf16;

#define S_LEN 2048
#define DM 1024
#define NH 32
#define DH 128
#define NSEG 64
#define SEGL 32
#define HD 4096
#define NQKV 12288
#define FF 3584
#define SENT 0xFFFFFFFFu

__device__ __align__(1024) bf16 g_xn[S_LEN * DM];
__device__ __align__(1024) bf16 g_qkv[(size_t)S_LEN * NQKV];
__device__ __align__(1024) bf16 g_otok[(size_t)S_LEN * HD];
__device__ float g_r[S_LEN];
__device__ __align__(128) uint4 g_bufA[4][128][96];
__device__ __align__(128) uint4 g_bufB[4][128][16][32];
__device__ __align__(128) uint4 g_bufC[4][1024];
__device__ __align__(128) bf16 g_h[2][FF];
__device__ float g_upd[2][DM];
__device__ int g_sel[2];
__device__ unsigned g_moe_cnt;
#define DLY_A 300u
#define DLY_B 800u
#define DLY_C 700u
#define TS(i)

__device__ __forceinline__ float bfr(float x) { return __bfloat162float(__float2bfloat16_rn(x)); }
__device__ __forceinline__ uint32_t pack2(float lo, float hi) {
  __nv_bfloat162 v = __floats2bfloat162_rn(lo, hi);
  return *reinterpret_cast<uint32_t*>(&v);
}
__device__ __forceinline__ float bflo(uint32_t v) { return __uint_as_float(v << 16); }
__device__ __forceinline__ float bfhi(uint32_t v) { return __uint_as_float(v & 0xFFFF0000u); }
__device__ __forceinline__ uint32_t smem_u32(const void* p) { return (uint32_t)__cvta_generic_to_shared(p); }

__device__ __forceinline__ uint4 ld_poll(const uint4* p) {
  uint4 v;
  asm volatile("ld.relaxed.gpu.global.v4.u32 {%0,%1,%2,%3},[%4];" : "=r"(v.x), "=r"(v.y), "=r"(v.z), "=r"(v.w) : "l"(p) : "memory");
  return v;
}
__device__ __forceinline__ void st_pub32(void* p, uint32_t v) {
  asm volatile("st.relaxed.gpu.global.u32 [%0],%1;" ::"l"(p), "r"(v) : "memory");
}
__device__ __forceinline__ void st_pub64(void* p, uint32_t a, uint32_t b) {
  asm volatile("st.relaxed.gpu.global.v2.u32 [%0],{%1,%2};" ::"l"(p), "r"(a), "r"(b) : "memory");
}
__device__ __forceinline__ bool pkt_ok(const uint4& v) { return v.x != SENT && v.y != SENT && v.z != SENT && v.w != SENT; }
__device__ __forceinline__ uint32_t desent(uint32_t v) { return v == SENT ? 0x7FFF7FFFu : v; }

__device__ __forceinline__ void ldsm4(uint32_t& r0, uint32_t& r1, uint32_t& r2, uint32_t& r3, uint32_t addr) {
  asm volatile("ldmatrix.sync.aligned.m8n8.x4.shared.b16 {%0,%1,%2,%3},[%4];" : "=r"(r0), "=r"(r1), "=r"(r2), "=r"(r3) : "r"(addr) : "memory");
}
__device__ __forceinline__ void ldsm4t(uint32_t& r0, uint32_t& r1, uint32_t& r2, uint32_t& r3, uint32_t addr) {
  asm volatile("ldmatrix.sync.aligned.m8n8.x4.trans.shared.b16 {%0,%1,%2,%3},[%4];" : "=r"(r0), "=r"(r1), "=r"(r2), "=r"(r3) : "r"(addr) : "memory");
}
__device__ __forceinline__ void mma16816(float (&d)[4], uint32_t a0, uint32_t a1, uint32_t a2, uint32_t a3, uint32_t b0, uint32_t b1) {
  asm volatile("mma.sync.aligned.m16n8k16.row.col.f32.bf16.bf16.f32 {%0,%1,%2,%3},{%4,%5,%6,%7},{%8,%9},{%0,%1,%2,%3};"
               : "+f"(d[0]), "+f"(d[1]), "+f"(d[2]), "+f"(d[3])
               : "r"(a0), "r"(a1), "r"(a2), "r"(a3), "r"(b0), "r"(b1));
}
__device__ __forceinline__ void cp_async16(uint32_t dst, const void* src) {
  asm volatile("cp.async.cg.shared.global [%0],[%1],16;" ::"r"(dst), "l"(src) : "memory");
}
__device__ __forceinline__ void cp_commit() { asm volatile("cp.async.commit_group;" ::: "memory"); }
template <int N>
__device__ __forceinline__ void cp_wait() { asm volatile("cp.async.wait_group %0;" ::"n"(N) : "memory"); }

__device__ __forceinline__ void mbar_init(uint32_t bar, uint32_t cnt) { asm volatile("mbarrier.init.shared::cta.b64 [%0],%1;" ::"r"(bar), "r"(cnt) : "memory"); }
__device__ __forceinline__ void mbar_expect_tx(uint32_t bar, uint32_t bytes) {
  asm volatile("mbarrier.arrive.expect_tx.shared::cta.b64 _,[%0],%1;" ::"r"(bar), "r"(bytes) : "memory");
}
__device__ __forceinline__ void mbar_arrive(uint32_t bar) { asm volatile("mbarrier.arrive.shared::cta.b64 _,[%0];" ::"r"(bar) : "memory"); }
__device__ __forceinline__ void mbar_wait(uint32_t bar, uint32_t parity) {
  asm volatile(
      "{\n.reg .pred p;\n"
      "WAIT_LOOP:\n"
      "mbarrier.try_wait.parity.shared::cta.b64 p,[%0],%1;\n"
      "@p bra WAIT_DONE;\n"
      "bra WAIT_LOOP;\n"
      "WAIT_DONE:\n}\n" ::"r"(bar), "r"(parity) : "memory");
}
__device__ __forceinline__ void tma_load2d(uint32_t dst, const CUtensorMap* tm, uint32_t bar, int c0, int c1) {
  asm volatile("cp.async.bulk.tensor.2d.shared::cluster.global.mbarrier::complete_tx::bytes [%0],[%1,{%3,%4}],[%2];"
               ::"r"(dst), "l"(tm), "r"(bar), "r"(c0), "r"(c1) : "memory");
}
__device__ __forceinline__ void wg_fence() { asm volatile("wgmma.fence.sync.aligned;" ::: "memory"); }
__device__ __forceinline__ void wg_commit() { asm volatile("wgmma.commit_group.sync.aligned;" ::: "memory"); }
template <int N>
__device__ __forceinline__ void wg_wait() { asm volatile("wgmma.wait_group.sync.aligned %0;" ::"n"(N) : "memory"); }
__device__ __forceinline__ uint64_t make_desc(uint32_t addr, uint32_t lbo, uint32_t sbo) {
  return (uint64_t)((addr & 0x3FFFF) >> 4) | ((uint64_t)(lbo >> 4) << 16) | ((uint64_t)(sbo >> 4) << 32) | (1ull << 62);
}

__device__ __forceinline__ void wgmma_m64n256k16(float (&d)[128], uint64_t da, uint64_t db, int scaleD) {
  asm volatile(
    "{\n.reg .pred p;\nsetp.ne.b32 p, %130, 0;\n"
    "wgmma.mma_async.sync.aligned.m64n256k16.f32.bf16.bf16 "
    "{%0, %1, %2, %3, %4, %5, %6, %7, %8, %9, %10, %11, %12, %13, %14, %15, %16, %17, %18, %19, %20, %21, %22, %23, %24, %25, %26, %27, %28, %29, %30, %31, %32, %33, %34, %35, %36, %37, %38, %39, %40, %41, %42, %43, %44, %45, %46, %47, %48, %49, %50, %51, %52, %53, %54, %55, %56, %57, %58, %59, %60, %61, %62, %63, %64, %65, %66, %67, %68, %69, %70, %71, %72, %73, %74, %75, %76, %77, %78, %79, %80, %81, %82, %83, %84, %85, %86, %87, %88, %89, %90, %91, %92, %93, %94, %95, %96, %97, %98, %99, %100, %101, %102, %103, %104, %105, %106, %107, %108, %109, %110, %111, %112, %113, %114, %115, %116, %117, %118, %119, %120, %121, %122, %123, %124, %125, %126, %127}, %128, %129, p, 1, 1, 0, 1;\n}\n"
    : "+f"(d[0]), "+f"(d[1]), "+f"(d[2]), "+f"(d[3]), "+f"(d[4]), "+f"(d[5]), "+f"(d[6]), "+f"(d[7]), "+f"(d[8]), "+f"(d[9]), "+f"(d[10]), "+f"(d[11]), "+f"(d[12]), "+f"(d[13]), "+f"(d[14]), "+f"(d[15]), "+f"(d[16]), "+f"(d[17]), "+f"(d[18]), "+f"(d[19]), "+f"(d[20]), "+f"(d[21]), "+f"(d[22]), "+f"(d[23]), "+f"(d[24]), "+f"(d[25]), "+f"(d[26]), "+f"(d[27]), "+f"(d[28]), "+f"(d[29]), "+f"(d[30]), "+f"(d[31]), "+f"(d[32]), "+f"(d[33]), "+f"(d[34]), "+f"(d[35]), "+f"(d[36]), "+f"(d[37]), "+f"(d[38]), "+f"(d[39]), "+f"(d[40]), "+f"(d[41]), "+f"(d[42]), "+f"(d[43]), "+f"(d[44]), "+f"(d[45]), "+f"(d[46]), "+f"(d[47]), "+f"(d[48]), "+f"(d[49]), "+f"(d[50]), "+f"(d[51]), "+f"(d[52]), "+f"(d[53]), "+f"(d[54]), "+f"(d[55]), "+f"(d[56]), "+f"(d[57]), "+f"(d[58]), "+f"(d[59]), "+f"(d[60]), "+f"(d[61]), "+f"(d[62]), "+f"(d[63]), "+f"(d[64]), "+f"(d[65]), "+f"(d[66]), "+f"(d[67]), "+f"(d[68]), "+f"(d[69]), "+f"(d[70]), "+f"(d[71]), "+f"(d[72]), "+f"(d[73]), "+f"(d[74]), "+f"(d[75]), "+f"(d[76]), "+f"(d[77]), "+f"(d[78]), "+f"(d[79]), "+f"(d[80]), "+f"(d[81]), "+f"(d[82]), "+f"(d[83]), "+f"(d[84]), "+f"(d[85]), "+f"(d[86]), "+f"(d[87]), "+f"(d[88]), "+f"(d[89]), "+f"(d[90]), "+f"(d[91]), "+f"(d[92]), "+f"(d[93]), "+f"(d[94]), "+f"(d[95]), "+f"(d[96]), "+f"(d[97]), "+f"(d[98]), "+f"(d[99]), "+f"(d[100]), "+f"(d[101]), "+f"(d[102]), "+f"(d[103]), "+f"(d[104]), "+f"(d[105]), "+f"(d[106]), "+f"(d[107]), "+f"(d[108]), "+f"(d[109]), "+f"(d[110]), "+f"(d[111]), "+f"(d[112]), "+f"(d[113]), "+f"(d[114]), "+f"(d[115]), "+f"(d[116]), "+f"(d[117]), "+f"(d[118]), "+f"(d[119]), "+f"(d[120]), "+f"(d[121]), "+f"(d[122]), "+f"(d[123]), "+f"(d[124]), "+f"(d[125]), "+f"(d[126]), "+f"(d[127])
    : "l"(da), "l"(db), "r"(scaleD));
}

__device__ __forceinline__ void wgmma_m64n128k16(float (&d)[64], uint64_t da, uint64_t db, int scaleD) {
  asm volatile(
    "{\n.reg .pred p;\nsetp.ne.b32 p, %66, 0;\n"
    "wgmma.mma_async.sync.aligned.m64n128k16.f32.bf16.bf16 "
    "{%0, %1, %2, %3, %4, %5, %6, %7, %8, %9, %10, %11, %12, %13, %14, %15, %16, %17, %18, %19, %20, %21, %22, %23, %24, %25, %26, %27, %28, %29, %30, %31, %32, %33, %34, %35, %36, %37, %38, %39, %40, %41, %42, %43, %44, %45, %46, %47, %48, %49, %50, %51, %52, %53, %54, %55, %56, %57, %58, %59, %60, %61, %62, %63}, %64, %65, p, 1, 1, 0, 1;\n}\n"
    : "+f"(d[0]), "+f"(d[1]), "+f"(d[2]), "+f"(d[3]), "+f"(d[4]), "+f"(d[5]), "+f"(d[6]), "+f"(d[7]), "+f"(d[8]), "+f"(d[9]), "+f"(d[10]), "+f"(d[11]), "+f"(d[12]), "+f"(d[13]), "+f"(d[14]), "+f"(d[15]), "+f"(d[16]), "+f"(d[17]), "+f"(d[18]), "+f"(d[19]), "+f"(d[20]), "+f"(d[21]), "+f"(d[22]), "+f"(d[23]), "+f"(d[24]), "+f"(d[25]), "+f"(d[26]), "+f"(d[27]), "+f"(d[28]), "+f"(d[29]), "+f"(d[30]), "+f"(d[31]), "+f"(d[32]), "+f"(d[33]), "+f"(d[34]), "+f"(d[35]), "+f"(d[36]), "+f"(d[37]), "+f"(d[38]), "+f"(d[39]), "+f"(d[40]), "+f"(d[41]), "+f"(d[42]), "+f"(d[43]), "+f"(d[44]), "+f"(d[45]), "+f"(d[46]), "+f"(d[47]), "+f"(d[48]), "+f"(d[49]), "+f"(d[50]), "+f"(d[51]), "+f"(d[52]), "+f"(d[53]), "+f"(d[54]), "+f"(d[55]), "+f"(d[56]), "+f"(d[57]), "+f"(d[58]), "+f"(d[59]), "+f"(d[60]), "+f"(d[61]), "+f"(d[62]), "+f"(d[63])
    : "l"(da), "l"(db), "r"(scaleD));
}

template <int BN> struct WG;
template <> struct WG<256> { static __device__ __forceinline__ void mma(float (&d)[128], uint64_t a, uint64_t b, int s) { wgmma_m64n256k16(d, a, b, s); } };
template <> struct WG<128> { static __device__ __forceinline__ void mma(float (&d)[64], uint64_t a, uint64_t b, int s) { wgmma_m64n128k16(d, a, b, s); } };

__global__ void __launch_bounds__(256) ln_kernel(const bf16* __restrict__ x, const bf16* __restrict__ w_r) {
  int warp = threadIdx.x >> 5, lane = threadIdx.x & 31;
  int row = blockIdx.x * 8 + warp;
  const uint4* xp = reinterpret_cast<const uint4*>(x + (size_t)row * DM);
  uint4 v[4];
#pragma unroll
  for (int i = 0; i < 4; i++) v[i] = xp[lane + 32 * i];
  float f[32];
#pragma unroll
  for (int i = 0; i < 4; i++) {
    f[8 * i + 0] = bflo(v[i].x); f[8 * i + 1] = bfhi(v[i].x);
    f[8 * i + 2] = bflo(v[i].y); f[8 * i + 3] = bfhi(v[i].y);
    f[8 * i + 4] = bflo(v[i].z); f[8 * i + 5] = bfhi(v[i].z);
    f[8 * i + 6] = bflo(v[i].w); f[8 * i + 7] = bfhi(v[i].w);
  }
  float s = 0.f;
#pragma unroll
  for (int i = 0; i < 32; i++) s += f[i];
#pragma unroll
  for (int o = 16; o > 0; o >>= 1) s += __shfl_xor_sync(0xffffffffu, s, o);
  float mean = s * (1.0f / DM);
  float q = 0.f;
#pragma unroll
  for (int i = 0; i < 32; i++) { float d = f[i] - mean; q += d * d; }
#pragma unroll
  for (int o = 16; o > 0; o >>= 1) q += __shfl_xor_sync(0xffffffffu, q, o);
  float var = bfr(q * (1.0f / DM));
  float mb = bfr(mean);
  float den = bfr(sqrtf(bfr(var + 1e-5f)));
  const uint4* wp = reinterpret_cast<const uint4*>(w_r);
  uint4* op = reinterpret_cast<uint4*>(g_xn + (size_t)row * DM);
  float r = 0.f;
#pragma unroll
  for (int i = 0; i < 4; i++) {
    uint4 w = wp[lane + 32 * i];
    float y[8];
#pragma unroll
    for (int k = 0; k < 8; k++) y[k] = bfr(bfr(f[8 * i + k] - mb) / den);
    r += y[0] * bflo(w.x) + y[1] * bfhi(w.x) + y[2] * bflo(w.y) + y[3] * bfhi(w.y) + y[4] * bflo(w.z) + y[5] * bfhi(w.z) +
         y[6] * bflo(w.w) + y[7] * bfhi(w.w);
    op[lane + 32 * i] = make_uint4(pack2(y[0], y[1]), pack2(y[2], y[3]), pack2(y[4], y[5]), pack2(y[6], y[7]));
  }
#pragma unroll
  for (int o = 16; o > 0; o >>= 1) r += __shfl_xor_sync(0xffffffffu, r, o);
  if (lane == 0) g_r[row] = bfr(r);
  int gt = blockIdx.x * 256 + threadIdx.x;
  const uint4 sv = make_uint4(SENT, SENT, SENT, SENT);
  uint4* a = &g_bufA[0][0][0];
  for (int i = gt; i < 2 * 128 * 96; i += 65536) a[i] = sv;
  uint4* b = &g_bufB[0][0][0][0];
  for (int i = gt; i < 2 * 128 * 32 * 16; i += 65536) b[i] = sv;
  uint4* c = &g_bufC[0][0];
  for (int i = gt; i < 2 * 1024; i += 65536) c[i] = sv;
  if (gt == 0) g_moe_cnt = 0;
}

template <int BN, int STAGES>
struct GemmSmem {
  static constexpr int A_BYTES = 128 * 64 * 2;
  static constexpr int B_BYTES = 64 * BN * 2;
  static constexpr int STAGE_BYTES = A_BYTES + B_BYTES;
  static constexpr int TOTAL = STAGES * STAGE_BYTES + 1024 + 256;
};

__device__ __forceinline__ void quad_transpose(uint32_t (&v)[4], int c) {
  {
    uint32_t s0 = (c & 1) ? v[0] : v[1];
    uint32_t s1 = (c & 1) ? v[2] : v[3];
    uint32_t r0 = __shfl_xor_sync(0xffffffffu, s0, 1);
    uint32_t r1 = __shfl_xor_sync(0xffffffffu, s1, 1);
    if (c & 1) { v[0] = r0; v[2] = r1; } else { v[1] = r0; v[3] = r1; }
  }
  {
    uint32_t s0 = (c & 2) ? v[0] : v[2];
    uint32_t s1 = (c & 2) ? v[1] : v[3];
    uint32_t r0 = __shfl_xor_sync(0xffffffffu, s0, 2);
    uint32_t r1 = __shfl_xor_sync(0xffffffffu, s1, 2);
    if (c & 2) { v[0] = r0; v[1] = r1; } else { v[2] = r0; v[3] = r1; }
  }
}

__device__ __forceinline__ uint32_t add3(uint32_t a, uint32_t x, uint32_t b) {
  float lo = bfr(bflo(x) + bflo(a)) + bflo(b);
  float hi = bfr(bfhi(x) + bfhi(a)) + bfhi(b);
  return pack2(lo, hi);
}

template <int BN, int STAGES, int EPI>
__global__ void __launch_bounds__(288, 1)
gemm_kernel(const __grid_constant__ CUtensorMap tmA, const __grid_constant__ CUtensorMap tmB0,
            const __grid_constant__ CUtensorMap tmB1, const __grid_constant__ CUtensorMap tmB2,
            int kblocks, int tiles_m, int tiles_total, const bf16* __restrict__ xin, bf16* __restrict__ outp) {
  using SM = GemmSmem<BN, STAGES>;
  extern __shared__ uint8_t smem_raw[];
  uint32_t base = (smem_u32(smem_raw) + 1023) & ~1023u;
  uint32_t bars = base + STAGES * SM::STAGE_BYTES;
  int warp = threadIdx.x >> 5, lane = threadIdx.x & 31;
  if (threadIdx.x == 0) {
    for (int i = 0; i < STAGES; i++) { mbar_init(bars + 8 * i, 1); mbar_init(bars + 8 * (STAGES + i), 8); }
    asm volatile("fence.mbarrier_init.release.cluster;" ::: "memory");
  }
  __syncthreads();
  if (warp == 8) {
    if (lane == 0) {
      int it = 0;
      for (int t = blockIdx.x; t < tiles_total; t += gridDim.x) {
        int tm = t % tiles_m, tn = t / tiles_m;
        int n0 = tn * BN;
        const CUtensorMap* tb = &tmB0;
        if (EPI == 0) { int wsel = n0 >> 12; tb = wsel == 0 ? &tmB0 : (wsel == 1 ? &tmB1 : &tmB2); n0 &= 4095; }
        for (int kb = 0; kb < kblocks; kb++, it++) {
          int st = it % STAGES; uint32_t ph = (it / STAGES) & 1;
          mbar_wait(bars + 8 * (STAGES + st), ph ^ 1);
          uint32_t sa = base + st * SM::STAGE_BYTES, sb = sa + SM::A_BYTES;
          mbar_expect_tx(bars + 8 * st, SM::STAGE_BYTES);
          tma_load2d(sa, &tmA, bars + 8 * st, kb * 64, tm * 128);
#pragma unroll
          for (int i = 0; i < BN / 64; i++) tma_load2d(sb + i * 8192, tb, bars + 8 * st, n0 + i * 64, kb * 64);
        }
      }
    }
  } else {
    int wg = warp >> 2;
    int g = lane >> 2, c = lane & 3;
    int it = 0;
    float acc[BN / 2];
    for (int t = blockIdx.x; t < tiles_total; t += gridDim.x) {
      int tm = t % tiles_m, tn = t / tiles_m;
      for (int kb = 0; kb < kblocks; kb++, it++) {
        int st = it % STAGES; uint32_t ph = (it / STAGES) & 1;
        mbar_wait(bars + 8 * st, ph);
        uint32_t sa = base + st * SM::STAGE_BYTES + wg * 8192, sb = base + st * SM::STAGE_BYTES + SM::A_BYTES;
        wg_fence();
#pragma unroll
        for (int kk = 0; kk < 4; kk++) {
          uint64_t da = make_desc(sa + kk * 32, 16, 1024);
          uint64_t db = make_desc(sb + kk * 2048, 8192, 1024);
          WG<BN>::mma(acc, da, db, (kb | kk) != 0);
        }
        wg_commit();
        if (kb > 0) {
          wg_wait<1>();
          int pst = (it - 1) % STAGES;
          if (lane == 0) mbar_arrive(bars + 8 * (STAGES + pst));
        }
      }
      wg_wait<0>();
      { int pst = (it - 1) % STAGES; if (lane == 0) mbar_arrive(bars + 8 * (STAGES + pst)); }
      int row0 = tm * 128 + wg * 64 + (warp & 3) * 16 + g;
      int sel0 = -1, sel1 = -1;
      if (EPI == 1) { sel0 = g_sel[0]; sel1 = g_sel[1]; }
#pragma unroll
      for (int half = 0; half < 2; half++) {
        int row = row0 + half * 8;
#pragma unroll
        for (int q = 0; q < BN / 32; q++) {
          uint32_t v[4];
#pragma unroll
          for (int tt = 0; tt < 4; tt++) v[tt] = pack2(acc[(q * 4 + tt) * 4 + half * 2], acc[(q * 4 + tt) * 4 + half * 2 + 1]);
          quad_transpose(v, c);
          int col = tn * BN + q * 32 + c * 8;
          if (EPI == 0) {
            __stcs(reinterpret_cast<uint4*>(outp + (size_t)row * NQKV + col), make_uint4(v[0], v[1], v[2], v[3]));
          } else {
            uint4 xv = *reinterpret_cast<const uint4*>(xin + (size_t)row * DM + col);
            uint4 bv = *reinterpret_cast<const uint4*>(g_xn + (size_t)row * DM + col);
            if (row == sel0 || row == sel1) {
              const float* u = &g_upd[row == sel0 ? 0 : 1][col];
              bv.x = pack2(bflo(bv.x) + u[0], bfhi(bv.x) + u[1]);
              bv.y = pack2(bflo(bv.y) + u[2], bfhi(bv.y) + u[3]);
              bv.z = pack2(bflo(bv.z) + u[4], bfhi(bv.z) + u[5]);
              bv.w = pack2(bflo(bv.w) + u[6], bfhi(bv.w) + u[7]);
            }
            uint4 o = make_uint4(add3(v[0], xv.x, bv.x), add3(v[1], xv.y, bv.y), add3(v[2], xv.z, bv.z), add3(v[3], xv.w, bv.w));
            *reinterpret_cast<uint4*>(outp + (size_t)row * DM + col) = o;
          }
        }
      }
    }
  }
}

#define RK 10
#define SK (16 - RK)
#define TP 272
#define OFF_WQS 0
#define OFF_MEMT (OFF_WQS + 8 * SK * 3 * 512)
#define OFF_RED (OFF_MEMT + 16384)
#define OFF_QKVM (OFF_RED + 12288)
#define OFF_TOK (OFF_QKVM + 6144)
#define TOK_BYTES (72 * TP)
#define OFF_SA (OFF_TOK + 2 * TOK_BYTES)
#define OFF_BAR (OFF_SA + 8 * TP)
#define CH_END (OFF_BAR + 64)
#define CH_STG2 (131072)
#define CH_SMEM (196608 + 1024)
static_assert(CH_END <= CH_SMEM, "smem");

__device__ void moe_part(int m, const bf16* __restrict__ wg, const bf16* __restrict__ wu, const bf16* __restrict__ wd, uint8_t* smem);

__device__ __forceinline__ void bulk_copy(uint32_t dst, const void* src, uint32_t bytes, uint32_t bar) {
  asm volatile("cp.async.bulk.shared::cluster.global.mbarrier::complete_tx::bytes [%0],[%1],%2,[%3];"
               ::"r"(dst), "l"(src), "r"(bytes), "r"(bar) : "memory");
}
__device__ __forceinline__ void st_pub128(void* p, uint32_t v) {
  asm volatile("st.relaxed.gpu.global.v4.u32 [%0],{%1,%1,%1,%1};" ::"l"(p), "r"(v) : "memory");
}
__device__ __forceinline__ void sts128(uint32_t addr, const uint4& v) {
  asm volatile("st.shared.v4.u32 [%0],{%1,%2,%3,%4};" ::"r"(addr), "r"(v.x), "r"(v.y), "r"(v.z), "r"(v.w) : "memory");
}

#define POLL_MAX (1 << 22)
__device__ __forceinline__ uint32_t clk32() { uint32_t c; asm volatile("mov.u32 %0,%%clock;" : "=r"(c)); return c; }
__device__ __forceinline__ void wait_until(uint32_t t0, uint32_t d) { while (clk32() - t0 < d) {} }
#define DLY_DEC 48u

__device__ __forceinline__ float ex2f(float x) { float y; asm("ex2.approx.ftz.f32 %0,%1;" : "=f"(y) : "f"(x)); return y; }
__device__ __forceinline__ float rcpf(float x) { float y; asm("rcp.approx.ftz.f32 %0,%1;" : "=f"(y) : "f"(x)); return y; }
template <bool TOK>
__device__ __forceinline__ void attn8(uint32_t sb, uint32_t tok, int lane, int wq4, int tr, bf16* otok_row) {
  const int g = lane >> 2, c = lane & 3;
  float sc[5][4];
#pragma unroll
  for (int n = 0; n < 5; n++)
#pragma unroll
    for (int i = 0; i < 4; i++) sc[n][i] = 0.f;
  const uint32_t tokrow = tok + (lane & 7) * TP + (lane >> 3) * 16;
  const uint32_t qaddr = TOK ? (tok + (64 + (lane & 7)) * TP + (lane >> 4) * 16) : (sb + OFF_QKVM + ((lane & 7) + 8 * (lane >> 4)) * 16);
#pragma unroll
  for (int kp = 0; kp < 4; kp++) {
    uint32_t q0[4], q1[4], km[4], kt[4][4];
    if (TOK) {
      ldsm4(q0[0], q0[1], q0[2], q0[3], qaddr + 64 * kp);
      ldsm4(q1[0], q1[1], q1[2], q1[3], qaddr + 64 * kp + 32);
    } else {
      ldsm4t(q0[0], q0[1], q0[2], q0[3], qaddr + 512 * kp);
      ldsm4t(q1[0], q1[1], q1[2], q1[3], qaddr + 512 * kp + 256);
    }
    ldsm4t(km[0], km[1], km[2], km[3], sb + OFF_QKVM + (128 + 32 * kp + lane) * 16);
#pragma unroll
    for (int n = 0; n < 4; n++) ldsm4(kt[n][0], kt[n][1], kt[n][2], kt[n][3], tokrow + 8 * n * TP + 64 * kp);
    mma16816(sc[0], q0[0], q0[1], q0[2], q0[3], km[0], km[1]);
#pragma unroll
    for (int n = 0; n < 4; n++) mma16816(sc[n + 1], q0[0], q0[1], q0[2], q0[3], kt[n][0], kt[n][1]);
    mma16816(sc[0], q1[0], q1[1], q1[2], q1[3], km[2], km[3]);
#pragma unroll
    for (int n = 0; n < 4; n++) mma16816(sc[n + 1], q1[0], q1[1], q1[2], q1[3], kt[n][2], kt[n][3]);
  }
  uint32_t vma[4], vmb[4], vt[4][4];
  ldsm4(vma[0], vma[1], vma[2], vma[3], sb + OFF_QKVM + (256 + 32 * wq4 + lane) * 16);
  ldsm4(vmb[0], vmb[1], vmb[2], vmb[3], sb + OFF_QKVM + (256 + 32 * wq4 + (lane ^ 8)) * 16);
#pragma unroll
  for (int n = 0; n < 4; n++) ldsm4t(vt[n][0], vt[n][1], vt[n][2], vt[n][3], tok + (32 + lane) * TP + (32 * wq4 + 8 * n) * 2);
  const float scale = 0.08838834764831845f;
  float m0 = -3.0e38f;
#pragma unroll
  for (int n = 0; n < 5; n++) {
    uint32_t p1 = pack2(sc[n][0], sc[n][1]);
    uint32_t p2 = pack2(bflo(p1) * scale, bfhi(p1) * scale);
    sc[n][0] = bflo(p2);
    sc[n][1] = bfhi(p2);
    if (TOK && n > 0) {
      int kt = 8 * (n - 1) + 2 * c;
      if (kt > tr) sc[n][0] = -1.0e9f;
      if (kt + 1 > tr) sc[n][1] = -1.0e9f;
    }
    m0 = fmaxf(m0, fmaxf(sc[n][0], sc[n][1]));
  }
  m0 = fmaxf(m0, __shfl_xor_sync(0xffffffffu, m0, 1));
  m0 = fmaxf(m0, __shfl_xor_sync(0xffffffffu, m0, 2));
  const float l2e = 1.4426950408889634f;
  float s0 = 0.f;
#pragma unroll
  for (int n = 0; n < 5; n++) {
    sc[n][0] = ex2f((sc[n][0] - m0) * l2e);
    sc[n][1] = ex2f((sc[n][1] - m0) * l2e);
    s0 += sc[n][0] + sc[n][1];
  }
  s0 += __shfl_xor_sync(0xffffffffu, s0, 1);
  s0 += __shfl_xor_sync(0xffffffffu, s0, 2);
  const float i0 = rcpf(s0);
  uint32_t pp[5];
#pragma unroll
  for (int n = 0; n < 5; n++) pp[n] = pack2(sc[n][0] * i0, sc[n][1] * i0);
  float o[4][4];
#pragma unroll
  for (int n = 0; n < 4; n++) {
#pragma unroll
    for (int i = 0; i < 4; i++) o[n][i] = 0.f;
    mma16816(o[n], pp[1], pp[1], pp[2], pp[2], vt[n][0], vt[n][1]);
  }
#pragma unroll
  for (int n = 0; n < 4; n++) mma16816(o[n], pp[3], pp[3], pp[4], pp[4], vt[n][2], vt[n][3]);
  mma16816(o[0], pp[0], 0u, 0u, 0u, vma[0], vma[1]);
  mma16816(o[1], pp[0], 0u, 0u, 0u, vmb[0], vmb[1]);
  mma16816(o[2], pp[0], 0u, 0u, 0u, vma[2], vma[3]);
  mma16816(o[3], pp[0], 0u, 0u, 0u, vmb[2], vmb[3]);
#pragma unroll
  for (int n = 0; n < 4; n++) {
    const int e = 32 * wq4 + 8 * n + 2 * c;
    if (TOK) *reinterpret_cast<uint32_t*>(otok_row + e) = pack2(o[n][0], o[n][1]);
    else asm volatile("st.shared.u32 [%0],%1;" ::"r"(sb + OFF_SA + g * TP + e * 2), "r"(pack2(o[n][0], o[n][1])) : "memory");
  }
}

__global__ void __launch_bounds__(256, 1)
chain_kernel(const bf16* __restrict__ mem0, const bf16* __restrict__ Wq, const bf16* __restrict__ Wk, const bf16* __restrict__ Wv,
             const bf16* __restrict__ Wo, const bf16* __restrict__ wgate, const bf16* __restrict__ wup, const bf16* __restrict__ wdown) {
  extern __shared__ __align__(1024) uint8_t smem[];
  const int cta = blockIdx.x, t = threadIdx.x, warp = t >> 5, lane = t & 31;
  if (cta >= 128) {
    moe_part(cta - 128, wgate, wup, wdown, smem);
    return;
  }
  const int h = cta >> 2, j = cta & 3;
  const int g = lane >> 2, c = lane & 3;
  const uint32_t sb = smem_u32(smem);
  const int mg = warp & 1, kq = warp >> 1;

  uint32_t wq[RK][3][4];
  uint32_t wo[2][8][4];
  {
    for (int i = t; i < 128 * 4; i += 256)
      asm volatile("prefetch.global.L2 [%0];" ::"l"(Wo + (size_t)(h * 128 + (i >> 2)) * DM + 256 * j + (i & 3) * 64));
    for (int i = t; i < 3 * 1024 * 4; i += 256) {
      int which = i >> 12, k = (i >> 2) & 1023, ch = i & 3;
      const bf16* W = which == 0 ? Wq : (which == 1 ? Wk : Wv);
      cp_async16(sb + (which * 1024 + k) * 64 + ch * 16, W + (size_t)k * HD + h * 128 + 32 * j + ch * 8);
    }
    cp_commit(); cp_wait<0>();
    __syncthreads();
    uint32_t tmp[SK][3][4];
#pragma unroll
    for (int ks = 0; ks < 16; ks++) {
#pragma unroll
      for (int tt = 0; tt < 3; tt++) {
        int tile = 3 * mg + tt;
        int which = tile >> 1, ch = tile & 1;
        int k = (16 * kq + ks) * 16 + (lane & 7) + 8 * (lane >> 4);
        uint32_t addr = sb + (which * 1024 + k) * 64 + ch * 32 + 16 * ((lane >> 3) & 1);
        if (ks < RK) ldsm4t(wq[ks][tt][0], wq[ks][tt][1], wq[ks][tt][2], wq[ks][tt][3], addr);
        else ldsm4t(tmp[ks - RK][tt][0], tmp[ks - RK][tt][1], tmp[ks - RK][tt][2], tmp[ks - RK][tt][3], addr);
      }
    }
    __syncthreads();
#pragma unroll
    for (int ks = 0; ks < SK; ks++)
#pragma unroll
      for (int tt = 0; tt < 3; tt++)
        *reinterpret_cast<uint4*>(smem + OFF_WQS + (((warp * SK + ks) * 3 + tt) * 32 + lane) * 16) =
            make_uint4(tmp[ks][tt][0], tmp[ks][tt][1], tmp[ks][tt][2], tmp[ks][tt][3]);
    for (int i = t; i < 128 * 32; i += 256) {
      int e = i >> 5, ch = i & 31;
      cp_async16(sb + CH_STG2 + e * 512 + ch * 16, Wo + (size_t)(h * 128 + e) * DM + 256 * j + ch * 8);
    }
    cp_commit(); cp_wait<0>();
    __syncthreads();
#pragma unroll
    for (int tt = 0; tt < 2; tt++)
#pragma unroll
      for (int ks = 0; ks < 8; ks++) {
        int e = 16 * ks + (lane & 7) + 8 * (lane >> 4);
        uint32_t addr = sb + CH_STG2 + e * 512 + (32 * warp + 16 * tt + 8 * ((lane >> 3) & 1)) * 2;
        ldsm4t(wo[tt][ks][0], wo[tt][ks][1], wo[tt][ks][2], wo[tt][ks][3], addr);
      }
    if (t == 0) {
      mbar_init(sb + OFF_BAR, 1); mbar_init(sb + OFF_BAR + 8, 1);
      asm volatile("fence.mbarrier_init.release.cluster;" ::: "memory");
    }
    __syncthreads();
    asm volatile("fence.proxy.async.shared::cta;" ::: "memory");
  }
  auto prefetch_tok = [&](int s) {
    const int i = t - 192;
    const uint32_t dst = sb + OFF_TOK + (s & 1) * TOK_BYTES + (i >> 4) * TP + (i & 15) * 16;
    const bf16* src = g_qkv + (size_t)(s * 32 + (i >> 4)) * NQKV + HD + h * 128 + (i & 15) * 8;
#pragma unroll
    for (int r = 0; r < 8; r++) {
      cp_async16(dst + 4 * r * TP, src + (size_t)4 * r * NQKV);
      cp_async16(dst + (32 + 4 * r) * TP, src + (size_t)4 * r * NQKV + HD);
    }
    cp_async16(dst + 64 * TP, src + (size_t)(8 * j) * NQKV - HD);
    cp_async16(dst + 68 * TP, src + (size_t)(8 * j + 4) * NQKV - HD);
    cp_commit();
  };
  if (warp >= 6) prefetch_tok(0);
  for (int i = t; i < 8 * 1024; i += 256) {
    int r = i >> 10, k = i & 1023;
    reinterpret_cast<bf16*>(smem + OFF_MEMT)[k * 8 + r] = mem0[i];
  }
  __syncthreads();
  uint32_t p2dst0, p2dst1;
  {
    int p = t, jj = p / 96, f = p % 96;
    p2dst0 = sb + OFF_QKVM + ((f >> 5) * 128 + 32 * jj + (f & 31)) * 16;
    p = 256 + (t & 127); jj = p / 96; f = p % 96;
    p2dst1 = sb + OFF_QKVM + ((f >> 5) * 128 + 32 * jj + (f & 31)) * 16;
  }
  const int p0idx = 256 * kq + 128 * mg + lane;
  uint32_t tpub = 0;
  const uint32_t dA = DLY_A, dB = DLY_B, dC = DLY_C;
  TS(0);
  for (int s = 0; s < NSEG; s++) {
    const int slot = s & 3, slot2 = (s + 2) & 3;
    if (s > 0) {
      const uint4* src = &g_bufC[(s - 1) & 3][p0idx];
      uint4 v[4];
      wait_until(tpub, dC);
#pragma unroll
      for (int i = 0; i < 4; i++) v[i] = ld_poll(src + 32 * i);
      int it = 0;
      while (!__all_sync(0xffffffffu, pkt_ok(v[0]) && pkt_ok(v[1]) && pkt_ok(v[2]) && pkt_ok(v[3])) && ++it < POLL_MAX) {
#pragma unroll
        for (int i = 0; i < 4; i++)
          if (!pkt_ok(v[i])) v[i] = ld_poll(src + 32 * i);
      }
#pragma unroll
      for (int i = 0; i < 4; i++) sts128(sb + OFF_MEMT + (p0idx + 32 * i) * 16, v[i]);
      TS(1);
      asm volatile("bar.sync %0, 64;" ::"r"(1 + kq) : "memory");
      TS(2);
    }
    {
      float acc[2][3][4];
#pragma unroll
      for (int a = 0; a < 2; a++)
#pragma unroll
        for (int tt = 0; tt < 3; tt++)
#pragma unroll
          for (int i = 0; i < 4; i++) acc[a][tt][i] = 0.f;
      uint4 sa[SK][3];
#pragma unroll
      for (int kp = 0; kp < 8; kp++) {
        uint32_t b0, b1, b2, b3;
        ldsm4t(b0, b1, b2, b3, sb + OFF_MEMT + ((16 * kq + 2 * kp) * 16 + lane) * 16);
#pragma unroll
        for (int u = 0; u < 2; u++) {
          int ks = 2 * (kp + 1) + u;
          if (ks >= RK && ks < 16) {
#pragma unroll
            for (int tt = 0; tt < 3; tt++)
              sa[ks - RK][tt] = *reinterpret_cast<const uint4*>(smem + OFF_WQS + (((warp * SK + (ks - RK)) * 3 + tt) * 32 + lane) * 16);
          }
        }
#pragma unroll
        for (int u = 0; u < 2; u++) {
          int ks = 2 * kp + u;
#pragma unroll
          for (int tt = 0; tt < 3; tt++) {
            if (ks < RK) mma16816(acc[u][tt], wq[ks][tt][0], wq[ks][tt][1], wq[ks][tt][2], wq[ks][tt][3], u ? b2 : b0, u ? b3 : b1);
            else mma16816(acc[u][tt], sa[ks - RK][tt].x, sa[ks - RK][tt].y, sa[ks - RK][tt].z, sa[ks - RK][tt].w, u ? b2 : b0, u ? b3 : b1);
          }
        }
      }
#pragma unroll
      for (int tt = 0; tt < 3; tt++)
        *reinterpret_cast<float4*>(smem + OFF_RED + ((kq * 6 + 3 * mg + tt) * 32 + lane) * 16) =
            make_float4(acc[0][tt][0] + acc[1][tt][0], acc[0][tt][1] + acc[1][tt][1], acc[0][tt][2] + acc[1][tt][2], acc[0][tt][3] + acc[1][tt][3]);
    }
    TS(3);
    __syncthreads();
    TS(4);
    if (warp < 6) {
      float4 r = *reinterpret_cast<const float4*>(smem + OFF_RED + ((0 * 6 + warp) * 32 + lane) * 16);
#pragma unroll
      for (int q = 1; q < 4; q++) {
        float4 x = *reinterpret_cast<const float4*>(smem + OFF_RED + ((q * 6 + warp) * 32 + lane) * 16);
        r.x += x.x; r.y += x.y; r.z += x.z; r.w += x.w;
      }
      uint32_t* dst = reinterpret_cast<uint32_t*>(&g_bufA[slot][cta][16 * warp + g]) + c;
      st_pub32(dst, desent(pack2(r.x, r.y)));
      st_pub32(dst + 32, desent(pack2(r.z, r.w)));
    }
    tpub = clk32();
    {
      const uint4* src = &g_bufA[slot][4 * h][t];
      wait_until(tpub, dA);
      uint4 v0 = ld_poll(src);
      uint4 v1 = make_uint4(0, 0, 0, 0);
      if (t < 128) v1 = ld_poll(src + 256);
      int it = 0;
      while (!__all_sync(0xffffffffu, pkt_ok(v0) && pkt_ok(v1)) && ++it < POLL_MAX) {
        if (!pkt_ok(v0)) v0 = ld_poll(src);
        if (!pkt_ok(v1)) v1 = ld_poll(src + 256);
      }
      sts128(p2dst0, v0);
      if (t < 128) sts128(p2dst1, v1);
    }
    TS(5);
    if (warp >= 6) cp_wait<0>();
    __syncthreads();
    TS(6);
    const uint32_t tok = sb + OFF_TOK + (s & 1) * TOK_BYTES;
    if (s < NSEG - 1) {
      if (warp < 4) attn8<false>(sb, tok, lane, warp, 0, nullptr);
      else if (warp >= 6) prefetch_tok(s + 1);
      else {
        const int i = t - 128;
        st_pub128(&g_bufA[slot2][cta][i], SENT);
        if (i < 32) st_pub128(&g_bufA[slot2][cta][64 + i], SENT);
        if (i < 8) st_pub128(&g_bufC[slot2][8 * cta + i], SENT);
        uint4* bb = &g_bufB[slot2][32 * j + (i >> 1)][0][0] + 2 * h + (i & 1);
#pragma unroll
        for (int col = 0; col < 8; col++) st_pub128(bb + 64 * col, SENT);
      }
      TS(7);
      __syncthreads();
      TS(8);
      {
        float acc[2][2][4];
#pragma unroll
        for (int a = 0; a < 2; a++)
#pragma unroll
          for (int tt = 0; tt < 2; tt++)
#pragma unroll
            for (int i = 0; i < 4; i++) acc[a][tt][i] = 0.f;
        uint32_t b[4][4];
#pragma unroll
        for (int kp = 0; kp < 4; kp++) ldsm4(b[kp][0], b[kp][1], b[kp][2], b[kp][3], sb + OFF_SA + (lane & 7) * TP + (32 * kp + 8 * (lane >> 3)) * 2);
#pragma unroll
        for (int kp = 0; kp < 4; kp++) {
#pragma unroll
          for (int tt = 0; tt < 2; tt++) {
            mma16816(acc[0][tt], wo[tt][2 * kp][0], wo[tt][2 * kp][1], wo[tt][2 * kp][2], wo[tt][2 * kp][3], b[kp][0], b[kp][1]);
            mma16816(acc[1][tt], wo[tt][2 * kp + 1][0], wo[tt][2 * kp + 1][1], wo[tt][2 * kp + 1][2], wo[tt][2 * kp + 1][3], b[kp][2], b[kp][3]);
          }
        }
        const int off = (g * 32 + h) * 4 + c;
#pragma unroll
        for (int tt = 0; tt < 2; tt++) {
          int r0 = 32 * j + 4 * warp + 2 * tt;
          uint32_t x0 = __float_as_uint(acc[0][tt][0] + acc[1][tt][0]), x1 = __float_as_uint(acc[0][tt][1] + acc[1][tt][1]);
          uint32_t x2 = __float_as_uint(acc[0][tt][2] + acc[1][tt][2]), x3 = __float_as_uint(acc[0][tt][3] + acc[1][tt][3]);
          x0 = x0 == SENT ? 0x7FFFFFFFu : x0; x1 = x1 == SENT ? 0x7FFFFFFFu : x1;
          x2 = x2 == SENT ? 0x7FFFFFFFu : x2; x3 = x3 == SENT ? 0x7FFFFFFFu : x3;
          st_pub64(reinterpret_cast<uint2*>(&g_bufB[slot][r0][0][0]) + off, x0, x1);
          st_pub64(reinterpret_cast<uint2*>(&g_bufB[slot][r0 + 1][0][0]) + off, x2, x3);
        }
        tpub = clk32();
      }
      TS(9);
      {
        const uint4* src = &g_bufB[slot][cta][0][0] + 64 * warp + 2 * lane;
        wait_until(tpub, dB);
        uint4 v0 = ld_poll(src), v1 = ld_poll(src + 1);
        int it = 0;
          while (!__all_sync(0xffffffffu, pkt_ok(v0) && pkt_ok(v1)) && ++it < POLL_MAX) {
            if (!pkt_ok(v0)) v0 = ld_poll(src);
          if (!pkt_ok(v1)) v1 = ld_poll(src + 1);
        }
        TS(10);
        const bool hi = lane & 16;
        float a0 = __uint_as_float(hi ? v1.x : v0.x), a1 = __uint_as_float(hi ? v1.y : v0.y);
        float a2 = __uint_as_float(hi ? v1.z : v0.z), a3 = __uint_as_float(hi ? v1.w : v0.w);
        float b0 = __uint_as_float(hi ? v0.x : v1.x), b1 = __uint_as_float(hi ? v0.y : v1.y);
        float b2 = __uint_as_float(hi ? v0.z : v1.z), b3 = __uint_as_float(hi ? v0.w : v1.w);
        a0 += __shfl_xor_sync(0xffffffffu, b0, 16); a1 += __shfl_xor_sync(0xffffffffu, b1, 16);
        a2 += __shfl_xor_sync(0xffffffffu, b2, 16); a3 += __shfl_xor_sync(0xffffffffu, b3, 16);
        const bool h8 = lane & 8;
        float k0 = h8 ? a2 : a0, k1 = h8 ? a3 : a1, s0 = h8 ? a0 : a2, s1 = h8 ? a1 : a3;
        k0 += __shfl_xor_sync(0xffffffffu, s0, 8); k1 += __shfl_xor_sync(0xffffffffu, s1, 8);
        const bool h4 = lane & 4;
        float z = h4 ? k1 : k0, zs = h4 ? k0 : k1;
        z += __shfl_xor_sync(0xffffffffu, zs, 4);
        z += __shfl_xor_sync(0xffffffffu, z, 2);
        z += __shfl_xor_sync(0xffffffffu, z, 1);
        float zo = __shfl_xor_sync(0xffffffffu, z, 4);
        if ((lane & 7) == 0) {
          uint32_t* d = reinterpret_cast<uint32_t*>(&g_bufC[slot][8 * cta + warp]) + (lane >> 3);
          st_pub32(d, desent(pack2(z, zo)));
        }
        tpub = clk32();
      }
    }
    if (warp >= 4) attn8<true>(sb, tok, lane, warp - 4, 8 * j + g, g_otok + (size_t)(s * 32 + 8 * j + g) * HD + h * 128);
    TS(11);
  }
}

__device__ void moe_part(int m, const bf16* __restrict__ wg, const bf16* __restrict__ wu, const bf16* __restrict__ wd, uint8_t* smem) {
  const int t = threadIdx.x, warp = t >> 5, lane = t & 31;
  float* xs = reinterpret_cast<float*>(smem);
  float* red = reinterpret_cast<float*>(smem + 8192);
  float* hs = reinterpret_cast<float*>(smem + 65536);
  __shared__ float bv[8];
  __shared__ int bi[8];
  __shared__ int sel[2];
  int first = -1;
  for (int pass = 0; pass < 2; pass++) {
    float best = -INFINITY; int bidx = 0x7fffffff;
    for (int i = t; i < S_LEN; i += 256) {
      float v = g_r[i];
      if (i == first) continue;
      if (v > best || (v == best && i < bidx) || bidx == 0x7fffffff) { best = v; bidx = i; }
    }
#pragma unroll
    for (int o = 16; o > 0; o >>= 1) {
      float ov = __shfl_xor_sync(0xffffffffu, best, o); int oi = __shfl_xor_sync(0xffffffffu, bidx, o);
      if (oi != 0x7fffffff && (bidx == 0x7fffffff || ov > best || (ov == best && oi < bidx))) { best = ov; bidx = oi; }
    }
    if (lane == 0) { bv[warp] = best; bi[warp] = bidx; }
    __syncthreads();
    if (t == 0) {
      float b = bv[0]; int ix = bi[0];
      for (int w = 1; w < 8; w++) if (bv[w] > b || (bv[w] == b && bi[w] < ix)) { b = bv[w]; ix = bi[w]; }
      sel[pass] = ix;
    }
    __syncthreads();
    first = sel[0];
  }
  const int s0 = sel[0], s1 = sel[1];
  for (int i = t; i < 2048; i += 256) xs[i] = __bfloat162float(g_xn[(size_t)(i < 1024 ? s0 : s1) * DM + (i & 1023)]);
  __syncthreads();
  {
    int cg = t % 112, kh = t / 112;
    float a[2][2][8];
#pragma unroll
    for (int i = 0; i < 8; i++) { a[0][0][i] = a[0][1][i] = a[1][0][i] = a[1][1][i] = 0.f; }
    if (kh < 2) {
      const bf16* pg = wg + (size_t)(kh * 512) * FF + 896 * m + cg * 8;
      const bf16* pu = wu + (size_t)(kh * 512) * FF + 896 * m + cg * 8;
#pragma unroll 8
      for (int k = 0; k < 512; k++) {
        uint4 gv = __ldg(reinterpret_cast<const uint4*>(pg + (size_t)k * FF));
        uint4 uv = __ldg(reinterpret_cast<const uint4*>(pu + (size_t)k * FF));
        float x0 = xs[kh * 512 + k], x1 = xs[1024 + kh * 512 + k];
        float gf[8] = {bflo(gv.x), bfhi(gv.x), bflo(gv.y), bfhi(gv.y), bflo(gv.z), bfhi(gv.z), bflo(gv.w), bfhi(gv.w)};
        float uf[8] = {bflo(uv.x), bfhi(uv.x), bflo(uv.y), bfhi(uv.y), bflo(uv.z), bfhi(uv.z), bflo(uv.w), bfhi(uv.w)};
#pragma unroll
        for (int i = 0; i < 8; i++) {
          a[0][0][i] += x0 * gf[i]; a[0][1][i] += x1 * gf[i];
          a[1][0][i] += x0 * uf[i]; a[1][1][i] += x1 * uf[i];
        }
      }
      if (kh == 1) {
#pragma unroll
        for (int i = 0; i < 8; i++) {
          red[(0 * 2 + 0) * 896 + cg * 8 + i] = a[0][0][i]; red[(0 * 2 + 1) * 896 + cg * 8 + i] = a[0][1][i];
          red[(1 * 2 + 0) * 896 + cg * 8 + i] = a[1][0][i]; red[(1 * 2 + 1) * 896 + cg * 8 + i] = a[1][1][i];
        }
      }
    }
    __syncthreads();
    if (kh == 0) {
#pragma unroll
      for (int i = 0; i < 8; i++) {
#pragma unroll
        for (int tk = 0; tk < 2; tk++) {
          float gq = bfr(a[0][tk][i] + red[(0 * 2 + tk) * 896 + cg * 8 + i]);
          float uq = bfr(a[1][tk][i] + red[(1 * 2 + tk) * 896 + cg * 8 + i]);
          float sg = bfr(gq / (1.0f + __expf(-gq)));
          g_h[tk][896 * m + cg * 8 + i] = __float2bfloat16_rn(sg * uq);
        }
      }
    }
    __threadfence();
    __syncthreads();
    if (t == 0) {
      atomicAdd(&g_moe_cnt, 1u);
      int it = 0;
      while (*reinterpret_cast<volatile unsigned*>(&g_moe_cnt) < 4u && ++it < (1 << 24)) {}
      __threadfence();
    }
    __syncthreads();
  }
  for (int i = t; i < 2 * FF; i += 256) {
    const volatile unsigned short* p = reinterpret_cast<const volatile unsigned short*>(&g_h[0][0]);
    hs[i] = __uint_as_float(((uint32_t)p[i]) << 16);
  }
  __syncthreads();
  {
    int cg = t & 31, ksl = t >> 5;
    float a[2][8];
#pragma unroll
    for (int i = 0; i < 8; i++) a[0][i] = a[1][i] = 0.f;
    const bf16* pd = wd + (size_t)(ksl * 448) * DM + 256 * m + cg * 8;
#pragma unroll 8
    for (int k = 0; k < 448; k++) {
      uint4 dv = __ldg(reinterpret_cast<const uint4*>(pd + (size_t)k * DM));
      float x0 = hs[ksl * 448 + k], x1 = hs[FF + ksl * 448 + k];
      float df[8] = {bflo(dv.x), bfhi(dv.x), bflo(dv.y), bfhi(dv.y), bflo(dv.z), bfhi(dv.z), bflo(dv.w), bfhi(dv.w)};
#pragma unroll
      for (int i = 0; i < 8; i++) { a[0][i] += x0 * df[i]; a[1][i] += x1 * df[i]; }
    }
#pragma unroll
    for (int i = 0; i < 8; i++) { red[(ksl * 2 + 0) * 256 + cg * 8 + i] = a[0][i]; red[(ksl * 2 + 1) * 256 + cg * 8 + i] = a[1][i]; }
    __syncthreads();
    for (int i = t; i < 512; i += 256) {
      int tk = i >> 8, col = i & 255;
      float y = 0.f;
#pragma unroll
      for (int q = 0; q < 8; q++) y += red[(q * 2 + tk) * 256 + col];
      float rr = g_r[tk == 0 ? s0 : s1];
      float sg = bfr(1.0f / (1.0f + __expf(-rr)));
      g_upd[tk][256 * m + col] = bfr(bfr(y) * sg);
    }
    if (m == 0 && t == 0) { g_sel[0] = s0; g_sel[1] = s1; }
  }
}

typedef CUresult (*EncodeFn)(CUtensorMap*, CUtensorMapDataType, cuuint32_t, void*, const cuuint64_t*, const cuuint64_t*,
                             const cuuint32_t*, const cuuint32_t*, CUtensorMapInterleave, CUtensorMapSwizzle,
                             CUtensorMapL2promotion, CUtensorMapFloatOOBfill);

static void make_map(EncodeFn enc, CUtensorMap* m, const void* ptr, uint64_t inner, uint64_t outer, uint32_t bi, uint32_t bo) {
  cuuint64_t dims[2] = {inner, outer};
  cuuint64_t strides[1] = {inner * 2};
  cuuint32_t box[2] = {bi, bo};
  cuuint32_t es[2] = {1, 1};
  enc(m, CU_TENSOR_MAP_DATA_TYPE_BFLOAT16, 2, const_cast<void*>(ptr), dims, strides, box, es, CU_TENSOR_MAP_INTERLEAVE_NONE,
      CU_TENSOR_MAP_SWIZZLE_128B, CU_TENSOR_MAP_L2_PROMOTION_L2_256B, CU_TENSOR_MAP_FLOAT_OOB_FILL_NONE);
}

extern "C" void kernel_launch(void* const* d_in, const int* in_sizes, int n_in, void* d_out, int out_size) {
  const bf16* x = (const bf16*)d_in[0];
  const bf16* mem0 = (const bf16*)d_in[1];
  const bf16* Wq = (const bf16*)d_in[2];
  const bf16* Wk = (const bf16*)d_in[3];
  const bf16* Wv = (const bf16*)d_in[4];
  const bf16* Wo = (const bf16*)d_in[5];
  const bf16* w_r = (const bf16*)d_in[8];
  const bf16* wg = (const bf16*)d_in[9];
  const bf16* wu = (const bf16*)d_in[10];
  const bf16* wd = (const bf16*)d_in[11];
  bf16* out = (bf16*)d_out;

  static EncodeFn enc = nullptr;
  static void *p_xn, *p_qkv, *p_otok;
  if (!enc) {
    cudaDriverEntryPointQueryResult qr;
    void* fn = nullptr;
    cudaGetDriverEntryPoint("cuTensorMapEncodeTiled", &fn, cudaEnableDefault, &qr);
    enc = (EncodeFn)fn;
    cudaGetSymbolAddress(&p_xn, g_xn);
    cudaGetSymbolAddress(&p_qkv, g_qkv);
    cudaGetSymbolAddress(&p_otok, g_otok);
    cudaFuncSetAttribute(gemm_kernel<256, 4, 0>, cudaFuncAttributeMaxDynamicSharedMemorySize, GemmSmem<256, 4>::TOTAL);
    cudaFuncSetAttribute(gemm_kernel<128, 6, 1>, cudaFuncAttributeMaxDynamicSharedMemorySize, GemmSmem<128, 6>::TOTAL);
    cudaFuncSetAttribute(chain_kernel, cudaFuncAttributeMaxDynamicSharedMemorySize, CH_SMEM);
  }
  CUtensorMap mA, mQ, mK, mV, mO, mWo;
  make_map(enc, &mA, p_xn, DM, S_LEN, 64, 128);
  make_map(enc, &mQ, Wq, HD, DM, 64, 64);
  make_map(enc, &mK, Wk, HD, DM, 64, 64);
  make_map(enc, &mV, Wv, HD, DM, 64, 64);
  make_map(enc, &mO, p_otok, HD, S_LEN, 64, 128);
  make_map(enc, &mWo, Wo, DM, HD, 64, 64);

  cudaStream_t st = cudaStreamPerThread;
  ln_kernel<<<256, 256, 0, st>>>(x, w_r);
  gemm_kernel<256, 4, 0><<<132, 288, GemmSmem<256, 4>::TOTAL, st>>>(mA, mQ, mK, mV, 16, 16, 16 * 48, nullptr, (bf16*)p_qkv);
  chain_kernel<<<132, 256, CH_SMEM, st>>>(mem0, Wq, Wk, Wv, Wo, wg, wu, wd);
  gemm_kernel<128, 6, 1><<<128, 288, GemmSmem<128, 6>::TOTAL, st>>>(mO, mWo, mWo, mWo, 64, 16, 16 * 8, x, out);
}
```

```cpp
#include <cuda_runtime.h>
#include <cuda_bf16.h>
#include <cuda.h>
#include <stdint.h>

typedef __nv_bfloat16 bf16;

#define S_LEN 2048
#define DM 1024
#define NH 32
#define DH 128
#define NSEG 64
#define SEGL 32
#define HD 4096
#define NQKV 12288
#define FF 3584
#define SENT 0xFFFFFFFFu

__device__ __align__(1024) bf16 g_xn[S_LEN * DM];
__device__ __align__(1024) bf16 g_qkv[(size_t)S_LEN * NQKV];
__device__ __align__(1024) bf16 g_otok[(size_t)S_LEN * HD];
__device__ float g_r[S_LEN];
__device__ __align__(128) uint4 g_bufA[4][128][96];
__device__ __align__(128) uint4 g_bufB[4][128][16][32];
__device__ __align__(128) uint4 g_bufC[4][1024];
__device__ __align__(128) bf16 g_h[2][FF];
__device__ float g_upd[2][DM];
__device__ int g_sel[2];
__device__ unsigned g_moe_cnt;
#define DLY_A 300u
#define DLY_B 800u
#define DLY_C 700u
#define TS(i)

__device__ __forceinline__ float bfr(float x) { return __bfloat162float(__float2bfloat16_rn(x)); }
__device__ __forceinline__ uint32_t pack2(float lo, float hi) {
  __nv_bfloat162 v = __floats2bfloat162_rn(lo, hi);
  return *reinterpret_cast<uint32_t*>(&v);
}
__device__ __forceinline__ float bflo(uint32_t v) { return __uint_as_float(v << 16); }
__device__ __forceinline__ float bfhi(uint32_t v) { return __uint_as_float(v & 0xFFFF0000u); }
__device__ __forceinline__ uint32_t smem_u32(const void* p) { return (uint32_t)__cvta_generic_to_shared(p); }

__device__ __forceinline__ uint4 ld_poll(const uint4* p) {
  uint4 v;
  asm volatile("ld.relaxed.gpu.global.v4.u32 {%0,%1,%2,%3},[%4];" : "=r"(v.x), "=r"(v.y), "=r"(v.z), "=r"(v.w) : "l"(p) : "memory");
  return v;
}
__device__ __forceinline__ void st_pub32(void* p, uint32_t v) {
  asm volatile("st.relaxed.gpu.global.u32 [%0],%1;" ::"l"(p), "r"(v) : "memory");
}
__device__ __forceinline__ void st_pub64(void* p, uint32_t a, uint32_t b) {
  asm volatile("st.relaxed.gpu.global.v2.u32 [%0],{%1,%2};" ::"l"(p), "r"(a), "r"(b) : "memory");
}
__device__ __forceinline__ bool pkt_ok(const uint4& v) { return v.x != SENT && v.y != SENT && v.z != SENT && v.w != SENT; }
__device__ __forceinline__ uint32_t desent(uint32_t v) { return v == SENT ? 0x7FFF7FFFu : v; }

__device__ __forceinline__ void ldsm4(uint32_t& r0, uint32_t& r1, uint32_t& r2, uint32_t& r3, uint32_t addr) {
  asm volatile("ldmatrix.sync.aligned.m8n8.x4.shared.b16 {%0,%1,%2,%3},[%4];" : "=r"(r0), "=r"(r1), "=r"(r2), "=r"(r3) : "r"(addr) : "memory");
}
__device__ __forceinline__ void ldsm4t(uint32_t& r0, uint32_t& r1, uint32_t& r2, uint32_t& r3, uint32_t addr) {
  asm volatile("ldmatrix.sync.aligned.m8n8.x4.trans.shared.b16 {%0,%1,%2,%3},[%4];" : "=r"(r0), "=r"(r1), "=r"(r2), "=r"(r3) : "r"(addr) : "memory");
}
__device__ __forceinline__ void mma16816(float (&d)[4], uint32_t a0, uint32_t a1, uint32_t a2, uint32_t a3, uint32_t b0, uint32_t b1) {
  asm volatile("mma.sync.aligned.m16n8k16.row.col.f32.bf16.bf16.f32 {%0,%1,%2,%3},{%4,%5,%6,%7},{%8,%9},{%0,%1,%2,%3};"
               : "+f"(d[0]), "+f"(d[1]), "+f"(d[2]), "+f"(d[3])
               : "r"(a0), "r"(a1), "r"(a2), "r"(a3), "r"(b0), "r"(b1));
}
__device__ __forceinline__ void cp_async16(uint32_t dst, const void* src) {
  asm volatile("cp.async.cg.shared.global [%0],[%1],16;" ::"r"(dst), "l"(src) : "memory");
}
__device__ __forceinline__ void cp_commit() { asm volatile("cp.async.commit_group;" ::: "memory"); }
template <int N>
__device__ __forceinline__ void cp_wait() { asm volatile("cp.async.wait_group %0;" ::"n"(N) : "memory"); }

__device__ __forceinline__ void mbar_init(uint32_t bar, uint32_t cnt) { asm volatile("mbarrier.init.shared::cta.b64 [%0],%1;" ::"r"(bar), "r"(cnt) : "memory"); }
__device__ __forceinline__ void mbar_expect_tx(uint32_t bar, uint32_t bytes) {
  asm volatile("mbarrier.arrive.expect_tx.shared::cta.b64 _,[%0],%1;" ::"r"(bar), "r"(bytes) : "memory");
}
__device__ __forceinline__ void mbar_arrive(uint32_t bar) { asm volatile("mbarrier.arrive.shared::cta.b64 _,[%0];" ::"r"(bar) : "memory"); }
__device__ __forceinline__ void mbar_wait(uint32_t bar, uint32_t parity) {
  asm volatile(
      "{\n.reg .pred p;\n"
      "WAIT_LOOP:\n"
      "mbarrier.try_wait.parity.shared::cta.b64 p,[%0],%1;\n"
      "@p bra WAIT_DONE;\n"
      "bra WAIT_LOOP;\n"
      "WAIT_DONE:\n}\n" ::"r"(bar), "r"(parity) : "memory");
}
__device__ __forceinline__ void tma_load2d(uint32_t dst, const CUtensorMap* tm, uint32_t bar, int c0, int c1) {
  asm volatile("cp.async.bulk.tensor.2d.shared::cluster.global.mbarrier::complete_tx::bytes [%0],[%1,{%3,%4}],[%2];"
               ::"r"(dst), "l"(tm), "r"(bar), "r"(c0), "r"(c1) : "memory");
}
__device__ __forceinline__ void wg_fence() { asm volatile("wgmma.fence.sync.aligned;" ::: "memory"); }
__device__ __forceinline__ void wg_commit() { asm volatile("wgmma.commit_group.sync.aligned;" ::: "memory"); }
template <int N>
__device__ __forceinline__ void wg_wait() { asm volatile("wgmma.wait_group.sync.aligned %0;" ::"n"(N) : "memory"); }
__device__ __forceinline__ uint64_t make_desc(uint32_t addr, uint32_t lbo, uint32_t sbo) {
  return (uint64_t)((addr & 0x3FFFF) >> 4) | ((uint64_t)(lbo >> 4) << 16) | ((uint64_t)(sbo >> 4) << 32) | (1ull << 62);
}

__device__ __forceinline__ void wgmma_m64n256k16(float (&d)[128], uint64_t da, uint64_t db, int scaleD) {
  asm volatile(
    "{\n.reg .pred p;\nsetp.ne.b32 p, %130, 0;\n"
    "wgmma.mma_async.sync.aligned.m64n256k16.f32.bf16.bf16 "
    "{%0, %1, %2, %3, %4, %5, %6, %7, %8, %9, %10, %11, %12, %13, %14, %15, %16, %17, %18, %19, %20, %21, %22, %23, %24, %25, %26, %27, %28, %29, %30, %31, %32, %33, %34, %35, %36, %37, %38, %39, %40, %41, %42, %43, %44, %45, %46, %47, %48, %49, %50, %51, %52, %53, %54, %55, %56, %57, %58, %59, %60, %61, %62, %63, %64, %65, %66, %67, %68, %69, %70, %71, %72, %73, %74, %75, %76, %77, %78, %79, %80, %81, %82, %83, %84, %85, %86, %87, %88, %89, %90, %91, %92, %93, %94, %95, %96, %97, %98, %99, %100, %101, %102, %103, %104, %105, %106, %107, %108, %109, %110, %111, %112, %113, %114, %115, %116, %117, %118, %119, %120, %121, %122, %123, %124, %125, %126, %127}, %128, %129, p, 1, 1, 0, 1;\n}\n"
    : "+f"(d[0]), "+f"(d[1]), "+f"(d[2]), "+f"(d[3]), "+f"(d[4]), "+f"(d[5]), "+f"(d[6]), "+f"(d[7]), "+f"(d[8]), "+f"(d[9]), "+f"(d[10]), "+f"(d[11]), "+f"(d[12]), "+f"(d[13]), "+f"(d[14]), "+f"(d[15]), "+f"(d[16]), "+f"(d[17]), "+f"(d[18]), "+f"(d[19]), "+f"(d[20]), "+f"(d[21]), "+f"(d[22]), "+f"(d[23]), "+f"(d[24]), "+f"(d[25]), "+f"(d[26]), "+f"(d[27]), "+f"(d[28]), "+f"(d[29]), "+f"(d[30]), "+f"(d[31]), "+f"(d[32]), "+f"(d[33]), "+f"(d[34]), "+f"(d[35]), "+f"(d[36]), "+f"(d[37]), "+f"(d[38]), "+f"(d[39]), "+f"(d[40]), "+f"(d[41]), "+f"(d[42]), "+f"(d[43]), "+f"(d[44]), "+f"(d[45]), "+f"(d[46]), "+f"(d[47]), "+f"(d[48]), "+f"(d[49]), "+f"(d[50]), "+f"(d[51]), "+f"(d[52]), "+f"(d[53]), "+f"(d[54]), "+f"(d[55]), "+f"(d[56]), "+f"(d[57]), "+f"(d[58]), "+f"(d[59]), "+f"(d[60]), "+f"(d[61]), "+f"(d[62]), "+f"(d[63]), "+f"(d[64]), "+f"(d[65]), "+f"(d[66]), "+f"(d[67]), "+f"(d[68]), "+f"(d[69]), "+f"(d[70]), "+f"(d[71]), "+f"(d[72]), "+f"(d[73]), "+f"(d[74]), "+f"(d[75]), "+f"(d[76]), "+f"(d[77]), "+f"(d[78]), "+f"(d[79]), "+f"(d[80]), "+f"(d[81]), "+f"(d[82]), "+f"(d[83]), "+f"(d[84]), "+f"(d[85]), "+f"(d[86]), "+f"(d[87]), "+f"(d[88]), "+f"(d[89]), "+f"(d[90]), "+f"(d[91]), "+f"(d[92]), "+f"(d[93]), "+f"(d[94]), "+f"(d[95]), "+f"(d[96]), "+f"(d[97]), "+f"(d[98]), "+f"(d[99]), "+f"(d[100]), "+f"(d[101]), "+f"(d[102]), "+f"(d[103]), "+f"(d[104]), "+f"(d[105]), "+f"(d[106]), "+f"(d[107]), "+f"(d[108]), "+f"(d[109]), "+f"(d[110]), "+f"(d[111]), "+f"(d[112]), "+f"(d[113]), "+f"(d[114]), "+f"(d[115]), "+f"(d[116]), "+f"(d[117]), "+f"(d[118]), "+f"(d[119]), "+f"(d[120]), "+f"(d[121]), "+f"(d[122]), "+f"(d[123]), "+f"(d[124]), "+f"(d[125]), "+f"(d[126]), "+f"(d[127])
    : "l"(da), "l"(db), "r"(scaleD));
}

__device__ __forceinline__ void wgmma_m64n128k16(float (&d)[64], uint64_t da, uint64_t db, int scaleD) {
  asm volatile(
    "{\n.reg .pred p;\nsetp.ne.b32 p, %66, 0;\n"
    "wgmma.mma_async.sync.aligned.m64n128k16.f32.bf16.bf16 "
    "{%0, %1, %2, %3, %4, %5, %6, %7, %8, %9, %10, %11, %12, %13, %14, %15, %16, %17, %18, %19, %20, %21, %22, %23, %24, %25, %26, %27, %28, %29, %30, %31, %32, %33, %34, %35, %36, %37, %38, %39, %40, %41, %42, %43, %44, %45, %46, %47, %48, %49, %50, %51, %52, %53, %54, %55, %56, %57, %58, %59, %60, %61, %62, %63}, %64, %65, p, 1, 1, 0, 1;\n}\n"
    : "+f"(d[0]), "+f"(d[1]), "+f"(d[2]), "+f"(d[3]), "+f"(d[4]), "+f"(d[5]), "+f"(d[6]), "+f"(d[7]), "+f"(d[8]), "+f"(d[9]), "+f"(d[10]), "+f"(d[11]), "+f"(d[12]), "+f"(d[13]), "+f"(d[14]), "+f"(d[15]), "+f"(d[16]), "+f"(d[17]), "+f"(d[18]), "+f"(d[19]), "+f"(d[20]), "+f"(d[21]), "+f"(d[22]), "+f"(d[23]), "+f"(d[24]), "+f"(d[25]), "+f"(d[26]), "+f"(d[27]), "+f"(d[28]), "+f"(d[29]), "+f"(d[30]), "+f"(d[31]), "+f"(d[32]), "+f"(d[33]), "+f"(d[34]), "+f"(d[35]), "+f"(d[36]), "+f"(d[37]), "+f"(d[38]), "+f"(d[39]), "+f"(d[40]), "+f"(d[41]), "+f"(d[42]), "+f"(d[43]), "+f"(d[44]), "+f"(d[45]), "+f"(d[46]), "+f"(d[47]), "+f"(d[48]), "+f"(d[49]), "+f"(d[50]), "+f"(d[51]), "+f"(d[52]), "+f"(d[53]), "+f"(d[54]), "+f"(d[55]), "+f"(d[56]), "+f"(d[57]), "+f"(d[58]), "+f"(d[59]), "+f"(d[60]), "+f"(d[61]), "+f"(d[62]), "+f"(d[63])
    : "l"(da), "l"(db), "r"(scaleD));
}

template <int BN> struct WG;
template <> struct WG<256> { static __device__ __forceinline__ void mma(float (&d)[128], uint64_t a, uint64_t b, int s) { wgmma_m64n256k16(d, a, b, s); } };
template <> struct WG<128> { static __device__ __forceinline__ void mma(float (&d)[64], uint64_t a, uint64_t b, int s) { wgmma_m64n128k16(d, a, b, s); } };

__global__ void __launch_bounds__(256) ln_kernel(const bf16* __restrict__ x, const bf16* __restrict__ w_r) {
  int warp = threadIdx.x >> 5, lane = threadIdx.x & 31;
  int row = blockIdx.x * 8 + warp;
  const uint4* xp = reinterpret_cast<const uint4*>(x + (size_t)row * DM);
  uint4 v[4];
#pragma unroll
  for (int i = 0; i < 4; i++) v[i] = xp[lane + 32 * i];
  float f[32];
#pragma unroll
  for (int i = 0; i < 4; i++) {
    f[8 * i + 0] = bflo(v[i].x); f[8 * i + 1] = bfhi(v[i].x);
    f[8 * i + 2] = bflo(v[i].y); f[8 * i + 3] = bfhi(v[i].y);
    f[8 * i + 4] = bflo(v[i].z); f[8 * i + 5] = bfhi(v[i].z);
    f[8 * i + 6] = bflo(v[i].w); f[8 * i + 7] = bfhi(v[i].w);
  }
  float s = 0.f;
#pragma unroll
  for (int i = 0; i < 32; i++) s += f[i];
#pragma unroll
  for (int o = 16; o > 0; o >>= 1) s += __shfl_xor_sync(0xffffffffu, s, o);
  float mean = s * (1.0f / DM);
  float q = 0.f;
#pragma unroll
  for (int i = 0; i < 32; i++) { float d = f[i] - mean; q += d * d; }
#pragma unroll
  for (int o = 16; o > 0; o >>= 1) q += __shfl_xor_sync(0xffffffffu, q, o);
  float var = bfr(q * (1.0f / DM));
  float mb = bfr(mean);
  float den = bfr(sqrtf(bfr(var + 1e-5f)));
  const uint4* wp = reinterpret_cast<const uint4*>(w_r);
  uint4* op = reinterpret_cast<uint4*>(g_xn + (size_t)row * DM);
  float r = 0.f;
#pragma unroll
  for (int i = 0; i < 4; i++) {
    uint4 w = wp[lane + 32 * i];
    float y[8];
#pragma unroll
    for (int k = 0; k < 8; k++) y[k] = bfr(bfr(f[8 * i + k] - mb) / den);
    r += y[0] * bflo(w.x) + y[1] * bfhi(w.x) + y[2] * bflo(w.y) + y[3] * bfhi(w.y) + y[4] * bflo(w.z) + y[5] * bfhi(w.z) +
         y[6] * bflo(w.w) + y[7] * bfhi(w.w);
    op[lane + 32 * i] = make_uint4(pack2(y[0], y[1]), pack2(y[2], y[3]), pack2(y[4], y[5]), pack2(y[6], y[7]));
  }
#pragma unroll
  for (int o = 16; o > 0; o >>= 1) r += __shfl_xor_sync(0xffffffffu, r, o);
  if (lane == 0) g_r[row] = bfr(r);
  int gt = blockIdx.x * 256 + threadIdx.x;
  const uint4 sv = make_uint4(SENT, SENT, SENT, SENT);
  uint4* a = &g_bufA[0][0][0];
  for (int i = gt; i < 2 * 128 * 96; i += 65536) a[i] = sv;
  uint4* b = &g_bufB[0][0][0][0];
  for (int i = gt; i < 2 * 128 * 32 * 16; i += 65536) b[i] = sv;
  uint4* c = &g_bufC[0][0];
  for (int i = gt; i < 2 * 1024; i += 65536) c[i] = sv;
  if (gt == 0) g_moe_cnt = 0;
}

template <int BN, int STAGES>
struct GemmSmem {
  static constexpr int A_BYTES = 128 * 64 * 2;
  static constexpr int B_BYTES = 64 * BN * 2;
  static constexpr int STAGE_BYTES = A_BYTES + B_BYTES;
  static constexpr int TOTAL = STAGES * STAGE_BYTES + 1024 + 256;
};

__device__ __forceinline__ void quad_transpose(uint32_t (&v)[4], int c) {
  {
    uint32_t s0 = (c & 1) ? v[0] : v[1];
    uint32_t s1 = (c & 1) ? v[2] : v[3];
    uint32_t r0 = __shfl_xor_sync(0xffffffffu, s0, 1);
    uint32_t r1 = __shfl_xor_sync(0xffffffffu, s1, 1);
    if (c & 1) { v[0] = r0; v[2] = r1; } else { v[1] = r0; v[3] = r1; }
  }
  {
    uint32_t s0 = (c & 2) ? v[0] : v[2];
    uint32_t s1 = (c & 2) ? v[1] : v[3];
    uint32_t r0 = __shfl_xor_sync(0xffffffffu, s0, 2);
    uint32_t r1 = __shfl_xor_sync(0xffffffffu, s1, 2);
    if (c & 2) { v[0] = r0; v[1] = r1; } else { v[2] = r0; v[3] = r1; }
  }
}

__device__ __forceinline__ uint32_t add3(uint32_t a, uint32_t x, uint32_t b) {
  float lo = bfr(bflo(x) + bflo(a)) + bflo(b);
  float hi = bfr(bfhi(x) + bfhi(a)) + bfhi(b);
  return pack2(lo, hi);
}

template <int BN, int STAGES, int EPI>
__global__ void __launch_bounds__(288, 1)
gemm_kernel(const __grid_constant__ CUtensorMap tmA, const __grid_constant__ CUtensorMap tmB0,
            const __grid_constant__ CUtensorMap tmB1, const __grid_constant__ CUtensorMap tmB2,
            int kblocks, int tiles_m, int tiles_total, const bf16* __restrict__ xin, bf16* __restrict__ outp) {
  using SM = GemmSmem<BN, STAGES>;
  extern __shared__ uint8_t smem_raw[];
  uint32_t base = (smem_u32(smem_raw) + 1023) & ~1023u;
  uint32_t bars = base + STAGES * SM::STAGE_BYTES;
  int warp = threadIdx.x >> 5, lane = threadIdx.x & 31;
  if (threadIdx.x == 0) {
    for (int i = 0; i < STAGES; i++) { mbar_init(bars + 8 * i, 1); mbar_init(bars + 8 * (STAGES + i), 8); }
    asm volatile("fence.mbarrier_init.release.cluster;" ::: "memory");
  }
  __syncthreads();
  if (warp == 8) {
    if (lane == 0) {
      int it = 0;
      for (int t = blockIdx.x; t < tiles_total; t += gridDim.x) {
        int tm = t % tiles_m, tn = t / tiles_m;
        int n0 = tn * BN;
        const CUtensorMap* tb = &tmB0;
        if (EPI == 0) { int wsel = n0 >> 12; tb = wsel == 0 ? &tmB0 : (wsel == 1 ? &tmB1 : &tmB2); n0 &= 4095; }
        for (int kb = 0; kb < kblocks; kb++, it++) {
          int st = it % STAGES; uint32_t ph = (it / STAGES) & 1;
          mbar_wait(bars + 8 * (STAGES + st), ph ^ 1);
          uint32_t sa = base + st * SM::STAGE_BYTES, sb = sa + SM::A_BYTES;
          mbar_expect_tx(bars + 8 * st, SM::STAGE_BYTES);
          tma_load2d(sa, &tmA, bars + 8 * st, kb * 64, tm * 128);
#pragma unroll
          for (int i = 0; i < BN / 64; i++) tma_load2d(sb + i * 8192, tb, bars + 8 * st, n0 + i * 64, kb * 64);
        }
      }
    }
  } else {
    int wg = warp >> 2;
    int g = lane >> 2, c = lane & 3;
    int it = 0;
    float acc[BN / 2];
    for (int t = blockIdx.x; t < tiles_total; t += gridDim.x) {
      int tm = t % tiles_m, tn = t / tiles_m;
      for (int kb = 0; kb < kblocks; kb++, it++) {
        int st = it % STAGES; uint32_t ph = (it / STAGES) & 1;
        mbar_wait(bars + 8 * st, ph);
        uint32_t sa = base + st * SM::STAGE_BYTES + wg * 8192, sb = base + st * SM::STAGE_BYTES + SM::A_BYTES;
        wg_fence();
#pragma unroll
        for (int kk = 0; kk < 4; kk++) {
          uint64_t da = make_desc(sa + kk * 32, 16, 1024);
          uint64_t db = make_desc(sb + kk * 2048, 8192, 1024);
          WG<BN>::mma(acc, da, db, (kb | kk) != 0);
        }
        wg_commit();
        if (kb > 0) {
          wg_wait<1>();
          int pst = (it - 1) % STAGES;
          if (lane == 0) mbar_arrive(bars + 8 * (STAGES + pst));
        }
      }
      wg_wait<0>();
      { int pst = (it - 1) % STAGES; if (lane == 0) mbar_arrive(bars + 8 * (STAGES + pst)); }
      int row0 = tm * 128 + wg * 64 + (warp & 3) * 16 + g;
      int sel0 = -1, sel1 = -1;
      if (EPI == 1) { sel0 = g_sel[0]; sel1 = g_sel[1]; }
#pragma unroll
      for (int half = 0; half < 2; half++) {
        int row = row0 + half * 8;
#pragma unroll
        for (int q = 0; q < BN / 32; q++) {
          uint32_t v[4];
#pragma unroll
          for (int tt = 0; tt < 4; tt++) v[tt] = pack2(acc[(q * 4 + tt) * 4 + half * 2], acc[(q * 4 + tt) * 4 + half * 2 + 1]);
          quad_transpose(v, c);
          int col = tn * BN + q * 32 + c * 8;
          if (EPI == 0) {
            __stcs(reinterpret_cast<uint4*>(outp + (size_t)row * NQKV + col), make_uint4(v[0], v[1], v[2], v[3]));
          } else {
            uint4 xv = *reinterpret_cast<const uint4*>(xin + (size_t)row * DM + col);
            uint4 bv = *reinterpret_cast<const uint4*>(g_xn + (size_t)row * DM + col);
            if (row == sel0 || row == sel1) {
              const float* u = &g_upd[row == sel0 ? 0 : 1][col];
              bv.x = pack2(bflo(bv.x) + u[0], bfhi(bv.x) + u[1]);
              bv.y = pack2(bflo(bv.y) + u[2], bfhi(bv.y) + u[3]);
              bv.z = pack2(bflo(bv.z) + u[4], bfhi(bv.z) + u[5]);
              bv.w = pack2(bflo(bv.w) + u[6], bfhi(bv.w) + u[7]);
            }
            uint4 o = make_uint4(add3(v[0], xv.x, bv.x), add3(v[1], xv.y, bv.y), add3(v[2], xv.z, bv.z), add3(v[3], xv.w, bv.w));
            *reinterpret_cast<uint4*>(outp + (size_t)row * DM + col) = o;
          }
        }
      }
    }
  }
}

#define RK 10
#define SK (16 - RK)
#define TP 272
#define OFF_WQS 0
#define OFF_MEMT (OFF_WQS + 8 * SK * 3 * 512)
#define OFF_RED (OFF_MEMT + 16384)
#define OFF_QKVM (OFF_RED + 12288)
#define OFF_TOK (OFF_QKVM + 6144)
#define TOK_BYTES (72 * TP)
#define OFF_SA (OFF_TOK + 2 * TOK_BYTES)
#define OFF_BAR (OFF_SA + 8 * TP)
#define CH_END (OFF_BAR + 64)
#define CH_STG2 (131072)
#define CH_SMEM (196608 + 1024)
static_assert(CH_END <= CH_SMEM, "smem");

__device__ void moe_part(int m, const bf16* __restrict__ wg, const bf16* __restrict__ wu, const bf16* __restrict__ wd, uint8_t* smem);

__device__ __forceinline__ void bulk_copy(uint32_t dst, const void* src, uint32_t bytes, uint32_t bar) {
  asm volatile("cp.async.bulk.shared::cluster.global.mbarrier::complete_tx::bytes [%0],[%1],%2,[%3];"
               ::"r"(dst), "l"(src), "r"(bytes), "r"(bar) : "memory");
}
__device__ __forceinline__ void st_pub128(void* p, uint32_t v) {
  asm volatile("st.relaxed.gpu.global.v4.u32 [%0],{%1,%1,%1,%1};" ::"l"(p), "r"(v) : "memory");
}
__device__ __forceinline__ void sts128(uint32_t addr, const uint4& v) {
  asm volatile("st.shared.v4.u32 [%0],{%1,%2,%3,%4};" ::"r"(addr), "r"(v.x), "r"(v.y), "r"(v.z), "r"(v.w) : "memory");
}

#define POLL_MAX (1 << 22)
__device__ __forceinline__ uint32_t clk32() { uint32_t c; asm volatile("mov.u32 %0,%%clock;" : "=r"(c)); return c; }
__device__ __forceinline__ void wait_until(uint32_t t0, uint32_t d) { while (clk32() - t0 < d) {} }
#define DLY_DEC 48u

__device__ __forceinline__ float ex2f(float x) { float y; asm("ex2.approx.ftz.f32 %0,%1;" : "=f"(y) : "f"(x)); return y; }
__device__ __forceinline__ float rcpf(float x) { float y; asm("rcp.approx.ftz.f32 %0,%1;" : "=f"(y) : "f"(x)); return y; }
template <bool TOK>
__device__ __forceinline__ void attn8(uint32_t sb, uint32_t tok, int lane, int wq4, int tr, bf16* otok_row) {
  const int g = lane >> 2, c = lane & 3;
  float sc[5][4];
#pragma unroll
  for (int n = 0; n < 5; n++)
#pragma unroll
    for (int i = 0; i < 4; i++) sc[n][i] = 0.f;
  const uint32_t tokrow = tok + (lane & 7) * TP + (lane >> 3) * 16;
  const uint32_t qaddr = TOK ? (tok + (64 + (lane & 7)) * TP + (lane >> 4) * 16) : (sb + OFF_QKVM + ((lane & 7) + 8 * (lane >> 4)) * 16);
#pragma unroll
  for (int kp = 0; kp < 4; kp++) {
    uint32_t q0[4], q1[4], km[4], kt[4][4];
    if (TOK) {
      ldsm4(q0[0], q0[1], q0[2], q0[3], qaddr + 64 * kp);
      ldsm4(q1[0], q1[1], q1[2], q1[3], qaddr + 64 * kp + 32);
    } else {
      ldsm4t(q0[0], q0[1], q0[2], q0[3], qaddr + 512 * kp);
      ldsm4t(q1[0], q1[1], q1[2], q1[3], qaddr + 512 * kp + 256);
    }
    ldsm4t(km[0], km[1], km[2], km[3], sb + OFF_QKVM + (128 + 32 * kp + lane) * 16);
#pragma unroll
    for (int n = 0; n < 4; n++) ldsm4(kt[n][0], kt[n][1], kt[n][2], kt[n][3], tokrow + 8 * n * TP + 64 * kp);
    mma16816(sc[0], q0[0], q0[1], q0[2], q0[3], km[0], km[1]);
#pragma unroll
    for (int n = 0; n < 4; n++) mma16816(sc[n + 1], q0[0], q0[1], q0[2], q0[3], kt[n][0], kt[n][1]);
    mma16816(sc[0], q1[0], q1[1], q1[2], q1[3], km[2], km[3]);
#pragma unroll
    for (int n = 0; n < 4; n++) mma16816(sc[n + 1], q1[0], q1[1], q1[2], q1[3], kt[n][2], kt[n][3]);
  }
  uint32_t vma[4], vmb[4], vt[4][4];
  ldsm4(vma[0], vma[1], vma[2], vma[3], sb + OFF_QKVM + (256 + 32 * wq4 + lane) * 16);
  ldsm4(vmb[0], vmb[1], vmb[2], vmb[3], sb + OFF_QKVM + (256 + 32 * wq4 + (lane ^ 8)) * 16);
#pragma unroll
  for (int n = 0; n < 4; n++) ldsm4t(vt[n][0], vt[n][1], vt[n][2], vt[n][3], tok + (32 + lane) * TP + (32 * wq4 + 8 * n) * 2);
  const float scale = 0.08838834764831845f;
  float m0 = -3.0e38f;
#pragma unroll
  for (int n = 0; n < 5; n++) {
    uint32_t p1 = pack2(sc[n][0], sc[n][1]);
    uint32_t p2 = pack2(bflo(p1) * scale, bfhi(p1) * scale);
    sc[n][0] = bflo(p2);
    sc[n][1] = bfhi(p2);
    if (TOK && n > 0) {
      int kt = 8 * (n - 1) + 2 * c;
      if (kt > tr) sc[n][0] = -1.0e9f;
      if (kt + 1 > tr) sc[n][1] = -1.0e9f;
    }
    m0 = fmaxf(m0, fmaxf(sc[n][0], sc[n][1]));
  }
  m0 = fmaxf(m0, __shfl_xor_sync(0xffffffffu, m0, 1));
  m0 = fmaxf(m0, __shfl_xor_sync(0xffffffffu, m0, 2));
  const float l2e = 1.4426950408889634f;
  float s0 = 0.f;
#pragma unroll
  for (int n = 0; n < 5; n++) {
    sc[n][0] = ex2f((sc[n][0] - m0) * l2e);
    sc[n][1] = ex2f((sc[n][1] - m0) * l2e);
    s0 += sc[n][0] + sc[n][1];
  }
  s0 += __shfl_xor_sync(0xffffffffu, s0, 1);
  s0 += __shfl_xor_sync(0xffffffffu, s0, 2);
  const float i0 = rcpf(s0);
  uint32_t pp[5];
#pragma unroll
  for (int n = 0; n < 5; n++) pp[n] = pack2(sc[n][0] * i0, sc[n][1] * i0);
  float o[4][4];
#pragma unroll
  for (int n = 0; n < 4; n++) {
#pragma unroll
    for (int i = 0; i < 4; i++) o[n][i] = 0.f;
    mma16816(o[n], pp[1], pp[1], pp[2], pp[2], vt[n][0], vt[n][1]);
  }
#pragma unroll
  for (int n = 0; n < 4; n++) mma16816(o[n], pp[3], pp[3], pp[4], pp[4], vt[n][2], vt[n][3]);
  mma16816(o[0], pp[0], 0u, 0u, 0u, vma[0], vma[1]);
  mma16816(o[1], pp[0], 0u, 0u, 0u, vmb[0], vmb[1]);
  mma16816(o[2], pp[0], 0u, 0u, 0u, vma[2], vma[3]);
  mma16816(o[3], pp[0], 0u, 0u, 0u, vmb[2], vmb[3]);
#pragma unroll
  for (int n = 0; n < 4; n++) {
    const int e = 32 * wq4 + 8 * n + 2 * c;
    if (TOK) *reinterpret_cast<uint32_t*>(otok_row + e) = pack2(o[n][0], o[n][1]);
    else asm volatile("st.shared.u32 [%0],%1;" ::"r"(sb + OFF_SA + g * TP + e * 2), "r"(pack2(o[n][0], o[n][1])) : "memory");
  }
}

__global__ void __launch_bounds__(256, 1)
chain_kernel(const bf16* __restrict__ mem0, const bf16* __restrict__ Wq, const bf16* __restrict__ Wk, const bf16* __restrict__ Wv,
             const bf16* __restrict__ Wo, const bf16* __restrict__ wgate, const bf16* __restrict__ wup, const bf16* __restrict__ wdown) {
  extern __shared__ __align__(1024) uint8_t smem[];
  const int cta = blockIdx.x, t = threadIdx.x, warp = t >> 5, lane = t & 31;
  if (cta >= 128) {
    moe_part(cta - 128, wgate, wup, wdown, smem);
    return;
  }
  const int h = cta >> 2, j = cta & 3;
  const int g = lane >> 2, c = lane & 3;
  const uint32_t sb = smem_u32(smem);
  const int mg = warp & 1, kq = warp >> 1;

  uint32_t wq[RK][3][4];
  uint32_t wo[2][8][4];
  {
    for (int i = t; i < 128 * 4; i += 256)
      asm volatile("prefetch.global.L2 [%0];" ::"l"(Wo + (size_t)(h * 128 + (i >> 2)) * DM + 256 * j + (i & 3) * 64));
    for (int i = t; i < 3 * 1024 * 4; i += 256) {
      int which = i >> 12, k = (i >> 2) & 1023, ch = i & 3;
      const bf16* W = which == 0 ? Wq : (which == 1 ? Wk : Wv);
      cp_async16(sb + (which * 1024 + k) * 64 + ch * 16, W + (size_t)k * HD + h * 128 + 32 * j + ch * 8);
    }
    cp_commit(); cp_wait<0>();
    __syncthreads();
    uint32_t tmp[SK][3][4];
#pragma unroll
    for (int ks = 0; ks < 16; ks++) {
#pragma unroll
      for (int tt = 0; tt < 3; tt++) {
        int tile = 3 * mg + tt;
        int which = tile >> 1, ch = tile & 1;
        int k = (16 * kq + ks) * 16 + (lane & 7) + 8 * (lane >> 4);
        uint32_t addr = sb + (which * 1024 + k) * 64 + ch * 32 + 16 * ((lane >> 3) & 1);
        if (ks < RK) ldsm4t(wq[ks][tt][0], wq[ks][tt][1], wq[ks][tt][2], wq[ks][tt][3], addr);
        else ldsm4t(tmp[ks - RK][tt][0], tmp[ks - RK][tt][1], tmp[ks - RK][tt][2], tmp[ks - RK][tt][3], addr);
      }
    }
    __syncthreads();
#pragma unroll
    for (int ks = 0; ks < SK; ks++)
#pragma unroll
      for (int tt = 0; tt < 3; tt++)
        *reinterpret_cast<uint4*>(smem + OFF_WQS + (((warp * SK + ks) * 3 + tt) * 32 + lane) * 16) =
            make_uint4(tmp[ks][tt][0], tmp[ks][tt][1], tmp[ks][tt][2], tmp[ks][tt][3]);
    for (int i = t; i < 128 * 32; i += 256) {
      int e = i >> 5, ch = i & 31;
      cp_async16(sb + CH_STG2 + e * 512 + ch * 16, Wo + (size_t)(h * 128 + e) * DM + 256 * j + ch * 8);
    }
    cp_commit(); cp_wait<0>();
    __syncthreads();
#pragma unroll
    for (int tt = 0; tt < 2; tt++)
#pragma unroll
      for (int ks = 0; ks < 8; ks++) {
        int e = 16 * ks + (lane & 7) + 8 * (lane >> 4);
        uint32_t addr = sb + CH_STG2 + e * 512 + (32 * warp + 16 * tt + 8 * ((lane >> 3) & 1)) * 2;
        ldsm4t(wo[tt][ks][0], wo[tt][ks][1], wo[tt][ks][2], wo[tt][ks][3], addr);
      }
    if (t == 0) {
      mbar_init(sb + OFF_BAR, 1); mbar_init(sb + OFF_BAR + 8, 1);
      asm volatile("fence.mbarrier_init.release.cluster;" ::: "memory");
    }
    __syncthreads();
    asm volatile("fence.proxy.async.shared::cta;" ::: "memory");
  }
  auto prefetch_tok = [&](int s) {
    const int i = t - 192;
    const uint32_t dst = sb + OFF_TOK + (s & 1) * TOK_BYTES + (i >> 4) * TP + (i & 15) * 16;
    const bf16* src = g_qkv + (size_t)(s * 32 + (i >> 4)) * NQKV + HD + h * 128 + (i & 15) * 8;
#pragma unroll
    for (int r = 0; r < 8; r++) {
      cp_async16(dst + 4 * r * TP, src + (size_t)4 * r * NQKV);
      cp_async16(dst + (32 + 4 * r) * TP, src + (size_t)4 * r * NQKV + HD);
    }
    cp_async16(dst + 64 * TP, src + (size_t)(8 * j) * NQKV - HD);
    cp_async16(dst + 68 * TP, src + (size_t)(8 * j + 4) * NQKV - HD);
    cp_commit();
  };
  if (warp >= 6) prefetch_tok(0);
  for (int i = t; i < 8 * 1024; i += 256) {
    int r = i >> 10, k = i & 1023;
    reinterpret_cast<bf16*>(smem + OFF_MEMT)[k * 8 + r] = mem0[i];
  }
  __syncthreads();
  uint32_t p2dst0, p2dst1;
  {
    int p = t, jj = p / 96, f = p % 96;
    p2dst0 = sb + OFF_QKVM + ((f >> 5) * 128 + 32 * jj + (f & 31)) * 16;
    p = 256 + (t & 127); jj = p / 96; f = p % 96;
    p2dst1 = sb + OFF_QKVM + ((f >> 5) * 128 + 32 * jj + (f & 31)) * 16;
  }
  const int p0idx = 256 * kq + 128 * mg + lane;
  uint32_t tpub = 0;
  const uint32_t dA = DLY_A, dB = DLY_B, dC = DLY_C;
  TS(0);
  for (int s = 0; s < NSEG; s++) {
    const int slot = s & 3, slot2 = (s + 2) & 3;
    if (s > 0) {
      const uint4* src = &g_bufC[(s - 1) & 3][p0idx];
      uint4 v[4];
      wait_until(tpub, dC);
#pragma unroll
      for (int i = 0; i < 4; i++) v[i] = ld_poll(src + 32 * i);
      int it = 0;
      while (!__all_sync(0xffffffffu, pkt_ok(v[0]) && pkt_ok(v[1]) && pkt_ok(v[2]) && pkt_ok(v[3])) && ++it < POLL_MAX) {
#pragma unroll
        for (int i = 0; i < 4; i++)
          if (!pkt_ok(v[i])) v[i] = ld_poll(src + 32 * i);
      }
#pragma unroll
      for (int i = 0; i < 4; i++) sts128(sb + OFF_MEMT + (p0idx + 32 * i) * 16, v[i]);
      TS(1);
      asm volatile("bar.sync %0, 64;" ::"r"(1 + kq) : "memory");
      TS(2);
    }
    {
      float acc[2][3][4];
#pragma unroll
      for (int a = 0; a < 2; a++)
#pragma unroll
        for (int tt = 0; tt < 3; tt++)
#pragma unroll
          for (int i = 0; i < 4; i++) acc[a][tt][i] = 0.f;
      uint4 sa[SK][3];
#pragma unroll
      for (int kp = 0; kp < 8; kp++) {
        uint32_t b0, b1, b2, b3;
        ldsm4t(b0, b1, b2, b3, sb + OFF_MEMT + ((16 * kq + 2 * kp) * 16 + lane) * 16);
#pragma unroll
        for (int u = 0; u < 2; u++) {
          int ks = 2 * (kp + 1) + u;
          if (ks >= RK && ks < 16) {
#pragma unroll
            for (int tt = 0; tt < 3; tt++)
              sa[ks - RK][tt] = *reinterpret_cast<const uint4*>(smem + OFF_WQS + (((warp * SK + (ks - RK)) * 3 + tt) * 32 + lane) * 16);
          }
        }
#pragma unroll
        for (int u = 0; u < 2; u++) {
          int ks = 2 * kp + u;
#pragma unroll
          for (int tt = 0; tt < 3; tt++) {
            if (ks < RK) mma16816(acc[u][tt], wq[ks][tt][0], wq[ks][tt][1], wq[ks][tt][2], wq[ks][tt][3], u ? b2 : b0, u ? b3 : b1);
            else mma16816(acc[u][tt], sa[ks - RK][tt].x, sa[ks - RK][tt].y, sa[ks - RK][tt].z, sa[ks - RK][tt].w, u ? b2 : b0, u ? b3 : b1);
          }
        }
      }
#pragma unroll
      for (int tt = 0; tt < 3; tt++)
        *reinterpret_cast<float4*>(smem + OFF_RED + ((kq * 6 + 3 * mg + tt) * 32 + lane) * 16) =
            make_float4(acc[0][tt][0] + acc[1][tt][0], acc[0][tt][1] + acc[1][tt][1], acc[0][tt][2] + acc[1][tt][2], acc[0][tt][3] + acc[1][tt][3]);
    }
    TS(3);
    __syncthreads();
    TS(4);
    if (warp < 6) {
      float4 r = *reinterpret_cast<const float4*>(smem + OFF_RED + ((0 * 6 + warp) * 32 + lane) * 16);
#pragma unroll
      for (int q = 1; q < 4; q++) {
        float4 x = *reinterpret_cast<const float4*>(smem + OFF_RED + ((q * 6 + warp) * 32 + lane) * 16);
        r.x += x.x; r.y += x.y; r.z += x.z; r.w += x.w;
      }
      uint32_t* dst = reinterpret_cast<uint32_t*>(&g_bufA[slot][cta][16 * warp + g]) + c;
      st_pub32(dst, desent(pack2(r.x, r.y)));
      st_pub32(dst + 32, desent(pack2(r.z, r.w)));
    }
    tpub = clk32();
    {
      const uint4* src = &g_bufA[slot][4 * h][t];
      wait_until(tpub, dA);
      uint4 v0 = ld_poll(src);
      uint4 v1 = make_uint4(0, 0, 0, 0);
      if (t < 128) v1 = ld_poll(src + 256);
      int it = 0;
      while (!__all_sync(0xffffffffu, pkt_ok(v0) && pkt_ok(v1)) && ++it < POLL_MAX) {
        if (!pkt_ok(v0)) v0 = ld_poll(src);
        if (!pkt_ok(v1)) v1 = ld_poll(src + 256);
      }
      sts128(p2dst0, v0);
      if (t < 128) sts128(p2dst1, v1);
    }
    TS(5);
    if (warp >= 6) cp_wait<0>();
    __syncthreads();
    TS(6);
    const uint32_t tok = sb + OFF_TOK + (s & 1) * TOK_BYTES;
    if (s < NSEG - 1) {
      if (warp < 4) attn8<false>(sb, tok, lane, warp, 0, nullptr);
      TS(7);
      __syncthreads();
      TS(8);
      {
        float acc[2][2][4];
#pragma unroll
        for (int a = 0; a < 2; a++)
#pragma unroll
          for (int tt = 0; tt < 2; tt++)
#pragma unroll
            for (int i = 0; i < 4; i++) acc[a][tt][i] = 0.f;
        uint32_t b[4][4];
#pragma unroll
        for (int kp = 0; kp < 4; kp++) ldsm4(b[kp][0], b[kp][1], b[kp][2], b[kp][3], sb + OFF_SA + (lane & 7) * TP + (32 * kp + 8 * (lane >> 3)) * 2);
#pragma unroll
        for (int kp = 0; kp < 4; kp++) {
#pragma unroll
          for (int tt = 0; tt < 2; tt++) {
            mma16816(acc[0][tt], wo[tt][2 * kp][0], wo[tt][2 * kp][1], wo[tt][2 * kp][2], wo[tt][2 * kp][3], b[kp][0], b[kp][1]);
            mma16816(acc[1][tt], wo[tt][2 * kp + 1][0], wo[tt][2 * kp + 1][1], wo[tt][2 * kp + 1][2], wo[tt][2 * kp + 1][3], b[kp][2], b[kp][3]);
          }
        }
        const int off = (g * 32 + h) * 4 + c;
#pragma unroll
        for (int tt = 0; tt < 2; tt++) {
          int r0 = 32 * j + 4 * warp + 2 * tt;
          uint32_t x0 = __float_as_uint(acc[0][tt][0] + acc[1][tt][0]), x1 = __float_as_uint(acc[0][tt][1] + acc[1][tt][1]);
          uint32_t x2 = __float_as_uint(acc[0][tt][2] + acc[1][tt][2]), x3 = __float_as_uint(acc[0][tt][3] + acc[1][tt][3]);
          x0 = x0 == SENT ? 0x7FFFFFFFu : x0; x1 = x1 == SENT ? 0x7FFFFFFFu : x1;
          x2 = x2 == SENT ? 0x7FFFFFFFu : x2; x3 = x3 == SENT ? 0x7FFFFFFFu : x3;
          st_pub64(reinterpret_cast<uint2*>(&g_bufB[slot][r0][0][0]) + off, x0, x1);
          st_pub64(reinterpret_cast<uint2*>(&g_bufB[slot][r0 + 1][0][0]) + off, x2, x3);
        }
        tpub = clk32();
      }
      if (warp >= 4) attn8<true>(sb, tok, lane, warp - 4, 8 * j + g, g_otok + (size_t)(s * 32 + 8 * j + g) * HD + h * 128);
      TS(9);
      {
        const uint4* src = &g_bufB[slot][cta][0][0] + 64 * warp + 2 * lane;
        wait_until(tpub, dB);
        uint4 v0 = ld_poll(src), v1 = ld_poll(src + 1);
        int it = 0;
          while (!__all_sync(0xffffffffu, pkt_ok(v0) && pkt_ok(v1)) && ++it < POLL_MAX) {
            if (!pkt_ok(v0)) v0 = ld_poll(src);
          if (!pkt_ok(v1)) v1 = ld_poll(src + 1);
        }
        TS(10);
        const bool hi = lane & 16;
        float a0 = __uint_as_float(hi ? v1.x : v0.x), a1 = __uint_as_float(hi ? v1.y : v0.y);
        float a2 = __uint_as_float(hi ? v1.z : v0.z), a3 = __uint_as_float(hi ? v1.w : v0.w);
        float b0 = __uint_as_float(hi ? v0.x : v1.x), b1 = __uint_as_float(hi ? v0.y : v1.y);
        float b2 = __uint_as_float(hi ? v0.z : v1.z), b3 = __uint_as_float(hi ? v0.w : v1.w);
        a0 += __shfl_xor_sync(0xffffffffu, b0, 16); a1 += __shfl_xor_sync(0xffffffffu, b1, 16);
        a2 += __shfl_xor_sync(0xffffffffu, b2, 16); a3 += __shfl_xor_sync(0xffffffffu, b3, 16);
        const bool h8 = lane & 8;
        float k0 = h8 ? a2 : a0, k1 = h8 ? a3 : a1, s0 = h8 ? a0 : a2, s1 = h8 ? a1 : a3;
        k0 += __shfl_xor_sync(0xffffffffu, s0, 8); k1 += __shfl_xor_sync(0xffffffffu, s1, 8);
        const bool h4 = lane & 4;
        float z = h4 ? k1 : k0, zs = h4 ? k0 : k1;
        z += __shfl_xor_sync(0xffffffffu, zs, 4);
        z += __shfl_xor_sync(0xffffffffu, z, 2);
        z += __shfl_xor_sync(0xffffffffu, z, 1);
        float zo = __shfl_xor_sync(0xffffffffu, z, 4);
        if ((lane & 7) == 0) {
          uint32_t* d = reinterpret_cast<uint32_t*>(&g_bufC[slot][8 * cta + warp]) + (lane >> 3);
          st_pub32(d, desent(pack2(z, zo)));
        }
        tpub = clk32();
      }
    }
    if (s == NSEG - 1) {
      if (warp >= 4) attn8<true>(sb, tok, lane, warp - 4, 8 * j + g, g_otok + (size_t)(s * 32 + 8 * j + g) * HD + h * 128);
    } else if (warp >= 6) {
      prefetch_tok(s + 1);
    } else if (warp >= 4) {
      const int i = t - 128;
      st_pub128(&g_bufA[slot2][cta][i], SENT);
      if (i < 32) st_pub128(&g_bufA[slot2][cta][64 + i], SENT);
      if (i < 8) st_pub128(&g_bufC[slot2][8 * cta + i], SENT);
      uint4* bb = &g_bufB[slot2][32 * j + (i >> 1)][0][0] + 2 * h + (i & 1);
#pragma unroll
      for (int col = 0; col < 8; col++) st_pub128(bb + 64 * col, SENT);
    }
    TS(11);
  }
}

__device__ void moe_part(int m, const bf16* __restrict__ wg, const bf16* __restrict__ wu, const bf16* __restrict__ wd, uint8_t* smem) {
  const int t = threadIdx.x, warp = t >> 5, lane = t & 31;
  float* xs = reinterpret_cast<float*>(smem);
  float* red = reinterpret_cast<float*>(smem + 8192);
  float* hs = reinterpret_cast<float*>(smem + 65536);
  __shared__ float bv[8];
  __shared__ int bi[8];
  __shared__ int sel[2];
  int first = -1;
  for (int pass = 0; pass < 2; pass++) {
    float best = -INFINITY; int bidx = 0x7fffffff;
    for (int i = t; i < S_LEN; i += 256) {
      float v = g_r[i];
      if (i == first) continue;
      if (v > best || (v == best && i < bidx) || bidx == 0x7fffffff) { best = v; bidx = i; }
    }
#pragma unroll
    for (int o = 16; o > 0; o >>= 1) {
      float ov = __shfl_xor_sync(0xffffffffu, best, o); int oi = __shfl_xor_sync(0xffffffffu, bidx, o);
      if (oi != 0x7fffffff && (bidx == 0x7fffffff || ov > best || (ov == best && oi < bidx))) { best = ov; bidx = oi; }
    }
    if (lane == 0) { bv[warp] = best; bi[warp] = bidx; }
    __syncthreads();
    if (t == 0) {
      float b = bv[0]; int ix = bi[0];
      for (int w = 1; w < 8; w++) if (bv[w] > b || (bv[w] == b && bi[w] < ix)) { b = bv[w]; ix = bi[w]; }
      sel[pass] = ix;
    }
    __syncthreads();
    first = sel[0];
  }
  const int s0 = sel[0], s1 = sel[1];
  for (int i = t; i < 2048; i += 256) xs[i] = __bfloat162float(g_xn[(size_t)(i < 1024 ? s0 : s1) * DM + (i & 1023)]);
  __syncthreads();
  {
    int cg = t % 112, kh = t / 112;
    float a[2][2][8];
#pragma unroll
    for (int i = 0; i < 8; i++) { a[0][0][i] = a[0][1][i] = a[1][0][i] = a[1][1][i] = 0.f; }
    if (kh < 2) {
      const bf16* pg = wg + (size_t)(kh * 512) * FF + 896 * m + cg * 8;
      const bf16* pu = wu + (size_t)(kh * 512) * FF + 896 * m + cg * 8;
#pragma unroll 8
      for (int k = 0; k < 512; k++) {
        uint4 gv = __ldg(reinterpret_cast<const uint4*>(pg + (size_t)k * FF));
        uint4 uv = __ldg(reinterpret_cast<const uint4*>(pu + (size_t)k * FF));
        float x0 = xs[kh * 512 + k], x1 = xs[1024 + kh * 512 + k];
        float gf[8] = {bflo(gv.x), bfhi(gv.x), bflo(gv.y), bfhi(gv.y), bflo(gv.z), bfhi(gv.z), bflo(gv.w), bfhi(gv.w)};
        float uf[8] = {bflo(uv.x), bfhi(uv.x), bflo(uv.y), bfhi(uv.y), bflo(uv.z), bfhi(uv.z), bflo(uv.w), bfhi(uv.w)};
#pragma unroll
        for (int i = 0; i < 8; i++) {
          a[0][0][i] += x0 * gf[i]; a[0][1][i] += x1 * gf[i];
          a[1][0][i] += x0 * uf[i]; a[1][1][i] += x1 * uf[i];
        }
      }
      if (kh == 1) {
#pragma unroll
        for (int i = 0; i < 8; i++) {
          red[(0 * 2 + 0) * 896 + cg * 8 + i] = a[0][0][i]; red[(0 * 2 + 1) * 896 + cg * 8 + i] = a[0][1][i];
          red[(1 * 2 + 0) * 896 + cg * 8 + i] = a[1][0][i]; red[(1 * 2 + 1) * 896 + cg * 8 + i] = a[1][1][i];
        }
      }
    }
    __syncthreads();
    if (kh == 0) {
#pragma unroll
      for (int i = 0; i < 8; i++) {
#pragma unroll
        for (int tk = 0; tk < 2; tk++) {
          float gq = bfr(a[0][tk][i] + red[(0 * 2 + tk) * 896 + cg * 8 + i]);
          float uq = bfr(a[1][tk][i] + red[(1 * 2 + tk) * 896 + cg * 8 + i]);
          float sg = bfr(gq / (1.0f + __expf(-gq)));
          g_h[tk][896 * m + cg * 8 + i] = __float2bfloat16_rn(sg * uq);
        }
      }
    }
    __threadfence();
    __syncthreads();
    if (t == 0) {
      atomicAdd(&g_moe_cnt, 1u);
      int it = 0;
      while (*reinterpret_cast<volatile unsigned*>(&g_moe_cnt) < 4u && ++it < (1 << 24)) {}
      __threadfence();
    }
    __syncthreads();
  }
  for (int i = t; i < 2 * FF; i += 256) {
    const volatile unsigned short* p = reinterpret_cast<const volatile unsigned short*>(&g_h[0][0]);
    hs[i] = __uint_as_float(((uint32_t)p[i]) << 16);
  }
  __syncthreads();
  {
    int cg = t & 31, ksl = t >> 5;
    float a[2][8];
#pragma unroll
    for (int i = 0; i < 8; i++) a[0][i] = a[1][i] = 0.f;
    const bf16* pd = wd + (size_t)(ksl * 448) * DM + 256 * m + cg * 8;
#pragma unroll 8
    for (int k = 0; k < 448; k++) {
      uint4 dv = __ldg(reinterpret_cast<const uint4*>(pd + (size_t)k * DM));
      float x0 = hs[ksl * 448 + k], x1 = hs[FF + ksl * 448 + k];
      float df[8] = {bflo(dv.x), bfhi(dv.x), bflo(dv.y), bfhi(dv.y), bflo(dv.z), bfhi(dv.z), bflo(dv.w), bfhi(dv.w)};
#pragma unroll
      for (int i = 0; i < 8; i++) { a[0][i] += x0 * df[i]; a[1][i] += x1 * df[i]; }
    }
#pragma unroll
    for (int i = 0; i < 8; i++) { red[(ksl * 2 + 0) * 256 + cg * 8 + i] = a[0][i]; red[(ksl * 2 + 1) * 256 + cg * 8 + i] = a[1][i]; }
    __syncthreads();
    for (int i = t; i < 512; i += 256) {
      int tk = i >> 8, col = i & 255;
      float y = 0.f;
#pragma unroll
      for (int q = 0; q < 8; q++) y += red[(q * 2 + tk) * 256 + col];
      float rr = g_r[tk == 0 ? s0 : s1];
      float sg = bfr(1.0f / (1.0f + __expf(-rr)));
      g_upd[tk][256 * m + col] = bfr(bfr(y) * sg);
    }
    if (m == 0 && t == 0) { g_sel[0] = s0; g_sel[1] = s1; }
  }
}

typedef CUresult (*EncodeFn)(CUtensorMap*, CUtensorMapDataType, cuuint32_t, void*, const cuuint64_t*, const cuuint64_t*,
                             const cuuint32_t*, const cuuint32_t*, CUtensorMapInterleave, CUtensorMapSwizzle,
                             CUtensorMapL2promotion, CUtensorMapFloatOOBfill);

static void make_map(EncodeFn enc, CUtensorMap* m, const void* ptr, uint64_t inner, uint64_t outer, uint32_t bi, uint32_t bo) {
  cuuint64_t dims[2] = {inner, outer};
  cuuint64_t strides[1] = {inner * 2};
  cuuint32_t box[2] = {bi, bo};
  cuuint32_t es[2] = {1, 1};
  enc(m, CU_TENSOR_MAP_DATA_TYPE_BFLOAT16, 2, const_cast<void*>(ptr), dims, strides, box, es, CU_TENSOR_MAP_INTERLEAVE_NONE,
      CU_TENSOR_MAP_SWIZZLE_128B, CU_TENSOR_MAP_L2_PROMOTION_L2_256B, CU_TENSOR_MAP_FLOAT_OOB_FILL_NONE);
}

extern "C" void kernel_launch(void* const* d_in, const int* in_sizes, int n_in, void* d_out, int out_size) {
  const bf16* x = (const bf16*)d_in[0];
  const bf16* mem0 = (const bf16*)d_in[1];
  const bf16* Wq = (const bf16*)d_in[2];
  const bf16* Wk = (const bf16*)d_in[3];
  const bf16* Wv = (const bf16*)d_in[4];
  const bf16* Wo = (const bf16*)d_in[5];
  const bf16* w_r = (const bf16*)d_in[8];
  const bf16* wg = (const bf16*)d_in[9];
  const bf16* wu = (const bf16*)d_in[10];
  const bf16* wd = (const bf16*)d_in[11];
  bf16* out = (bf16*)d_out;

  static EncodeFn enc = nullptr;
  static void *p_xn, *p_qkv, *p_otok;
  if (!enc) {
    cudaDriverEntryPointQueryResult qr;
    void* fn = nullptr;
    cudaGetDriverEntryPoint("cuTensorMapEncodeTiled", &fn, cudaEnableDefault, &qr);
    enc = (EncodeFn)fn;
    cudaGetSymbolAddress(&p_xn, g_xn);
    cudaGetSymbolAddress(&p_qkv, g_qkv);
    cudaGetSymbolAddress(&p_otok, g_otok);
    cudaFuncSetAttribute(gemm_kernel<256, 4, 0>, cudaFuncAttributeMaxDynamicSharedMemorySize, GemmSmem<256, 4>::TOTAL);
    cudaFuncSetAttribute(gemm_kernel<128, 6, 1>, cudaFuncAttributeMaxDynamicSharedMemorySize, GemmSmem<128, 6>::TOTAL);
    cudaFuncSetAttribute(chain_kernel, cudaFuncAttributeMaxDynamicSharedMemorySize, CH_SMEM);
  }
  CUtensorMap mA, mQ, mK, mV, mO, mWo;
  make_map(enc, &mA, p_xn, DM, S_LEN, 64, 128);
  make_map(enc, &mQ, Wq, HD, DM, 64, 64);
  make_map(enc, &mK, Wk, HD, DM, 64, 64);
  make_map(enc, &mV, Wv, HD, DM, 64, 64);
  make_map(enc, &mO, p_otok, HD, S_LEN, 64, 128);
  make_map(enc, &mWo, Wo, DM, HD, 64, 64);

  cudaStream_t st = cudaStreamPerThread;
  ln_kernel<<<256, 256, 0, st>>>(x, w_r);
  gemm_kernel<256, 4, 0><<<132, 288, GemmSmem<256, 4>::TOTAL, st>>>(mA, mQ, mK, mV, 16, 16, 16 * 48, nullptr, (bf16*)p_qkv);
  chain_kernel<<<132, 256, CH_SMEM, st>>>(mem0, Wq, Wk, Wv, Wo, wg, wu, wd);
  gemm_kernel<128, 6, 1><<<128, 288, GemmSmem<128, 6>::TOTAL, st>>>(mO, mWo, mWo, mWo, 64, 16, 16 * 8, x, out);
}
```

```cpp
#include <cuda_runtime.h>
#include <cuda_bf16.h>
#include <cuda.h>
#include <stdint.h>

typedef __nv_bfloat16 bf16;

#define S_LEN 2048
#define DM 1024
#define NH 32
#define DH 128
#define NSEG 64
#define SEGL 32
#define HD 4096
#define NQKV 12288
#define FF 3584
#define SENT 0xFFFFFFFFu

__device__ __align__(1024) bf16 g_xn[S_LEN * DM];
__device__ __align__(1024) bf16 g_qkv[(size_t)S_LEN * NQKV];
__device__ __align__(1024) bf16 g_otok[(size_t)S_LEN * HD];
__device__ float g_r[S_LEN];
__device__ __align__(128) uint4 g_bufA[4][128][96];
__device__ __align__(128) uint4 g_bufB[4][128][16][32];
__device__ __align__(128) uint4 g_bufC[4][1024];
__device__ __align__(128) bf16 g_h[2][FF];
__device__ float g_upd[2][DM];
__device__ int g_sel[2];
__device__ unsigned g_moe_cnt;
#define VAR 1
#define DLY_A 300u
#define DLY_B 800u
#define DLY_C 700u
#define TS(i)

__device__ __forceinline__ float bfr(float x) { return __bfloat162float(__float2bfloat16_rn(x)); }
__device__ __forceinline__ uint32_t pack2(float lo, float hi) {
  __nv_bfloat162 v = __floats2bfloat162_rn(lo, hi);
  return *reinterpret_cast<uint32_t*>(&v);
}
__device__ __forceinline__ float bflo(uint32_t v) { return __uint_as_float(v << 16); }
__device__ __forceinline__ float bfhi(uint32_t v) { return __uint_as_float(v & 0xFFFF0000u); }
__device__ __forceinline__ uint32_t smem_u32(const void* p) { return (uint32_t)__cvta_generic_to_shared(p); }

__device__ __forceinline__ uint4 ld_poll(const uint4* p) {
  uint4 v;
  asm volatile("ld.relaxed.gpu.global.v4.u32 {%0,%1,%2,%3},[%4];" : "=r"(v.x), "=r"(v.y), "=r"(v.z), "=r"(v.w) : "l"(p) : "memory");
  return v;
}
__device__ __forceinline__ void st_pub32(void* p, uint32_t v) {
  asm volatile("st.relaxed.gpu.global.u32 [%0],%1;" ::"l"(p), "r"(v) : "memory");
}
__device__ __forceinline__ void st_pub64(void* p, uint32_t a, uint32_t b) {
  asm volatile("st.relaxed.gpu.global.v2.u32 [%0],{%1,%2};" ::"l"(p), "r"(a), "r"(b) : "memory");
}
__device__ __forceinline__ bool pkt_ok(const uint4& v) { return v.x != SENT && v.y != SENT && v.z != SENT && v.w != SENT; }
__device__ __forceinline__ uint32_t desent(uint32_t v) { return v == SENT ? 0x7FFF7FFFu : v; }

__device__ __forceinline__ void ldsm4(uint32_t& r0, uint32_t& r1, uint32_t& r2, uint32_t& r3, uint32_t addr) {
  asm volatile("ldmatrix.sync.aligned.m8n8.x4.shared.b16 {%0,%1,%2,%3},[%4];" : "=r"(r0), "=r"(r1), "=r"(r2), "=r"(r3) : "r"(addr) : "memory");
}
__device__ __forceinline__ void ldsm4t(uint32_t& r0, uint32_t& r1, uint32_t& r2, uint32_t& r3, uint32_t addr) {
  asm volatile("ldmatrix.sync.aligned.m8n8.x4.trans.shared.b16 {%0,%1,%2,%3},[%4];" : "=r"(r0), "=r"(r1), "=r"(r2), "=r"(r3) : "r"(addr) : "memory");
}
__device__ __forceinline__ void mma16816(float (&d)[4], uint32_t a0, uint32_t a1, uint32_t a2, uint32_t a3, uint32_t b0, uint32_t b1) {
  asm volatile("mma.sync.aligned.m16n8k16.row.col.f32.bf16.bf16.f32 {%0,%1,%2,%3},{%4,%5,%6,%7},{%8,%9},{%0,%1,%2,%3};"
               : "+f"(d[0]), "+f"(d[1]), "+f"(d[2]), "+f"(d[3])
               : "r"(a0), "r"(a1), "r"(a2), "r"(a3), "r"(b0), "r"(b1));
}
__device__ __forceinline__ void cp_async16(uint32_t dst, const void* src) {
  asm volatile("cp.async.cg.shared.global [%0],[%1],16;" ::"r"(dst), "l"(src) : "memory");
}
__device__ __forceinline__ void cp_commit() { asm volatile("cp.async.commit_group;" ::: "memory"); }
template <int N>
__device__ __forceinline__ void cp_wait() { asm volatile("cp.async.wait_group %0;" ::"n"(N) : "memory"); }

__device__ __forceinline__ void mbar_init(uint32_t bar, uint32_t cnt) { asm volatile("mbarrier.init.shared::cta.b64 [%0],%1;" ::"r"(bar), "r"(cnt) : "memory"); }
__device__ __forceinline__ void mbar_expect_tx(uint32_t bar, uint32_t bytes) {
  asm volatile("mbarrier.arrive.expect_tx.shared::cta.b64 _,[%0],%1;" ::"r"(bar), "r"(bytes) : "memory");
}
__device__ __forceinline__ void mbar_arrive(uint32_t bar) { asm volatile("mbarrier.arrive.shared::cta.b64 _,[%0];" ::"r"(bar) : "memory"); }
__device__ __forceinline__ void mbar_wait(uint32_t bar, uint32_t parity) {
  asm volatile(
      "{\n.reg .pred p;\n"
      "WAIT_LOOP:\n"
      "mbarrier.try_wait.parity.shared::cta.b64 p,[%0],%1;\n"
      "@p bra WAIT_DONE;\n"
      "bra WAIT_LOOP;\n"
      "WAIT_DONE:\n}\n" ::"r"(bar), "r"(parity) : "memory");
}
__device__ __forceinline__ void tma_load2d(uint32_t dst, const CUtensorMap* tm, uint32_t bar, int c0, int c1) {
  asm volatile("cp.async.bulk.tensor.2d.shared::cluster.global.mbarrier::complete_tx::bytes [%0],[%1,{%3,%4}],[%2];"
               ::"r"(dst), "l"(tm), "r"(bar), "r"(c0), "r"(c1) : "memory");
}
__device__ __forceinline__ void tma_load2d_mc(uint32_t dst, const CUtensorMap* tm, uint32_t bar, int c0, int c1, uint16_t mask) {
  asm volatile("cp.async.bulk.tensor.2d.shared::cluster.global.mbarrier::complete_tx::bytes.multicast::cluster [%0],[%1,{%3,%4}],[%2],%5;"
               ::"r"(dst), "l"(tm), "r"(bar), "r"(c0), "r"(c1), "h"(mask) : "memory");
}
__device__ __forceinline__ void mbar_arrive_cluster(uint32_t bar, uint32_t cta) {
  asm volatile("{\n.reg .b32 ra;\nmapa.shared::cluster.u32 ra,%0,%1;\nmbarrier.arrive.shared::cluster.b64 _,[ra];\n}\n" ::"r"(bar), "r"(cta) : "memory");
}
__device__ __forceinline__ void cluster_sync() {
  asm volatile("barrier.cluster.arrive.release.aligned;\nbarrier.cluster.wait.acquire.aligned;\n" ::: "memory");
}
__device__ __forceinline__ void wg_fence() { asm volatile("wgmma.fence.sync.aligned;" ::: "memory"); }
__device__ __forceinline__ void wg_commit() { asm volatile("wgmma.commit_group.sync.aligned;" ::: "memory"); }
template <int N>
__device__ __forceinline__ void wg_wait() { asm volatile("wgmma.wait_group.sync.aligned %0;" ::"n"(N) : "memory"); }
__device__ __forceinline__ uint64_t make_desc(uint32_t addr, uint32_t lbo, uint32_t sbo) {
  return (uint64_t)((addr & 0x3FFFF) >> 4) | ((uint64_t)(lbo >> 4) << 16) | ((uint64_t)(sbo >> 4) << 32) | (1ull << 62);
}

__device__ __forceinline__ void wgmma_m64n256k16(float (&d)[128], uint64_t da, uint64_t db, int scaleD) {
  asm volatile(
    "{\n.reg .pred p;\nsetp.ne.b32 p, %130, 0;\n"
    "wgmma.mma_async.sync.aligned.m64n256k16.f32.bf16.bf16 "
    "{%0, %1, %2, %3, %4, %5, %6, %7, %8, %9, %10, %11, %12, %13, %14, %15, %16, %17, %18, %19, %20, %21, %22, %23, %24, %25, %26, %27, %28, %29, %30, %31, %32, %33, %34, %35, %36, %37, %38, %39, %40, %41, %42, %43, %44, %45, %46, %47, %48, %49, %50, %51, %52, %53, %54, %55, %56, %57, %58, %59, %60, %61, %62, %63, %64, %65, %66, %67, %68, %69, %70, %71, %72, %73, %74, %75, %76, %77, %78, %79, %80, %81, %82, %83, %84, %85, %86, %87, %88, %89, %90, %91, %92, %93, %94, %95, %96, %97, %98, %99, %100, %101, %102, %103, %104, %105, %106, %107, %108, %109, %110, %111, %112, %113, %114, %115, %116, %117, %118, %119, %120, %121, %122, %123, %124, %125, %126, %127}, %128, %129, p, 1, 1, 0, 1;\n}\n"
    : "+f"(d[0]), "+f"(d[1]), "+f"(d[2]), "+f"(d[3]), "+f"(d[4]), "+f"(d[5]), "+f"(d[6]), "+f"(d[7]), "+f"(d[8]), "+f"(d[9]), "+f"(d[10]), "+f"(d[11]), "+f"(d[12]), "+f"(d[13]), "+f"(d[14]), "+f"(d[15]), "+f"(d[16]), "+f"(d[17]), "+f"(d[18]), "+f"(d[19]), "+f"(d[20]), "+f"(d[21]), "+f"(d[22]), "+f"(d[23]), "+f"(d[24]), "+f"(d[25]), "+f"(d[26]), "+f"(d[27]), "+f"(d[28]), "+f"(d[29]), "+f"(d[30]), "+f"(d[31]), "+f"(d[32]), "+f"(d[33]), "+f"(d[34]), "+f"(d[35]), "+f"(d[36]), "+f"(d[37]), "+f"(d[38]), "+f"(d[39]), "+f"(d[40]), "+f"(d[41]), "+f"(d[42]), "+f"(d[43]), "+f"(d[44]), "+f"(d[45]), "+f"(d[46]), "+f"(d[47]), "+f"(d[48]), "+f"(d[49]), "+f"(d[50]), "+f"(d[51]), "+f"(d[52]), "+f"(d[53]), "+f"(d[54]), "+f"(d[55]), "+f"(d[56]), "+f"(d[57]), "+f"(d[58]), "+f"(d[59]), "+f"(d[60]), "+f"(d[61]), "+f"(d[62]), "+f"(d[63]), "+f"(d[64]), "+f"(d[65]), "+f"(d[66]), "+f"(d[67]), "+f"(d[68]), "+f"(d[69]), "+f"(d[70]), "+f"(d[71]), "+f"(d[72]), "+f"(d[73]), "+f"(d[74]), "+f"(d[75]), "+f"(d[76]), "+f"(d[77]), "+f"(d[78]), "+f"(d[79]), "+f"(d[80]), "+f"(d[81]), "+f"(d[82]), "+f"(d[83]), "+f"(d[84]), "+f"(d[85]), "+f"(d[86]), "+f"(d[87]), "+f"(d[88]), "+f"(d[89]), "+f"(d[90]), "+f"(d[91]), "+f"(d[92]), "+f"(d[93]), "+f"(d[94]), "+f"(d[95]), "+f"(d[96]), "+f"(d[97]), "+f"(d[98]), "+f"(d[99]), "+f"(d[100]), "+f"(d[101]), "+f"(d[102]), "+f"(d[103]), "+f"(d[104]), "+f"(d[105]), "+f"(d[106]), "+f"(d[107]), "+f"(d[108]), "+f"(d[109]), "+f"(d[110]), "+f"(d[111]), "+f"(d[112]), "+f"(d[113]), "+f"(d[114]), "+f"(d[115]), "+f"(d[116]), "+f"(d[117]), "+f"(d[118]), "+f"(d[119]), "+f"(d[120]), "+f"(d[121]), "+f"(d[122]), "+f"(d[123]), "+f"(d[124]), "+f"(d[125]), "+f"(d[126]), "+f"(d[127])
    : "l"(da), "l"(db), "r"(scaleD));
}

__device__ __forceinline__ void wgmma_m64n128k16(float (&d)[64], uint64_t da, uint64_t db, int scaleD) {
  asm volatile(
    "{\n.reg .pred p;\nsetp.ne.b32 p, %66, 0;\n"
    "wgmma.mma_async.sync.aligned.m64n128k16.f32.bf16.bf16 "
    "{%0, %1, %2, %3, %4, %5, %6, %7, %8, %9, %10, %11, %12, %13, %14, %15, %16, %17, %18, %19, %20, %21, %22, %23, %24, %25, %26, %27, %28, %29, %30, %31, %32, %33, %34, %35, %36, %37, %38, %39, %40, %41, %42, %43, %44, %45, %46, %47, %48, %49, %50, %51, %52, %53, %54, %55, %56, %57, %58, %59, %60, %61, %62, %63}, %64, %65, p, 1, 1, 0, 1;\n}\n"
    : "+f"(d[0]), "+f"(d[1]), "+f"(d[2]), "+f"(d[3]), "+f"(d[4]), "+f"(d[5]), "+f"(d[6]), "+f"(d[7]), "+f"(d[8]), "+f"(d[9]), "+f"(d[10]), "+f"(d[11]), "+f"(d[12]), "+f"(d[13]), "+f"(d[14]), "+f"(d[15]), "+f"(d[16]), "+f"(d[17]), "+f"(d[18]), "+f"(d[19]), "+f"(d[20]), "+f"(d[21]), "+f"(d[22]), "+f"(d[23]), "+f"(d[24]), "+f"(d[25]), "+f"(d[26]), "+f"(d[27]), "+f"(d[28]), "+f"(d[29]), "+f"(d[30]), "+f"(d[31]), "+f"(d[32]), "+f"(d[33]), "+f"(d[34]), "+f"(d[35]), "+f"(d[36]), "+f"(d[37]), "+f"(d[38]), "+f"(d[39]), "+f"(d[40]), "+f"(d[41]), "+f"(d[42]), "+f"(d[43]), "+f"(d[44]), "+f"(d[45]), "+f"(d[46]), "+f"(d[47]), "+f"(d[48]), "+f"(d[49]), "+f"(d[50]), "+f"(d[51]), "+f"(d[52]), "+f"(d[53]), "+f"(d[54]), "+f"(d[55]), "+f"(d[56]), "+f"(d[57]), "+f"(d[58]), "+f"(d[59]), "+f"(d[60]), "+f"(d[61]), "+f"(d[62]), "+f"(d[63])
    : "l"(da), "l"(db), "r"(scaleD));
}

template <int BN> struct WG;
template <> struct WG<256> { static __device__ __forceinline__ void mma(float (&d)[128], uint64_t a, uint64_t b, int s) { wgmma_m64n256k16(d, a, b, s); } };
template <> struct WG<128> { static __device__ __forceinline__ void mma(float (&d)[64], uint64_t a, uint64_t b, int s) { wgmma_m64n128k16(d, a, b, s); } };

__global__ void __launch_bounds__(256) ln_kernel(const bf16* __restrict__ x, const bf16* __restrict__ w_r) {
  int warp = threadIdx.x >> 5, lane = threadIdx.x & 31;
  int row = blockIdx.x * 8 + warp;
  const uint4* xp = reinterpret_cast<const uint4*>(x + (size_t)row * DM);
  uint4 v[4];
#pragma unroll
  for (int i = 0; i < 4; i++) v[i] = xp[lane + 32 * i];
  float f[32];
#pragma unroll
  for (int i = 0; i < 4; i++) {
    f[8 * i + 0] = bflo(v[i].x); f[8 * i + 1] = bfhi(v[i].x);
    f[8 * i + 2] = bflo(v[i].y); f[8 * i + 3] = bfhi(v[i].y);
    f[8 * i + 4] = bflo(v[i].z); f[8 * i + 5] = bfhi(v[i].z);
    f[8 * i + 6] = bflo(v[i].w); f[8 * i + 7] = bfhi(v[i].w);
  }
  float s = 0.f;
#pragma unroll
  for (int i = 0; i < 32; i++) s += f[i];
#pragma unroll
  for (int o = 16; o > 0; o >>= 1) s += __shfl_xor_sync(0xffffffffu, s, o);
  float mean = s * (1.0f / DM);
  float q = 0.f;
#pragma unroll
  for (int i = 0; i < 32; i++) { float d = f[i] - mean; q += d * d; }
#pragma unroll
  for (int o = 16; o > 0; o >>= 1) q += __shfl_xor_sync(0xffffffffu, q, o);
  float var = bfr(q * (1.0f / DM));
  float mb = bfr(mean);
  float den = bfr(sqrtf(bfr(var + 1e-5f)));
  const uint4* wp = reinterpret_cast<const uint4*>(w_r);
  uint4* op = reinterpret_cast<uint4*>(g_xn + (size_t)row * DM);
  float r = 0.f;
#pragma unroll
  for (int i = 0; i < 4; i++) {
    uint4 w = wp[lane + 32 * i];
    float y[8];
#pragma unroll
    for (int k = 0; k < 8; k++) y[k] = bfr(bfr(f[8 * i + k] - mb) / den);
    r += y[0] * bflo(w.x) + y[1] * bfhi(w.x) + y[2] * bflo(w.y) + y[3] * bfhi(w.y) + y[4] * bflo(w.z) + y[5] * bfhi(w.z) +
         y[6] * bflo(w.w) + y[7] * bfhi(w.w);
    op[lane + 32 * i] = make_uint4(pack2(y[0], y[1]), pack2(y[2], y[3]), pack2(y[4], y[5]), pack2(y[6], y[7]));
  }
#pragma unroll
  for (int o = 16; o > 0; o >>= 1) r += __shfl_xor_sync(0xffffffffu, r, o);
  if (lane == 0) g_r[row] = bfr(r);
  int gt = blockIdx.x * 256 + threadIdx.x;
  const uint4 sv = make_uint4(SENT, SENT, SENT, SENT);
  uint4* a = &g_bufA[0][0][0];
  for (int i = gt; i < 2 * 128 * 96; i += 65536) a[i] = sv;
  uint4* b = &g_bufB[0][0][0][0];
  for (int i = gt; i < 2 * 128 * 32 * 16; i += 65536) b[i] = sv;
  uint4* c = &g_bufC[0][0];
  for (int i = gt; i < 2 * 1024; i += 65536) c[i] = sv;
  if (gt == 0) g_moe_cnt = 0;
}

template <int BN, int STAGES>
struct GemmSmem {
  static constexpr int A_BYTES = 128 * 64 * 2;
  static constexpr int B_BYTES = 64 * BN * 2;
  static constexpr int STAGE_BYTES = A_BYTES + B_BYTES;
  static constexpr int TOTAL = STAGES * STAGE_BYTES + 1024 + 256;
};

__device__ __forceinline__ void quad_transpose(uint32_t (&v)[4], int c) {
  {
    uint32_t s0 = (c & 1) ? v[0] : v[1];
    uint32_t s1 = (c & 1) ? v[2] : v[3];
    uint32_t r0 = __shfl_xor_sync(0xffffffffu, s0, 1);
    uint32_t r1 = __shfl_xor_sync(0xffffffffu, s1, 1);
    if (c & 1) { v[0] = r0; v[2] = r1; } else { v[1] = r0; v[3] = r1; }
  }
  {
    uint32_t s0 = (c & 2) ? v[0] : v[2];
    uint32_t s1 = (c & 2) ? v[1] : v[3];
    uint32_t r0 = __shfl_xor_sync(0xffffffffu, s0, 2);
    uint32_t r1 = __shfl_xor_sync(0xffffffffu, s1, 2);
    if (c & 2) { v[0] = r0; v[1] = r1; } else { v[2] = r0; v[3] = r1; }
  }
}

__device__ __forceinline__ uint32_t add3(uint32_t a, uint32_t x, uint32_t b) {
  float lo = bfr(bflo(x) + bflo(a)) + bflo(b);
  float hi = bfr(bfhi(x) + bfhi(a)) + bfhi(b);
  return pack2(lo, hi);
}

template <int BN, int STAGES, int EPI>
__global__ void __launch_bounds__(288, 1)
gemm_kernel(const __grid_constant__ CUtensorMap tmA, const __grid_constant__ CUtensorMap tmB0,
            const __grid_constant__ CUtensorMap tmB1, const __grid_constant__ CUtensorMap tmB2,
            int kblocks, int tiles_m, int tiles_total, const bf16* __restrict__ xin, bf16* __restrict__ outp) {
  using SM = GemmSmem<BN, STAGES>;
  extern __shared__ uint8_t smem_raw[];
  uint32_t base = (smem_u32(smem_raw) + 1023) & ~1023u;
  uint32_t bars = base + STAGES * SM::STAGE_BYTES;
  int warp = threadIdx.x >> 5, lane = threadIdx.x & 31;
  uint32_t rank;
  asm volatile("mov.u32 %0,%%cluster_ctarank;" : "=r"(rank));
  const int cl = blockIdx.x >> 1, ncl = gridDim.x >> 1;
  const int pairs_m = tiles_m >> 1, pairs_total = tiles_total >> 1;
  if (threadIdx.x == 0) {
    for (int i = 0; i < STAGES; i++) { mbar_init(bars + 8 * i, 1); mbar_init(bars + 8 * (STAGES + i), 16); }
    asm volatile("fence.mbarrier_init.release.cluster;" ::: "memory");
  }
  __syncthreads();
  cluster_sync();
  if (warp == 8) {
    if (lane == 0) {
      int it = 0;
      for (int t = cl; t < pairs_total; t += ncl) {
        int tm = 2 * (t % pairs_m) + rank, tn = t / pairs_m;
        int n0 = tn * BN;
        const CUtensorMap* tb = &tmB0;
        if (EPI == 0) { int wsel = n0 >> 12; tb = wsel == 0 ? &tmB0 : (wsel == 1 ? &tmB1 : &tmB2); n0 &= 4095; }
        for (int kb = 0; kb < kblocks; kb++, it++) {
          int st = it % STAGES; uint32_t ph = (it / STAGES) & 1;
          mbar_wait(bars + 8 * (STAGES + st), ph ^ 1);
          uint32_t sa = base + st * SM::STAGE_BYTES, sb = sa + SM::A_BYTES;
          mbar_expect_tx(bars + 8 * st, SM::STAGE_BYTES);
          tma_load2d(sa, &tmA, bars + 8 * st, kb * 64, tm * 128);
#pragma unroll
          for (int i = 0; i < BN / 128; i++) {
            int bx = rank * (BN / 128) + i;
            tma_load2d_mc(sb + bx * 8192, tb, bars + 8 * st, n0 + bx * 64, kb * 64, (uint16_t)3);
          }
        }
      }
    }
    __syncwarp();
  } else {
    int wg = warp >> 2;
    int g = lane >> 2, c = lane & 3;
    int it = 0;
    float acc[BN / 2];
    for (int t = cl; t < pairs_total; t += ncl) {
      int tm = 2 * (t % pairs_m) + rank, tn = t / pairs_m;
      for (int kb = 0; kb < kblocks; kb++, it++) {
        int st = it % STAGES; uint32_t ph = (it / STAGES) & 1;
        mbar_wait(bars + 8 * st, ph);
        uint32_t sa = base + st * SM::STAGE_BYTES + wg * 8192, sb = base + st * SM::STAGE_BYTES + SM::A_BYTES;
        wg_fence();
#pragma unroll
        for (int kk = 0; kk < 4; kk++) {
          uint64_t da = make_desc(sa + kk * 32, 16, 1024);
          uint64_t db = make_desc(sb + kk * 2048, 8192, 1024);
          WG<BN>::mma(acc, da, db, (kb | kk) != 0);
        }
        wg_commit();
        if (kb > 0) {
          wg_wait<1>();
          int pst = (it - 1) % STAGES;
          if (lane < 2) mbar_arrive_cluster(bars + 8 * (STAGES + pst), lane);
        }
      }
      wg_wait<0>();
      { int pst = (it - 1) % STAGES; if (lane < 2) mbar_arrive_cluster(bars + 8 * (STAGES + pst), lane); }
      int row0 = tm * 128 + wg * 64 + (warp & 3) * 16 + g;
      int sel0 = -1, sel1 = -1;
      if (EPI == 1) { sel0 = g_sel[0]; sel1 = g_sel[1]; }
#pragma unroll
      for (int half = 0; half < 2; half++) {
        int row = row0 + half * 8;
#pragma unroll
        for (int q = 0; q < BN / 32; q++) {
          uint32_t v[4];
#pragma unroll
          for (int tt = 0; tt < 4; tt++) v[tt] = pack2(acc[(q * 4 + tt) * 4 + half * 2], acc[(q * 4 + tt) * 4 + half * 2 + 1]);
          quad_transpose(v, c);
          int col = tn * BN + q * 32 + c * 8;
          if (EPI == 0) {
            __stcs(reinterpret_cast<uint4*>(outp + (size_t)row * NQKV + col), make_uint4(v[0], v[1], v[2], v[3]));
          } else {
            uint4 xv = *reinterpret_cast<const uint4*>(xin + (size_t)row * DM + col);
            uint4 bv = *reinterpret_cast<const uint4*>(g_xn + (size_t)row * DM + col);
            if (row == sel0 || row == sel1) {
              const float* u = &g_upd[row == sel0 ? 0 : 1][col];
              bv.x = pack2(bflo(bv.x) + u[0], bfhi(bv.x) + u[1]);
              bv.y = pack2(bflo(bv.y) + u[2], bfhi(bv.y) + u[3]);
              bv.z = pack2(bflo(bv.z) + u[4], bfhi(bv.z) + u[5]);
              bv.w = pack2(bflo(bv.w) + u[6], bfhi(bv.w) + u[7]);
            }
            uint4 o = make_uint4(add3(v[0], xv.x, bv.x), add3(v[1], xv.y, bv.y), add3(v[2], xv.z, bv.z), add3(v[3], xv.w, bv.w));
            *reinterpret_cast<uint4*>(outp + (size_t)row * DM + col) = o;
          }
        }
      }
    }
  }
  cluster_sync();
}

#define RK 10
#define SK (16 - RK)
#define TP 272
#define OFF_WQS 0
#define OFF_MEMT (OFF_WQS + 8 * SK * 3 * 512)
#define OFF_RED (OFF_MEMT + 16384)
#define OFF_QKVM (OFF_RED + 12288)
#define OFF_TOK (OFF_QKVM + 6144)
#define TOK_BYTES (72 * TP)
#define OFF_SA (OFF_TOK + 2 * TOK_BYTES)
#define OFF_BAR (OFF_SA + 8 * TP)
#define CH_END (OFF_BAR + 64)
#define CH_STG2 (131072)
#define CH_SMEM (196608 + 1024)
static_assert(CH_END <= CH_SMEM, "smem");

__device__ void moe_part(int m, const bf16* __restrict__ wg, const bf16* __restrict__ wu, const bf16* __restrict__ wd, uint8_t* smem);

__device__ __forceinline__ void bulk_copy(uint32_t dst, const void* src, uint32_t bytes, uint32_t bar) {
  asm volatile("cp.async.bulk.shared::cluster.global.mbarrier::complete_tx::bytes [%0],[%1],%2,[%3];"
               ::"r"(dst), "l"(src), "r"(bytes), "r"(bar) : "memory");
}
__device__ __forceinline__ void st_pub128(void* p, uint32_t v) {
  asm volatile("st.relaxed.gpu.global.v4.u32 [%0],{%1,%1,%1,%1};" ::"l"(p), "r"(v) : "memory");
}
__device__ __forceinline__ void sts128(uint32_t addr, const uint4& v) {
  asm volatile("st.shared.v4.u32 [%0],{%1,%2,%3,%4};" ::"r"(addr), "r"(v.x), "r"(v.y), "r"(v.z), "r"(v.w) : "memory");
}

#define POLL_MAX (1 << 22)
__device__ __forceinline__ uint32_t clk32() { uint32_t c; asm volatile("mov.u32 %0,%%clock;" : "=r"(c)); return c; }
__device__ __forceinline__ void wait_until(uint32_t t0, uint32_t d) { while (clk32() - t0 < d) {} }
#define DLY_DEC 48u

__device__ __forceinline__ float ex2f(float x) { float y; asm("ex2.approx.ftz.f32 %0,%1;" : "=f"(y) : "f"(x)); return y; }
__device__ __forceinline__ float rcpf(float x) { float y; asm("rcp.approx.ftz.f32 %0,%1;" : "=f"(y) : "f"(x)); return y; }
template <bool TOK>
__device__ __forceinline__ void attn8(uint32_t sb, uint32_t tok, int lane, int wq4, int tr, bf16* otok_row) {
  const int g = lane >> 2, c = lane & 3;
  float sc[5][4];
#pragma unroll
  for (int n = 0; n < 5; n++)
#pragma unroll
    for (int i = 0; i < 4; i++) sc[n][i] = 0.f;
  const uint32_t tokrow = tok + (lane & 7) * TP + (lane >> 3) * 16;
  const uint32_t qaddr = TOK ? (tok + (64 + (lane & 7)) * TP + (lane >> 4) * 16) : (sb + OFF_QKVM + ((lane & 7) + 8 * (lane >> 4)) * 16);
#pragma unroll
  for (int kp = 0; kp < 4; kp++) {
    uint32_t q0[4], q1[4], km[4], kt[4][4];
    if (TOK) {
      ldsm4(q0[0], q0[1], q0[2], q0[3], qaddr + 64 * kp);
      ldsm4(q1[0], q1[1], q1[2], q1[3], qaddr + 64 * kp + 32);
    } else {
      ldsm4t(q0[0], q0[1], q0[2], q0[3], qaddr + 512 * kp);
      ldsm4t(q1[0], q1[1], q1[2], q1[3], qaddr + 512 * kp + 256);
    }
    ldsm4t(km[0], km[1], km[2], km[3], sb + OFF_QKVM + (128 + 32 * kp + lane) * 16);
#pragma unroll
    for (int n = 0; n < 4; n++) ldsm4(kt[n][0], kt[n][1], kt[n][2], kt[n][3], tokrow + 8 * n * TP + 64 * kp);
    mma16816(sc[0], q0[0], q0[1], q0[2], q0[3], km[0], km[1]);
#pragma unroll
    for (int n = 0; n < 4; n++) mma16816(sc[n + 1], q0[0], q0[1], q0[2], q0[3], kt[n][0], kt[n][1]);
    mma16816(sc[0], q1[0], q1[1], q1[2], q1[3], km[2], km[3]);
#pragma unroll
    for (int n = 0; n < 4; n++) mma16816(sc[n + 1], q1[0], q1[1], q1[2], q1[3], kt[n][2], kt[n][3]);
  }
  uint32_t vma[4], vmb[4], vt[4][4];
  ldsm4(vma[0], vma[1], vma[2], vma[3], sb + OFF_QKVM + (256 + 32 * wq4 + lane) * 16);
  ldsm4(vmb[0], vmb[1], vmb[2], vmb[3], sb + OFF_QKVM + (256 + 32 * wq4 + (lane ^ 8)) * 16);
#pragma unroll
  for (int n = 0; n < 4; n++) ldsm4t(vt[n][0], vt[n][1], vt[n][2], vt[n][3], tok + (32 + lane) * TP + (32 * wq4 + 8 * n) * 2);
  const float scale = 0.08838834764831845f;
  float m0 = -3.0e38f;
#pragma unroll
  for (int n = 0; n < 5; n++) {
    uint32_t p1 = pack2(sc[n][0], sc[n][1]);
    uint32_t p2 = pack2(bflo(p1) * scale, bfhi(p1) * scale);
    sc[n][0] = bflo(p2);
    sc[n][1] = bfhi(p2);
    if (TOK && n > 0) {
      int kt = 8 * (n - 1) + 2 * c;
      if (kt > tr) sc[n][0] = -1.0e9f;
      if (kt + 1 > tr) sc[n][1] = -1.0e9f;
    }
    m0 = fmaxf(m0, fmaxf(sc[n][0], sc[n][1]));
  }
  m0 = fmaxf(m0, __shfl_xor_sync(0xffffffffu, m0, 1));
  m0 = fmaxf(m0, __shfl_xor_sync(0xffffffffu, m0, 2));
  const float l2e = 1.4426950408889634f;
  float s0 = 0.f;
#pragma unroll
  for (int n = 0; n < 5; n++) {
    sc[n][0] = ex2f((sc[n][0] - m0) * l2e);
    sc[n][1] = ex2f((sc[n][1] - m0) * l2e);
    s0 += sc[n][0] + sc[n][1];
  }
  s0 += __shfl_xor_sync(0xffffffffu, s0, 1);
  s0 += __shfl_xor_sync(0xffffffffu, s0, 2);
  const float i0 = rcpf(s0);
  uint32_t pp[5];
#pragma unroll
  for (int n = 0; n < 5; n++) pp[n] = pack2(sc[n][0] * i0, sc[n][1] * i0);
  float o[4][4];
#pragma unroll
  for (int n = 0; n < 4; n++) {
#pragma unroll
    for (int i = 0; i < 4; i++) o[n][i] = 0.f;
    mma16816(o[n], pp[1], pp[1], pp[2], pp[2], vt[n][0], vt[n][1]);
  }
#pragma unroll
  for (int n = 0; n < 4; n++) mma16816(o[n], pp[3], pp[3], pp[4], pp[4], vt[n][2], vt[n][3]);
  mma16816(o[0], pp[0], 0u, 0u, 0u, vma[0], vma[1]);
  mma16816(o[1], pp[0], 0u, 0u, 0u, vmb[0], vmb[1]);
  mma16816(o[2], pp[0], 0u, 0u, 0u, vma[2], vma[3]);
  mma16816(o[3], pp[0], 0u, 0u, 0u, vmb[2], vmb[3]);
#pragma unroll
  for (int n = 0; n < 4; n++) {
    const int e = 32 * wq4 + 8 * n + 2 * c;
    if (TOK) *reinterpret_cast<uint32_t*>(otok_row + e) = pack2(o[n][0], o[n][1]);
    else asm volatile("st.shared.u32 [%0],%1;" ::"r"(sb + OFF_SA + g * TP + e * 2), "r"(pack2(o[n][0], o[n][1])) : "memory");
  }
}

__global__ void __launch_bounds__(256, 1)
chain_kernel(const bf16* __restrict__ mem0, const bf16* __restrict__ Wq, const bf16* __restrict__ Wk, const bf16* __restrict__ Wv,
             const bf16* __restrict__ Wo, const bf16* __restrict__ wgate, const bf16* __restrict__ wup, const bf16* __restrict__ wdown) {
  extern __shared__ __align__(1024) uint8_t smem[];
  const int cta = blockIdx.x, t = threadIdx.x, warp = t >> 5, lane = t & 31;
  if (cta >= 128) {
    moe_part(cta - 128, wgate, wup, wdown, smem);
    return;
  }
  const int h = cta >> 2, j = cta & 3;
  const int g = lane >> 2, c = lane & 3;
  const uint32_t sb = smem_u32(smem);
  const int mg = warp & 1, kq = warp >> 1;

  uint32_t wq[RK][3][4];
  uint32_t wo[2][8][4];
  {
    for (int i = t; i < 128 * 4; i += 256)
      asm volatile("prefetch.global.L2 [%0];" ::"l"(Wo + (size_t)(h * 128 + (i >> 2)) * DM + 256 * j + (i & 3) * 64));
    for (int i = t; i < 3 * 1024 * 4; i += 256) {
      int which = i >> 12, k = (i >> 2) & 1023, ch = i & 3;
      const bf16* W = which == 0 ? Wq : (which == 1 ? Wk : Wv);
      cp_async16(sb + (which * 1024 + k) * 64 + ch * 16, W + (size_t)k * HD + h * 128 + 32 * j + ch * 8);
    }
    cp_commit(); cp_wait<0>();
    __syncthreads();
    uint32_t tmp[SK][3][4];
#pragma unroll
    for (int ks = 0; ks < 16; ks++) {
#pragma unroll
      for (int tt = 0; tt < 3; tt++) {
        int tile = 3 * mg + tt;
        int which = tile >> 1, ch = tile & 1;
        int k = (16 * kq + ks) * 16 + (lane & 7) + 8 * (lane >> 4);
        uint32_t addr = sb + (which * 1024 + k) * 64 + ch * 32 + 16 * ((lane >> 3) & 1);
        if (ks < RK) ldsm4t(wq[ks][tt][0], wq[ks][tt][1], wq[ks][tt][2], wq[ks][tt][3], addr);
        else ldsm4t(tmp[ks - RK][tt][0], tmp[ks - RK][tt][1], tmp[ks - RK][tt][2], tmp[ks - RK][tt][3], addr);
      }
    }
    __syncthreads();
#pragma unroll
    for (int ks = 0; ks < SK; ks++)
#pragma unroll
      for (int tt = 0; tt < 3; tt++)
        *reinterpret_cast<uint4*>(smem + OFF_WQS + (((warp * SK + ks) * 3 + tt) * 32 + lane) * 16) =
            make_uint4(tmp[ks][tt][0], tmp[ks][tt][1], tmp[ks][tt][2], tmp[ks][tt][3]);
    for (int i = t; i < 128 * 32; i += 256) {
      int e = i >> 5, ch = i & 31;
      cp_async16(sb + CH_STG2 + e * 512 + ch * 16, Wo + (size_t)(h * 128 + e) * DM + 256 * j + ch * 8);
    }
    cp_commit(); cp_wait<0>();
    __syncthreads();
#pragma unroll
    for (int tt = 0; tt < 2; tt++)
#pragma unroll
      for (int ks = 0; ks < 8; ks++) {
        int e = 16 * ks + (lane & 7) + 8 * (lane >> 4);
        uint32_t addr = sb + CH_STG2 + e * 512 + (32 * warp + 16 * tt + 8 * ((lane >> 3) & 1)) * 2;
        ldsm4t(wo[tt][ks][0], wo[tt][ks][1], wo[tt][ks][2], wo[tt][ks][3], addr);
      }
    if (t == 0) {
      mbar_init(sb + OFF_BAR, 1); mbar_init(sb + OFF_BAR + 8, 1);
      asm volatile("fence.mbarrier_init.release.cluster;" ::: "memory");
    }
    __syncthreads();
    asm volatile("fence.proxy.async.shared::cta;" ::: "memory");
  }
  auto prefetch_tok = [&](int s) {
    const int i = t - 192;
    const uint32_t dst = sb + OFF_TOK + (s & 1) * TOK_BYTES + (i >> 4) * TP + (i & 15) * 16;
    const bf16* src = g_qkv + (size_t)(s * 32 + (i >> 4)) * NQKV + HD + h * 128 + (i & 15) * 8;
#pragma unroll
    for (int r = 0; r < 8; r++) {
      cp_async16(dst + 4 * r * TP, src + (size_t)4 * r * NQKV);
      cp_async16(dst + (32 + 4 * r) * TP, src + (size_t)4 * r * NQKV + HD);
    }
    cp_async16(dst + 64 * TP, src + (size_t)(8 * j) * NQKV - HD);
    cp_async16(dst + 68 * TP, src + (size_t)(8 * j + 4) * NQKV - HD);
    cp_commit();
  };
  auto side_work = [&](int s) {
    if (warp >= 6) {
      prefetch_tok(s + 1);
    } else {
      const int slot2 = (s + 2) & 3;
      const int i = t - 128;
      st_pub128(&g_bufA[slot2][cta][i], SENT);
      if (i < 32) st_pub128(&g_bufA[slot2][cta][64 + i], SENT);
      if (i < 8) st_pub128(&g_bufC[slot2][8 * cta + i], SENT);
      uint4* bb = &g_bufB[slot2][32 * j + (i >> 1)][0][0] + 2 * h + (i & 1);
#pragma unroll
      for (int col = 0; col < 8; col++) st_pub128(bb + 64 * col, SENT);
    }
  };
  if (warp >= 6) prefetch_tok(0);
  for (int i = t; i < 8 * 1024; i += 256) {
    int r = i >> 10, k = i & 1023;
    reinterpret_cast<bf16*>(smem + OFF_MEMT)[k * 8 + r] = mem0[i];
  }
  __syncthreads();
  uint32_t p2dst0, p2dst1;
  {
    int p = t, jj = p / 96, f = p % 96;
    p2dst0 = sb + OFF_QKVM + ((f >> 5) * 128 + 32 * jj + (f & 31)) * 16;
    p = 256 + (t & 127); jj = p / 96; f = p % 96;
    p2dst1 = sb + OFF_QKVM + ((f >> 5) * 128 + 32 * jj + (f & 31)) * 16;
  }
  const int p0idx = 256 * kq + 128 * mg + lane;
  uint32_t tpub = 0;
  const uint32_t dA = DLY_A, dB = DLY_B, dC = DLY_C;
  TS(0);
  for (int s = 0; s < NSEG; s++) {
    const int slot = s & 3, slot2 = (s + 2) & 3;
    if (s > 0) {
      const uint4* src = &g_bufC[(s - 1) & 3][p0idx];
      uint4 v[4];
      wait_until(tpub, dC);
#pragma unroll
      for (int i = 0; i < 4; i++) v[i] = ld_poll(src + 32 * i);
      int it = 0;
      while (!__all_sync(0xffffffffu, pkt_ok(v[0]) && pkt_ok(v[1]) && pkt_ok(v[2]) && pkt_ok(v[3])) && ++it < POLL_MAX) {
#pragma unroll
        for (int i = 0; i < 4; i++)
          if (!pkt_ok(v[i])) v[i] = ld_poll(src + 32 * i);
      }
#pragma unroll
      for (int i = 0; i < 4; i++) sts128(sb + OFF_MEMT + (p0idx + 32 * i) * 16, v[i]);
      TS(1);
      asm volatile("bar.sync %0, 64;" ::"r"(1 + kq) : "memory");
      TS(2);
    }
    {
      float acc[2][3][4];
#pragma unroll
      for (int a = 0; a < 2; a++)
#pragma unroll
        for (int tt = 0; tt < 3; tt++)
#pragma unroll
          for (int i = 0; i < 4; i++) acc[a][tt][i] = 0.f;
      uint4 sa[SK][3];
#pragma unroll
      for (int kp = 0; kp < 8; kp++) {
        uint32_t b0, b1, b2, b3;
        ldsm4t(b0, b1, b2, b3, sb + OFF_MEMT + ((16 * kq + 2 * kp) * 16 + lane) * 16);
#pragma unroll
        for (int u = 0; u < 2; u++) {
          int ks = 2 * (kp + 1) + u;
          if (ks >= RK && ks < 16) {
#pragma unroll
            for (int tt = 0; tt < 3; tt++)
              sa[ks - RK][tt] = *reinterpret_cast<const uint4*>(smem + OFF_WQS + (((warp * SK + (ks - RK)) * 3 + tt) * 32 + lane) * 16);
          }
        }
#pragma unroll
        for (int u = 0; u < 2; u++) {
          int ks = 2 * kp + u;
#pragma unroll
          for (int tt = 0; tt < 3; tt++) {
            if (ks < RK) mma16816(acc[u][tt], wq[ks][tt][0], wq[ks][tt][1], wq[ks][tt][2], wq[ks][tt][3], u ? b2 : b0, u ? b3 : b1);
            else mma16816(acc[u][tt], sa[ks - RK][tt].x, sa[ks - RK][tt].y, sa[ks - RK][tt].z, sa[ks - RK][tt].w, u ? b2 : b0, u ? b3 : b1);
          }
        }
      }
#pragma unroll
      for (int tt = 0; tt < 3; tt++)
        *reinterpret_cast<float4*>(smem + OFF_RED + ((kq * 6 + 3 * mg + tt) * 32 + lane) * 16) =
            make_float4(acc[0][tt][0] + acc[1][tt][0], acc[0][tt][1] + acc[1][tt][1], acc[0][tt][2] + acc[1][tt][2], acc[0][tt][3] + acc[1][tt][3]);
    }
    TS(3);
    __syncthreads();
    TS(4);
    if (warp < 6) {
      float4 r = *reinterpret_cast<const float4*>(smem + OFF_RED + ((0 * 6 + warp) * 32 + lane) * 16);
#pragma unroll
      for (int q = 1; q < 4; q++) {
        float4 x = *reinterpret_cast<const float4*>(smem + OFF_RED + ((q * 6 + warp) * 32 + lane) * 16);
        r.x += x.x; r.y += x.y; r.z += x.z; r.w += x.w;
      }
      uint32_t* dst = reinterpret_cast<uint32_t*>(&g_bufA[slot][cta][16 * warp + g]) + c;
      st_pub32(dst, desent(pack2(r.x, r.y)));
      st_pub32(dst + 32, desent(pack2(r.z, r.w)));
    }
    tpub = clk32();
    {
      const uint4* src = &g_bufA[slot][4 * h][t];
      wait_until(tpub, dA);
      uint4 v0 = ld_poll(src);
      uint4 v1 = make_uint4(0, 0, 0, 0);
      if (t < 128) v1 = ld_poll(src + 256);
      int it = 0;
      while (!__all_sync(0xffffffffu, pkt_ok(v0) && pkt_ok(v1)) && ++it < POLL_MAX) {
        if (!pkt_ok(v0)) v0 = ld_poll(src);
        if (!pkt_ok(v1)) v1 = ld_poll(src + 256);
      }
      sts128(p2dst0, v0);
      if (t < 128) sts128(p2dst1, v1);
    }
    TS(5);
    if (warp >= 6) cp_wait<0>();
    __syncthreads();
    TS(6);
    const uint32_t tok = sb + OFF_TOK + (s & 1) * TOK_BYTES;
    if (s < NSEG - 1) {
      if (warp < 4) attn8<false>(sb, tok, lane, warp, 0, nullptr);
      else if (VAR == 1 || VAR == 3) side_work(s);
      else if (VAR == 4) attn8<true>(sb, tok, lane, warp - 4, 8 * j + g, g_otok + (size_t)(s * 32 + 8 * j + g) * HD + h * 128);
      TS(7);
      __syncthreads();
      TS(8);
      {
        float acc[2][2][4];
#pragma unroll
        for (int a = 0; a < 2; a++)
#pragma unroll
          for (int tt = 0; tt < 2; tt++)
#pragma unroll
            for (int i = 0; i < 4; i++) acc[a][tt][i] = 0.f;
        uint32_t b[4][4];
#pragma unroll
        for (int kp = 0; kp < 4; kp++) ldsm4(b[kp][0], b[kp][1], b[kp][2], b[kp][3], sb + OFF_SA + (lane & 7) * TP + (32 * kp + 8 * (lane >> 3)) * 2);
#pragma unroll
        for (int kp = 0; kp < 4; kp++) {
#pragma unroll
          for (int tt = 0; tt < 2; tt++) {
            mma16816(acc[0][tt], wo[tt][2 * kp][0], wo[tt][2 * kp][1], wo[tt][2 * kp][2], wo[tt][2 * kp][3], b[kp][0], b[kp][1]);
            mma16816(acc[1][tt], wo[tt][2 * kp + 1][0], wo[tt][2 * kp + 1][1], wo[tt][2 * kp + 1][2], wo[tt][2 * kp + 1][3], b[kp][2], b[kp][3]);
          }
        }
        const int off = (g * 32 + h) * 4 + c;
#pragma unroll
        for (int tt = 0; tt < 2; tt++) {
          int r0 = 32 * j + 4 * warp + 2 * tt;
          uint32_t x0 = __float_as_uint(acc[0][tt][0] + acc[1][tt][0]), x1 = __float_as_uint(acc[0][tt][1] + acc[1][tt][1]);
          uint32_t x2 = __float_as_uint(acc[0][tt][2] + acc[1][tt][2]), x3 = __float_as_uint(acc[0][tt][3] + acc[1][tt][3]);
          x0 = x0 == SENT ? 0x7FFFFFFFu : x0; x1 = x1 == SENT ? 0x7FFFFFFFu : x1;
          x2 = x2 == SENT ? 0x7FFFFFFFu : x2; x3 = x3 == SENT ? 0x7FFFFFFFu : x3;
          st_pub64(reinterpret_cast<uint2*>(&g_bufB[slot][r0][0][0]) + off, x0, x1);
          st_pub64(reinterpret_cast<uint2*>(&g_bufB[slot][r0 + 1][0][0]) + off, x2, x3);
        }
        tpub = clk32();
      }
      if ((VAR == 2 || VAR == 3) && warp >= 4) attn8<true>(sb, tok, lane, warp - 4, 8 * j + g, g_otok + (size_t)(s * 32 + 8 * j + g) * HD + h * 128);
      TS(9);
      {
        const uint4* src = &g_bufB[slot][cta][0][0] + 64 * warp + 2 * lane;
        wait_until(tpub, dB);
        uint4 v0 = ld_poll(src), v1 = ld_poll(src + 1);
        int it = 0;
          while (!__all_sync(0xffffffffu, pkt_ok(v0) && pkt_ok(v1)) && ++it < POLL_MAX) {
            if (!pkt_ok(v0)) v0 = ld_poll(src);
          if (!pkt_ok(v1)) v1 = ld_poll(src + 1);
        }
        TS(10);
        const bool hi = lane & 16;
        float a0 = __uint_as_float(hi ? v1.x : v0.x), a1 = __uint_as_float(hi ? v1.y : v0.y);
        float a2 = __uint_as_float(hi ? v1.z : v0.z), a3 = __uint_as_float(hi ? v1.w : v0.w);
        float b0 = __uint_as_float(hi ? v0.x : v1.x), b1 = __uint_as_float(hi ? v0.y : v1.y);
        float b2 = __uint_as_float(hi ? v0.z : v1.z), b3 = __uint_as_float(hi ? v0.w : v1.w);
        a0 += __shfl_xor_sync(0xffffffffu, b0, 16); a1 += __shfl_xor_sync(0xffffffffu, b1, 16);
        a2 += __shfl_xor_sync(0xffffffffu, b2, 16); a3 += __shfl_xor_sync(0xffffffffu, b3, 16);
        const bool h8 = lane & 8;
        float k0 = h8 ? a2 : a0, k1 = h8 ? a3 : a1, s0 = h8 ? a0 : a2, s1 = h8 ? a1 : a3;
        k0 += __shfl_xor_sync(0xffffffffu, s0, 8); k1 += __shfl_xor_sync(0xffffffffu, s1, 8);
        const bool h4 = lane & 4;
        float z = h4 ? k1 : k0, zs = h4 ? k0 : k1;
        z += __shfl_xor_sync(0xffffffffu, zs, 4);
        z += __shfl_xor_sync(0xffffffffu, z, 2);
        z += __shfl_xor_sync(0xffffffffu, z, 1);
        float zo = __shfl_xor_sync(0xffffffffu, z, 4);
        if ((lane & 7) == 0) {
          uint32_t* d = reinterpret_cast<uint32_t*>(&g_bufC[slot][8 * cta + warp]) + (lane >> 3);
          st_pub32(d, desent(pack2(z, zo)));
        }
        tpub = clk32();
      }
    }
    if (warp >= 4) {
      if (s == NSEG - 1 || VAR == 1) attn8<true>(sb, tok, lane, warp - 4, 8 * j + g, g_otok + (size_t)(s * 32 + 8 * j + g) * HD + h * 128);
      if (s < NSEG - 1 && (VAR == 2 || VAR == 4)) side_work(s);
    }
    TS(11);
  }
}

__device__ void moe_part(int m, const bf16* __restrict__ wg, const bf16* __restrict__ wu, const bf16* __restrict__ wd, uint8_t* smem) {
  const int t = threadIdx.x, warp = t >> 5, lane = t & 31;
  float* xs = reinterpret_cast<float*>(smem);
  float* red = reinterpret_cast<float*>(smem + 8192);
  float* hs = reinterpret_cast<float*>(smem + 65536);
  __shared__ float bv[8];
  __shared__ int bi[8];
  __shared__ int sel[2];
  int first = -1;
  for (int pass = 0; pass < 2; pass++) {
    float best = -INFINITY; int bidx = 0x7fffffff;
    for (int i = t; i < S_LEN; i += 256) {
      float v = g_r[i];
      if (i == first) continue;
      if (v > best || (v == best && i < bidx) || bidx == 0x7fffffff) { best = v; bidx = i; }
    }
#pragma unroll
    for (int o = 16; o > 0; o >>= 1) {
      float ov = __shfl_xor_sync(0xffffffffu, best, o); int oi = __shfl_xor_sync(0xffffffffu, bidx, o);
      if (oi != 0x7fffffff && (bidx == 0x7fffffff || ov > best || (ov == best && oi < bidx))) { best = ov; bidx = oi; }
    }
    if (lane == 0) { bv[warp] = best; bi[warp] = bidx; }
    __syncthreads();
    if (t == 0) {
      float b = bv[0]; int ix = bi[0];
      for (int w = 1; w < 8; w++) if (bv[w] > b || (bv[w] == b && bi[w] < ix)) { b = bv[w]; ix = bi[w]; }
      sel[pass] = ix;
    }
    __syncthreads();
    first = sel[0];
  }
  const int s0 = sel[0], s1 = sel[1];
  for (int i = t; i < 2048; i += 256) xs[i] = __bfloat162float(g_xn[(size_t)(i < 1024 ? s0 : s1) * DM + (i & 1023)]);
  __syncthreads();
  {
    int cg = t % 112, kh = t / 112;
    float a[2][2][8];
#pragma unroll
    for (int i = 0; i < 8; i++) { a[0][0][i] = a[0][1][i] = a[1][0][i] = a[1][1][i] = 0.f; }
    if (kh < 2) {
      const bf16* pg = wg + (size_t)(kh * 512) * FF + 896 * m + cg * 8;
      const bf16* pu = wu + (size_t)(kh * 512) * FF + 896 * m + cg * 8;
#pragma unroll 8
      for (int k = 0; k < 512; k++) {
        uint4 gv = __ldg(reinterpret_cast<const uint4*>(pg + (size_t)k * FF));
        uint4 uv = __ldg(reinterpret_cast<const uint4*>(pu + (size_t)k * FF));
        float x0 = xs[kh * 512 + k], x1 = xs[1024 + kh * 512 + k];
        float gf[8] = {bflo(gv.x), bfhi(gv.x), bflo(gv.y), bfhi(gv.y), bflo(gv.z), bfhi(gv.z), bflo(gv.w), bfhi(gv.w)};
        float uf[8] = {bflo(uv.x), bfhi(uv.x), bflo(uv.y), bfhi(uv.y), bflo(uv.z), bfhi(uv.z), bflo(uv.w), bfhi(uv.w)};
#pragma unroll
        for (int i = 0; i < 8; i++) {
          a[0][0][i] += x0 * gf[i]; a[0][1][i] += x1 * gf[i];
          a[1][0][i] += x0 * uf[i]; a[1][1][i] += x1 * uf[i];
        }
      }
      if (kh == 1) {
#pragma unroll
        for (int i = 0; i < 8; i++) {
          red[(0 * 2 + 0) * 896 + cg * 8 + i] = a[0][0][i]; red[(0 * 2 + 1) * 896 + cg * 8 + i] = a[0][1][i];
          red[(1 * 2 + 0) * 896 + cg * 8 + i] = a[1][0][i]; red[(1 * 2 + 1) * 896 + cg * 8 + i] = a[1][1][i];
        }
      }
    }
    __syncthreads();
    if (kh == 0) {
#pragma unroll
      for (int i = 0; i < 8; i++) {
#pragma unroll
        for (int tk = 0; tk < 2; tk++) {
          float gq = bfr(a[0][tk][i] + red[(0 * 2 + tk) * 896 + cg * 8 + i]);
          float uq = bfr(a[1][tk][i] + red[(1 * 2 + tk) * 896 + cg * 8 + i]);
          float sg = bfr(gq / (1.0f + __expf(-gq)));
          g_h[tk][896 * m + cg * 8 + i] = __float2bfloat16_rn(sg * uq);
        }
      }
    }
    __threadfence();
    __syncthreads();
    if (t == 0) {
      atomicAdd(&g_moe_cnt, 1u);
      int it = 0;
      while (*reinterpret_cast<volatile unsigned*>(&g_moe_cnt) < 4u && ++it < (1 << 24)) {}
      __threadfence();
    }
    __syncthreads();
  }
  for (int i = t; i < 2 * FF; i += 256) {
    const volatile unsigned short* p = reinterpret_cast<const volatile unsigned short*>(&g_h[0][0]);
    hs[i] = __uint_as_float(((uint32_t)p[i]) << 16);
  }
  __syncthreads();
  {
    int cg = t & 31, ksl = t >> 5;
    float a[2][8];
#pragma unroll
    for (int i = 0; i < 8; i++) a[0][i] = a[1][i] = 0.f;
    const bf16* pd = wd + (size_t)(ksl * 448) * DM + 256 * m + cg * 8;
#pragma unroll 8
    for (int k = 0; k < 448; k++) {
      uint4 dv = __ldg(reinterpret_cast<const uint4*>(pd + (size_t)k * DM));
      float x0 = hs[ksl * 448 + k], x1 = hs[FF + ksl * 448 + k];
      float df[8] = {bflo(dv.x), bfhi(dv.x), bflo(dv.y), bfhi(dv.y), bflo(dv.z), bfhi(dv.z), bflo(dv.w), bfhi(dv.w)};
#pragma unroll
      for (int i = 0; i < 8; i++) { a[0][i] += x0 * df[i]; a[1][i] += x1 * df[i]; }
    }
#pragma unroll
    for (int i = 0; i < 8; i++) { red[(ksl * 2 + 0) * 256 + cg * 8 + i] = a[0][i]; red[(ksl * 2 + 1) * 256 + cg * 8 + i] = a[1][i]; }
    __syncthreads();
    for (int i = t; i < 512; i += 256) {
      int tk = i >> 8, col = i & 255;
      float y = 0.f;
#pragma unroll
      for (int q = 0; q < 8; q++) y += red[(q * 2 + tk) * 256 + col];
      float rr = g_r[tk == 0 ? s0 : s1];
      float sg = bfr(1.0f / (1.0f + __expf(-rr)));
      g_upd[tk][256 * m + col] = bfr(bfr(y) * sg);
    }
    if (m == 0 && t == 0) { g_sel[0] = s0; g_sel[1] = s1; }
  }
}

typedef CUresult (*EncodeFn)(CUtensorMap*, CUtensorMapDataType, cuuint32_t, void*, const cuuint64_t*, const cuuint64_t*,
                             const cuuint32_t*, const cuuint32_t*, CUtensorMapInterleave, CUtensorMapSwizzle,
                             CUtensorMapL2promotion, CUtensorMapFloatOOBfill);

static void make_map(EncodeFn enc, CUtensorMap* m, const void* ptr, uint64_t inner, uint64_t outer, uint32_t bi, uint32_t bo) {
  cuuint64_t dims[2] = {inner, outer};
  cuuint64_t strides[1] = {inner * 2};
  cuuint32_t box[2] = {bi, bo};
  cuuint32_t es[2] = {1, 1};
  enc(m, CU_TENSOR_MAP_DATA_TYPE_BFLOAT16, 2, const_cast<void*>(ptr), dims, strides, box, es, CU_TENSOR_MAP_INTERLEAVE_NONE,
      CU_TENSOR_MAP_SWIZZLE_128B, CU_TENSOR_MAP_L2_PROMOTION_L2_256B, CU_TENSOR_MAP_FLOAT_OOB_FILL_NONE);
}

extern "C" void kernel_launch(void* const* d_in, const int* in_sizes, int n_in, void* d_out, int out_size) {
  const bf16* x = (const bf16*)d_in[0];
  const bf16* mem0 = (const bf16*)d_in[1];
  const bf16* Wq = (const bf16*)d_in[2];
  const bf16* Wk = (const bf16*)d_in[3];
  const bf16* Wv = (const bf16*)d_in[4];
  const bf16* Wo = (const bf16*)d_in[5];
  const bf16* w_r = (const bf16*)d_in[8];
  const bf16* wg = (const bf16*)d_in[9];
  const bf16* wu = (const bf16*)d_in[10];
  const bf16* wd = (const bf16*)d_in[11];
  bf16* out = (bf16*)d_out;

  static EncodeFn enc = nullptr;
  static void *p_xn, *p_qkv, *p_otok;
  if (!enc) {
    cudaDriverEntryPointQueryResult qr;
    void* fn = nullptr;
    cudaGetDriverEntryPoint("cuTensorMapEncodeTiled", &fn, cudaEnableDefault, &qr);
    enc = (EncodeFn)fn;
    cudaGetSymbolAddress(&p_xn, g_xn);
    cudaGetSymbolAddress(&p_qkv, g_qkv);
    cudaGetSymbolAddress(&p_otok, g_otok);
    cudaFuncSetAttribute(gemm_kernel<256, 4, 0>, cudaFuncAttributeMaxDynamicSharedMemorySize, GemmSmem<256, 4>::TOTAL);
    cudaFuncSetAttribute(gemm_kernel<128, 6, 1>, cudaFuncAttributeMaxDynamicSharedMemorySize, GemmSmem<128, 6>::TOTAL);
    cudaFuncSetAttribute(chain_kernel, cudaFuncAttributeMaxDynamicSharedMemorySize, CH_SMEM);
  }
  CUtensorMap mA, mQ, mK, mV, mO, mWo;
  make_map(enc, &mA, p_xn, DM, S_LEN, 64, 128);
  make_map(enc, &mQ, Wq, HD, DM, 64, 64);
  make_map(enc, &mK, Wk, HD, DM, 64, 64);
  make_map(enc, &mV, Wv, HD, DM, 64, 64);
  make_map(enc, &mO, p_otok, HD, S_LEN, 64, 128);
  make_map(enc, &mWo, Wo, DM, HD, 64, 64);

  cudaStream_t st = cudaStreamPerThread;
  ln_kernel<<<256, 256, 0, st>>>(x, w_r);
  cudaLaunchAttribute cat[1];
  cat[0].id = cudaLaunchAttributeClusterDimension;
  cat[0].val.clusterDim.x = 2; cat[0].val.clusterDim.y = 1; cat[0].val.clusterDim.z = 1;
  cudaLaunchConfig_t cfg = {};
  cfg.gridDim = dim3(132); cfg.blockDim = dim3(288); cfg.dynamicSmemBytes = GemmSmem<256, 4>::TOTAL; cfg.stream = st;
  cfg.attrs = cat; cfg.numAttrs = 1;
  cudaLaunchKernelEx(&cfg, gemm_kernel<256, 4, 0>, mA, mQ, mK, mV, 16, 16, 16 * 48, (const bf16*)nullptr, (bf16*)p_qkv);
  chain_kernel<<<132, 256, CH_SMEM, st>>>(mem0, Wq, Wk, Wv, Wo, wg, wu, wd);
  cfg.gridDim = dim3(128); cfg.dynamicSmemBytes = GemmSmem<128, 6>::TOTAL;
  cudaLaunchKernelEx(&cfg, gemm_kernel<128, 6, 1>, mO, mWo, mWo, mWo, 64, 16, 16 * 8, x, out);
}
```

```cpp
#include <cuda_runtime.h>
#include <cuda_bf16.h>
#include <cuda.h>
#include <stdint.h>

typedef __nv_bfloat16 bf16;

#define S_LEN 2048
#define DM 1024
#define NH 32
#define DH 128
#define NSEG 64
#define SEGL 32
#define HD 4096
#define NQKV 12288
#define FF 3584
#define SENT 0xFFFFFFFFu

__device__ __align__(1024) bf16 g_xn[S_LEN * DM];
__device__ __align__(1024) bf16 g_qkv[(size_t)S_LEN * NQKV];
__device__ __align__(1024) bf16 g_otok[(size_t)S_LEN * HD];
__device__ float g_r[S_LEN];
__device__ __align__(128) uint4 g_bufA[4][128][96];
__device__ __align__(128) uint4 g_bufB[4][128][16][32];
__device__ __align__(128) uint4 g_bufC[4][1024];
__device__ __align__(128) bf16 g_h[2][FF];
__device__ float g_upd[2][DM];
__device__ int g_sel[2];
__device__ unsigned g_moe_cnt;
#define NOTOK 0
#define VAR 1
#define DLY_A 300u
#define DLY_B 800u
#define DLY_C 700u
#define TS(i)

__device__ __forceinline__ float bfr(float x) { return __bfloat162float(__float2bfloat16_rn(x)); }
__device__ __forceinline__ uint32_t pack2(float lo, float hi) {
  __nv_bfloat162 v = __floats2bfloat162_rn(lo, hi);
  return *reinterpret_cast<uint32_t*>(&v);
}
__device__ __forceinline__ float bflo(uint32_t v) { return __uint_as_float(v << 16); }
__device__ __forceinline__ float bfhi(uint32_t v) { return __uint_as_float(v & 0xFFFF0000u); }
__device__ __forceinline__ uint32_t smem_u32(const void* p) { return (uint32_t)__cvta_generic_to_shared(p); }

__device__ __forceinline__ uint4 ld_poll(const uint4* p) {
  uint4 v;
  asm volatile("ld.relaxed.gpu.global.v4.u32 {%0,%1,%2,%3},[%4];" : "=r"(v.x), "=r"(v.y), "=r"(v.z), "=r"(v.w) : "l"(p) : "memory");
  return v;
}
__device__ __forceinline__ void st_pub32(void* p, uint32_t v) {
  asm volatile("st.relaxed.gpu.global.u32 [%0],%1;" ::"l"(p), "r"(v) : "memory");
}
__device__ __forceinline__ void st_pub64(void* p, uint32_t a, uint32_t b) {
  asm volatile("st.relaxed.gpu.global.v2.u32 [%0],{%1,%2};" ::"l"(p), "r"(a), "r"(b) : "memory");
}
__device__ __forceinline__ bool pkt_ok(const uint4& v) { return v.x != SENT && v.y != SENT && v.z != SENT && v.w != SENT; }
__device__ __forceinline__ uint32_t desent(uint32_t v) { return v == SENT ? 0x7FFF7FFFu : v; }

__device__ __forceinline__ void ldsm4(uint32_t& r0, uint32_t& r1, uint32_t& r2, uint32_t& r3, uint32_t addr) {
  asm volatile("ldmatrix.sync.aligned.m8n8.x4.shared.b16 {%0,%1,%2,%3},[%4];" : "=r"(r0), "=r"(r1), "=r"(r2), "=r"(r3) : "r"(addr) : "memory");
}
__device__ __forceinline__ void ldsm4t(uint32_t& r0, uint32_t& r1, uint32_t& r2, uint32_t& r3, uint32_t addr) {
  asm volatile("ldmatrix.sync.aligned.m8n8.x4.trans.shared.b16 {%0,%1,%2,%3},[%4];" : "=r"(r0), "=r"(r1), "=r"(r2), "=r"(r3) : "r"(addr) : "memory");
}
__device__ __forceinline__ void mma16816(float (&d)[4], uint32_t a0, uint32_t a1, uint32_t a2, uint32_t a3, uint32_t b0, uint32_t b1) {
  asm volatile("mma.sync.aligned.m16n8k16.row.col.f32.bf16.bf16.f32 {%0,%1,%2,%3},{%4,%5,%6,%7},{%8,%9},{%0,%1,%2,%3};"
               : "+f"(d[0]), "+f"(d[1]), "+f"(d[2]), "+f"(d[3])
               : "r"(a0), "r"(a1), "r"(a2), "r"(a3), "r"(b0), "r"(b1));
}
__device__ __forceinline__ void cp_async16(uint32_t dst, const void* src) {
  asm volatile("cp.async.cg.shared.global [%0],[%1],16;" ::"r"(dst), "l"(src) : "memory");
}
__device__ __forceinline__ void cp_commit() { asm volatile("cp.async.commit_group;" ::: "memory"); }
template <int N>
__device__ __forceinline__ void cp_wait() { asm volatile("cp.async.wait_group %0;" ::"n"(N) : "memory"); }

__device__ __forceinline__ void mbar_init(uint32_t bar, uint32_t cnt) { asm volatile("mbarrier.init.shared::cta.b64 [%0],%1;" ::"r"(bar), "r"(cnt) : "memory"); }
__device__ __forceinline__ void mbar_expect_tx(uint32_t bar, uint32_t bytes) {
  asm volatile("mbarrier.arrive.expect_tx.shared::cta.b64 _,[%0],%1;" ::"r"(bar), "r"(bytes) : "memory");
}
__device__ __forceinline__ void mbar_arrive(uint32_t bar) { asm volatile("mbarrier.arrive.shared::cta.b64 _,[%0];" ::"r"(bar) : "memory"); }
__device__ __forceinline__ void mbar_wait(uint32_t bar, uint32_t parity) {
  asm volatile(
      "{\n.reg .pred p;\n"
      "WAIT_LOOP:\n"
      "mbarrier.try_wait.parity.shared::cta.b64 p,[%0],%1;\n"
      "@p bra WAIT_DONE;\n"
      "bra WAIT_LOOP;\n"
      "WAIT_DONE:\n}\n" ::"r"(bar), "r"(parity) : "memory");
}
__device__ __forceinline__ void tma_load2d(uint32_t dst, const CUtensorMap* tm, uint32_t bar, int c0, int c1) {
  asm volatile("cp.async.bulk.tensor.2d.shared::cluster.global.mbarrier::complete_tx::bytes [%0],[%1,{%3,%4}],[%2];"
               ::"r"(dst), "l"(tm), "r"(bar), "r"(c0), "r"(c1) : "memory");
}
__device__ __forceinline__ void tma_load2d_mc(uint32_t dst, const CUtensorMap* tm, uint32_t bar, int c0, int c1, uint16_t mask) {
  asm volatile("cp.async.bulk.tensor.2d.shared::cluster.global.mbarrier::complete_tx::bytes.multicast::cluster [%0],[%1,{%3,%4}],[%2],%5;"
               ::"r"(dst), "l"(tm), "r"(bar), "r"(c0), "r"(c1), "h"(mask) : "memory");
}
__device__ __forceinline__ void mbar_arrive_cluster(uint32_t bar, uint32_t cta) {
  asm volatile("{\n.reg .b32 ra;\nmapa.shared::cluster.u32 ra,%0,%1;\nmbarrier.arrive.shared::cluster.b64 _,[ra];\n}\n" ::"r"(bar), "r"(cta) : "memory");
}
__device__ __forceinline__ void cluster_sync() {
  asm volatile("barrier.cluster.arrive.release.aligned;\nbarrier.cluster.wait.acquire.aligned;\n" ::: "memory");
}
__device__ __forceinline__ void wg_fence() { asm volatile("wgmma.fence.sync.aligned;" ::: "memory"); }
__device__ __forceinline__ void wg_commit() { asm volatile("wgmma.commit_group.sync.aligned;" ::: "memory"); }
template <int N>
__device__ __forceinline__ void wg_wait() { asm volatile("wgmma.wait_group.sync.aligned %0;" ::"n"(N) : "memory"); }
__device__ __forceinline__ uint64_t make_desc(uint32_t addr, uint32_t lbo, uint32_t sbo) {
  return (uint64_t)((addr & 0x3FFFF) >> 4) | ((uint64_t)(lbo >> 4) << 16) | ((uint64_t)(sbo >> 4) << 32) | (1ull << 62);
}

__device__ __forceinline__ void wgmma_m64n256k16(float (&d)[128], uint64_t da, uint64_t db, int scaleD) {
  asm volatile(
    "{\n.reg .pred p;\nsetp.ne.b32 p, %130, 0;\n"
    "wgmma.mma_async.sync.aligned.m64n256k16.f32.bf16.bf16 "
    "{%0, %1, %2, %3, %4, %5, %6, %7, %8, %9, %10, %11, %12, %13, %14, %15, %16, %17, %18, %19, %20, %21, %22, %23, %24, %25, %26, %27, %28, %29, %30, %31, %32, %33, %34, %35, %36, %37, %38, %39, %40, %41, %42, %43, %44, %45, %46, %47, %48, %49, %50, %51, %52, %53, %54, %55, %56, %57, %58, %59, %60, %61, %62, %63, %64, %65, %66, %67, %68, %69, %70, %71, %72, %73, %74, %75, %76, %77, %78, %79, %80, %81, %82, %83, %84, %85, %86, %87, %88, %89, %90, %91, %92, %93, %94, %95, %96, %97, %98, %99, %100, %101, %102, %103, %104, %105, %106, %107, %108, %109, %110, %111, %112, %113, %114, %115, %116, %117, %118, %119, %120, %121, %122, %123, %124, %125, %126, %127}, %128, %129, p, 1, 1, 0, 1;\n}\n"
    : "+f"(d[0]), "+f"(d[1]), "+f"(d[2]), "+f"(d[3]), "+f"(d[4]), "+f"(d[5]), "+f"(d[6]), "+f"(d[7]), "+f"(d[8]), "+f"(d[9]), "+f"(d[10]), "+f"(d[11]), "+f"(d[12]), "+f"(d[13]), "+f"(d[14]), "+f"(d[15]), "+f"(d[16]), "+f"(d[17]), "+f"(d[18]), "+f"(d[19]), "+f"(d[20]), "+f"(d[21]), "+f"(d[22]), "+f"(d[23]), "+f"(d[24]), "+f"(d[25]), "+f"(d[26]), "+f"(d[27]), "+f"(d[28]), "+f"(d[29]), "+f"(d[30]), "+f"(d[31]), "+f"(d[32]), "+f"(d[33]), "+f"(d[34]), "+f"(d[35]), "+f"(d[36]), "+f"(d[37]), "+f"(d[38]), "+f"(d[39]), "+f"(d[40]), "+f"(d[41]), "+f"(d[42]), "+f"(d[43]), "+f"(d[44]), "+f"(d[45]), "+f"(d[46]), "+f"(d[47]), "+f"(d[48]), "+f"(d[49]), "+f"(d[50]), "+f"(d[51]), "+f"(d[52]), "+f"(d[53]), "+f"(d[54]), "+f"(d[55]), "+f"(d[56]), "+f"(d[57]), "+f"(d[58]), "+f"(d[59]), "+f"(d[60]), "+f"(d[61]), "+f"(d[62]), "+f"(d[63]), "+f"(d[64]), "+f"(d[65]), "+f"(d[66]), "+f"(d[67]), "+f"(d[68]), "+f"(d[69]), "+f"(d[70]), "+f"(d[71]), "+f"(d[72]), "+f"(d[73]), "+f"(d[74]), "+f"(d[75]), "+f"(d[76]), "+f"(d[77]), "+f"(d[78]), "+f"(d[79]), "+f"(d[80]), "+f"(d[81]), "+f"(d[82]), "+f"(d[83]), "+f"(d[84]), "+f"(d[85]), "+f"(d[86]), "+f"(d[87]), "+f"(d[88]), "+f"(d[89]), "+f"(d[90]), "+f"(d[91]), "+f"(d[92]), "+f"(d[93]), "+f"(d[94]), "+f"(d[95]), "+f"(d[96]), "+f"(d[97]), "+f"(d[98]), "+f"(d[99]), "+f"(d[100]), "+f"(d[101]), "+f"(d[102]), "+f"(d[103]), "+f"(d[104]), "+f"(d[105]), "+f"(d[106]), "+f"(d[107]), "+f"(d[108]), "+f"(d[109]), "+f"(d[110]), "+f"(d[111]), "+f"(d[112]), "+f"(d[113]), "+f"(d[114]), "+f"(d[115]), "+f"(d[116]), "+f"(d[117]), "+f"(d[118]), "+f"(d[119]), "+f"(d[120]), "+f"(d[121]), "+f"(d[122]), "+f"(d[123]), "+f"(d[124]), "+f"(d[125]), "+f"(d[126]), "+f"(d[127])
    : "l"(da), "l"(db), "r"(scaleD));
}

__device__ __forceinline__ void wgmma_m64n128k16(float (&d)[64], uint64_t da, uint64_t db, int scaleD) {
  asm volatile(
    "{\n.reg .pred p;\nsetp.ne.b32 p, %66, 0;\n"
    "wgmma.mma_async.sync.aligned.m64n128k16.f32.bf16.bf16 "
    "{%0, %1, %2, %3, %4, %5, %6, %7, %8, %9, %10, %11, %12, %13, %14, %15, %16, %17, %18, %19, %20, %21, %22, %23, %24, %25, %26, %27, %28, %29, %30, %31, %32, %33, %34, %35, %36, %37, %38, %39, %40, %41, %42, %43, %44, %45, %46, %47, %48, %49, %50, %51, %52, %53, %54, %55, %56, %57, %58, %59, %60, %61, %62, %63}, %64, %65, p, 1, 1, 0, 1;\n}\n"
    : "+f"(d[0]), "+f"(d[1]), "+f"(d[2]), "+f"(d[3]), "+f"(d[4]), "+f"(d[5]), "+f"(d[6]), "+f"(d[7]), "+f"(d[8]), "+f"(d[9]), "+f"(d[10]), "+f"(d[11]), "+f"(d[12]), "+f"(d[13]), "+f"(d[14]), "+f"(d[15]), "+f"(d[16]), "+f"(d[17]), "+f"(d[18]), "+f"(d[19]), "+f"(d[20]), "+f"(d[21]), "+f"(d[22]), "+f"(d[23]), "+f"(d[24]), "+f"(d[25]), "+f"(d[26]), "+f"(d[27]), "+f"(d[28]), "+f"(d[29]), "+f"(d[30]), "+f"(d[31]), "+f"(d[32]), "+f"(d[33]), "+f"(d[34]), "+f"(d[35]), "+f"(d[36]), "+f"(d[37]), "+f"(d[38]), "+f"(d[39]), "+f"(d[40]), "+f"(d[41]), "+f"(d[42]), "+f"(d[43]), "+f"(d[44]), "+f"(d[45]), "+f"(d[46]), "+f"(d[47]), "+f"(d[48]), "+f"(d[49]), "+f"(d[50]), "+f"(d[51]), "+f"(d[52]), "+f"(d[53]), "+f"(d[54]), "+f"(d[55]), "+f"(d[56]), "+f"(d[57]), "+f"(d[58]), "+f"(d[59]), "+f"(d[60]), "+f"(d[61]), "+f"(d[62]), "+f"(d[63])
    : "l"(da), "l"(db), "r"(scaleD));
}

template <int BN> struct WG;
template <> struct WG<256> { static __device__ __forceinline__ void mma(float (&d)[128], uint64_t a, uint64_t b, int s) { wgmma_m64n256k16(d, a, b, s); } };
template <> struct WG<128> { static __device__ __forceinline__ void mma(float (&d)[64], uint64_t a, uint64_t b, int s) { wgmma_m64n128k16(d, a, b, s); } };

__global__ void __launch_bounds__(256) ln_kernel(const bf16* __restrict__ x, const bf16* __restrict__ w_r) {
  int warp = threadIdx.x >> 5, lane = threadIdx.x & 31;
  int row = blockIdx.x * 8 + warp;
  const uint4* xp = reinterpret_cast<const uint4*>(x + (size_t)row * DM);
  uint4 v[4];
#pragma unroll
  for (int i = 0; i < 4; i++) v[i] = xp[lane + 32 * i];
  float f[32];
#pragma unroll
  for (int i = 0; i < 4; i++) {
    f[8 * i + 0] = bflo(v[i].x); f[8 * i + 1] = bfhi(v[i].x);
    f[8 * i + 2] = bflo(v[i].y); f[8 * i + 3] = bfhi(v[i].y);
    f[8 * i + 4] = bflo(v[i].z); f[8 * i + 5] = bfhi(v[i].z);
    f[8 * i + 6] = bflo(v[i].w); f[8 * i + 7] = bfhi(v[i].w);
  }
  float s = 0.f;
#pragma unroll
  for (int i = 0; i < 32; i++) s += f[i];
#pragma unroll
  for (int o = 16; o > 0; o >>= 1) s += __shfl_xor_sync(0xffffffffu, s, o);
  float mean = s * (1.0f / DM);
  float q = 0.f;
#pragma unroll
  for (int i = 0; i < 32; i++) { float d = f[i] - mean; q += d * d; }
#pragma unroll
  for (int o = 16; o > 0; o >>= 1) q += __shfl_xor_sync(0xffffffffu, q, o);
  float var = bfr(q * (1.0f / DM));
  float mb = bfr(mean);
  float den = bfr(sqrtf(bfr(var + 1e-5f)));
  const uint4* wp = reinterpret_cast<const uint4*>(w_r);
  uint4* op = reinterpret_cast<uint4*>(g_xn + (size_t)row * DM);
  float r = 0.f;
#pragma unroll
  for (int i = 0; i < 4; i++) {
    uint4 w = wp[lane + 32 * i];
    float y[8];
#pragma unroll
    for (int k = 0; k < 8; k++) y[k] = bfr(bfr(f[8 * i + k] - mb) / den);
    r += y[0] * bflo(w.x) + y[1] * bfhi(w.x) + y[2] * bflo(w.y) + y[3] * bfhi(w.y) + y[4] * bflo(w.z) + y[5] * bfhi(w.z) +
         y[6] * bflo(w.w) + y[7] * bfhi(w.w);
    op[lane + 32 * i] = make_uint4(pack2(y[0], y[1]), pack2(y[2], y[3]), pack2(y[4], y[5]), pack2(y[6], y[7]));
  }
#pragma unroll
  for (int o = 16; o > 0; o >>= 1) r += __shfl_xor_sync(0xffffffffu, r, o);
  if (lane == 0) g_r[row] = bfr(r);
  int gt = blockIdx.x * 256 + threadIdx.x;
  const uint4 sv = make_uint4(SENT, SENT, SENT, SENT);
  uint4* a = &g_bufA[0][0][0];
  for (int i = gt; i < 2 * 128 * 96; i += 65536) a[i] = sv;
  uint4* b = &g_bufB[0][0][0][0];
  for (int i = gt; i < 2 * 128 * 32 * 16; i += 65536) b[i] = sv;
  uint4* c = &g_bufC[0][0];
  for (int i = gt; i < 2 * 1024; i += 65536) c[i] = sv;
  if (gt == 0) g_moe_cnt = 0;
}

template <int BN, int STAGES>
struct GemmSmem {
  static constexpr int A_BYTES = 128 * 64 * 2;
  static constexpr int B_BYTES = 64 * BN * 2;
  static constexpr int STAGE_BYTES = A_BYTES + B_BYTES;
  static constexpr int TOTAL = STAGES * STAGE_BYTES + 1024 + 256;
};

__device__ __forceinline__ void quad_transpose(uint32_t (&v)[4], int c) {
  {
    uint32_t s0 = (c & 1) ? v[0] : v[1];
    uint32_t s1 = (c & 1) ? v[2] : v[3];
    uint32_t r0 = __shfl_xor_sync(0xffffffffu, s0, 1);
    uint32_t r1 = __shfl_xor_sync(0xffffffffu, s1, 1);
    if (c & 1) { v[0] = r0; v[2] = r1; } else { v[1] = r0; v[3] = r1; }
  }
  {
    uint32_t s0 = (c & 2) ? v[0] : v[2];
    uint32_t s1 = (c & 2) ? v[1] : v[3];
    uint32_t r0 = __shfl_xor_sync(0xffffffffu, s0, 2);
    uint32_t r1 = __shfl_xor_sync(0xffffffffu, s1, 2);
    if (c & 2) { v[0] = r0; v[1] = r1; } else { v[2] = r0; v[3] = r1; }
  }
}

__device__ __forceinline__ uint32_t add3(uint32_t a, uint32_t x, uint32_t b) {
  float lo = bfr(bflo(x) + bflo(a)) + bflo(b);
  float hi = bfr(bfhi(x) + bfhi(a)) + bfhi(b);
  return pack2(lo, hi);
}

template <int BN, int STAGES, int EPI>
__global__ void __launch_bounds__(288, 1)
gemm_kernel(const __grid_constant__ CUtensorMap tmA, const __grid_constant__ CUtensorMap tmB0,
            const __grid_constant__ CUtensorMap tmB1, const __grid_constant__ CUtensorMap tmB2,
            int kblocks, int tiles_m, int tiles_total, const bf16* __restrict__ xin, bf16* __restrict__ outp) {
  using SM = GemmSmem<BN, STAGES>;
  extern __shared__ uint8_t smem_raw[];
  uint32_t base = (smem_u32(smem_raw) + 1023) & ~1023u;
  uint32_t bars = base + STAGES * SM::STAGE_BYTES;
  int warp = threadIdx.x >> 5, lane = threadIdx.x & 31;
  uint32_t rank;
  asm volatile("mov.u32 %0,%%cluster_ctarank;" : "=r"(rank));
  const int cl = blockIdx.x >> 1, ncl = gridDim.x >> 1;
  const int pairs_m = tiles_m >> 1, pairs_total = tiles_total >> 1;
  if (threadIdx.x == 0) {
    for (int i = 0; i < STAGES; i++) { mbar_init(bars + 8 * i, 1); mbar_init(bars + 8 * (STAGES + i), 16); }
    asm volatile("fence.mbarrier_init.release.cluster;" ::: "memory");
  }
  __syncthreads();
  cluster_sync();
  if (warp == 8) {
    if (lane == 0) {
      int it = 0;
      for (int t = cl; t < pairs_total; t += ncl) {
        int tm = 2 * (t % pairs_m) + rank, tn = t / pairs_m;
        int n0 = tn * BN;
        const CUtensorMap* tb = &tmB0;
        if (EPI == 0) { int wsel = n0 >> 12; tb = wsel == 0 ? &tmB0 : (wsel == 1 ? &tmB1 : &tmB2); n0 &= 4095; }
        for (int kb = 0; kb < kblocks; kb++, it++) {
          int st = it % STAGES; uint32_t ph = (it / STAGES) & 1;
          mbar_wait(bars + 8 * (STAGES + st), ph ^ 1);
          uint32_t sa = base + st * SM::STAGE_BYTES, sb = sa + SM::A_BYTES;
          mbar_expect_tx(bars + 8 * st, SM::STAGE_BYTES);
          tma_load2d(sa, &tmA, bars + 8 * st, kb * 64, tm * 128);
#pragma unroll
          for (int i = 0; i < BN / 128; i++) {
            int bx = rank * (BN / 128) + i;
            tma_load2d_mc(sb + bx * 8192, tb, bars + 8 * st, n0 + bx * 64, kb * 64, (uint16_t)3);
          }
        }
      }
    }
    __syncwarp();
  } else {
    int wg = warp >> 2;
    int g = lane >> 2, c = lane & 3;
    int it = 0;
    float acc[BN / 2];
    for (int t = cl; t < pairs_total; t += ncl) {
      int tm = 2 * (t % pairs_m) + rank, tn = t / pairs_m;
      for (int kb = 0; kb < kblocks; kb++, it++) {
        int st = it % STAGES; uint32_t ph = (it / STAGES) & 1;
        mbar_wait(bars + 8 * st, ph);
        uint32_t sa = base + st * SM::STAGE_BYTES + wg * 8192, sb = base + st * SM::STAGE_BYTES + SM::A_BYTES;
        wg_fence();
#pragma unroll
        for (int kk = 0; kk < 4; kk++) {
          uint64_t da = make_desc(sa + kk * 32, 16, 1024);
          uint64_t db = make_desc(sb + kk * 2048, 8192, 1024);
          WG<BN>::mma(acc, da, db, (kb | kk) != 0);
        }
        wg_commit();
        if (kb > 0) {
          wg_wait<1>();
          int pst = (it - 1) % STAGES;
          if (lane < 2) mbar_arrive_cluster(bars + 8 * (STAGES + pst), lane);
        }
      }
      wg_wait<0>();
      { int pst = (it - 1) % STAGES; if (lane < 2) mbar_arrive_cluster(bars + 8 * (STAGES + pst), lane); }
      int row0 = tm * 128 + wg * 64 + (warp & 3) * 16 + g;
      int sel0 = -1, sel1 = -1;
      if (EPI == 1) { sel0 = g_sel[0]; sel1 = g_sel[1]; }
#pragma unroll
      for (int half = 0; half < 2; half++) {
        int row = row0 + half * 8;
#pragma unroll
        for (int q = 0; q < BN / 32; q++) {
          uint32_t v[4];
#pragma unroll
          for (int tt = 0; tt < 4; tt++) v[tt] = pack2(acc[(q * 4 + tt) * 4 + half * 2], acc[(q * 4 + tt) * 4 + half * 2 + 1]);
          quad_transpose(v, c);
          int col = tn * BN + q * 32 + c * 8;
          if (EPI == 0) {
            __stcs(reinterpret_cast<uint4*>(outp + (size_t)row * NQKV + col), make_uint4(v[0], v[1], v[2], v[3]));
          } else {
            uint4 xv = *reinterpret_cast<const uint4*>(xin + (size_t)row * DM + col);
            uint4 bv = *reinterpret_cast<const uint4*>(g_xn + (size_t)row * DM + col);
            if (row == sel0 || row == sel1) {
              const float* u = &g_upd[row == sel0 ? 0 : 1][col];
              bv.x = pack2(bflo(bv.x) + u[0], bfhi(bv.x) + u[1]);
              bv.y = pack2(bflo(bv.y) + u[2], bfhi(bv.y) + u[3]);
              bv.z = pack2(bflo(bv.z) + u[4], bfhi(bv.z) + u[5]);
              bv.w = pack2(bflo(bv.w) + u[6], bfhi(bv.w) + u[7]);
            }
            uint4 o = make_uint4(add3(v[0], xv.x, bv.x), add3(v[1], xv.y, bv.y), add3(v[2], xv.z, bv.z), add3(v[3], xv.w, bv.w));
            *reinterpret_cast<uint4*>(outp + (size_t)row * DM + col) = o;
          }
        }
      }
    }
  }
  cluster_sync();
}

#define RK 10
#define SK (16 - RK)
#define TP 272
#define OFF_WQS 0
#define OFF_MEMT (OFF_WQS + 8 * SK * 3 * 512)
#define OFF_RED (OFF_MEMT + 16384)
#define OFF_QKVM (OFF_RED + 12288)
#define OFF_TOK (OFF_QKVM + 6144)
#define TOK_BYTES (72 * TP)
#define OFF_SA (OFF_TOK + 2 * TOK_BYTES)
#define OFF_BAR (OFF_SA + 8 * TP)
#define CH_END (OFF_BAR + 64)
#define CH_STG2 (131072)
#define CH_SMEM (196608 + 1024)
static_assert(CH_END <= CH_SMEM, "smem");

__device__ void moe_part(int m, const bf16* __restrict__ wg, const bf16* __restrict__ wu, const bf16* __restrict__ wd, uint8_t* smem);

__device__ __forceinline__ void bulk_copy(uint32_t dst, const void* src, uint32_t bytes, uint32_t bar) {
  asm volatile("cp.async.bulk.shared::cluster.global.mbarrier::complete_tx::bytes [%0],[%1],%2,[%3];"
               ::"r"(dst), "l"(src), "r"(bytes), "r"(bar) : "memory");
}
__device__ __forceinline__ void st_pub128(void* p, uint32_t v) {
  asm volatile("st.relaxed.gpu.global.v4.u32 [%0],{%1,%1,%1,%1};" ::"l"(p), "r"(v) : "memory");
}
__device__ __forceinline__ void sts128(uint32_t addr, const uint4& v) {
  asm volatile("st.shared.v4.u32 [%0],{%1,%2,%3,%4};" ::"r"(addr), "r"(v.x), "r"(v.y), "r"(v.z), "r"(v.w) : "memory");
}

#define POLL_MAX (1 << 22)
__device__ __forceinline__ uint32_t clk32() { uint32_t c; asm volatile("mov.u32 %0,%%clock;" : "=r"(c)); return c; }
__device__ __forceinline__ void wait_until(uint32_t t0, uint32_t d) { while (clk32() - t0 < d) {} }
#define DLY_DEC 48u

__device__ __forceinline__ float ex2f(float x) { float y; asm("ex2.approx.ftz.f32 %0,%1;" : "=f"(y) : "f"(x)); return y; }
__device__ __forceinline__ float rcpf(float x) { float y; asm("rcp.approx.ftz.f32 %0,%1;" : "=f"(y) : "f"(x)); return y; }
template <bool TOK>
__device__ __forceinline__ void attn8(uint32_t sb, uint32_t tok, int lane, int wq4, int tr, bf16* otok_row) {
  const int g = lane >> 2, c = lane & 3;
  float sc[5][4];
#pragma unroll
  for (int n = 0; n < 5; n++)
#pragma unroll
    for (int i = 0; i < 4; i++) sc[n][i] = 0.f;
  const uint32_t tokrow = tok + (lane & 7) * TP + (lane >> 3) * 16;
  const uint32_t qaddr = TOK ? (tok + (64 + (lane & 7)) * TP + (lane >> 4) * 16) : (sb + OFF_QKVM + ((lane & 7) + 8 * (lane >> 4)) * 16);
#pragma unroll
  for (int kp = 0; kp < 4; kp++) {
    uint32_t q0[4], q1[4], km[4], kt[4][4];
    if (TOK) {
      ldsm4(q0[0], q0[1], q0[2], q0[3], qaddr + 64 * kp);
      ldsm4(q1[0], q1[1], q1[2], q1[3], qaddr + 64 * kp + 32);
    } else {
      ldsm4t(q0[0], q0[1], q0[2], q0[3], qaddr + 512 * kp);
      ldsm4t(q1[0], q1[1], q1[2], q1[3], qaddr + 512 * kp + 256);
    }
    ldsm4t(km[0], km[1], km[2], km[3], sb + OFF_QKVM + (128 + 32 * kp + lane) * 16);
#pragma unroll
    for (int n = 0; n < 4; n++) ldsm4(kt[n][0], kt[n][1], kt[n][2], kt[n][3], tokrow + 8 * n * TP + 64 * kp);
    mma16816(sc[0], q0[0], q0[1], q0[2], q0[3], km[0], km[1]);
#pragma unroll
    for (int n = 0; n < 4; n++) mma16816(sc[n + 1], q0[0], q0[1], q0[2], q0[3], kt[n][0], kt[n][1]);
    mma16816(sc[0], q1[0], q1[1], q1[2], q1[3], km[2], km[3]);
#pragma unroll
    for (int n = 0; n < 4; n++) mma16816(sc[n + 1], q1[0], q1[1], q1[2], q1[3], kt[n][2], kt[n][3]);
  }
  uint32_t vma[4], vmb[4], vt[4][4];
  ldsm4(vma[0], vma[1], vma[2], vma[3], sb + OFF_QKVM + (256 + 32 * wq4 + lane) * 16);
  ldsm4(vmb[0], vmb[1], vmb[2], vmb[3], sb + OFF_QKVM + (256 + 32 * wq4 + (lane ^ 8)) * 16);
#pragma unroll
  for (int n = 0; n < 4; n++) ldsm4t(vt[n][0], vt[n][1], vt[n][2], vt[n][3], tok + (32 + lane) * TP + (32 * wq4 + 8 * n) * 2);
  const float scale = 0.08838834764831845f;
  float m0 = -3.0e38f;
#pragma unroll
  for (int n = 0; n < 5; n++) {
    uint32_t p1 = pack2(sc[n][0], sc[n][1]);
    uint32_t p2 = pack2(bflo(p1) * scale, bfhi(p1) * scale);
    sc[n][0] = bflo(p2);
    sc[n][1] = bfhi(p2);
    if (TOK && n > 0) {
      int kt = 8 * (n - 1) + 2 * c;
      if (kt > tr) sc[n][0] = -1.0e9f;
      if (kt + 1 > tr) sc[n][1] = -1.0e9f;
    }
    m0 = fmaxf(m0, fmaxf(sc[n][0], sc[n][1]));
  }
  m0 = fmaxf(m0, __shfl_xor_sync(0xffffffffu, m0, 1));
  m0 = fmaxf(m0, __shfl_xor_sync(0xffffffffu, m0, 2));
  const float l2e = 1.4426950408889634f;
  float s0 = 0.f;
#pragma unroll
  for (int n = 0; n < 5; n++) {
    sc[n][0] = ex2f((sc[n][0] - m0) * l2e);
    sc[n][1] = ex2f((sc[n][1] - m0) * l2e);
    s0 += sc[n][0] + sc[n][1];
  }
  s0 += __shfl_xor_sync(0xffffffffu, s0, 1);
  s0 += __shfl_xor_sync(0xffffffffu, s0, 2);
  const float i0 = rcpf(s0);
  uint32_t pp[5];
#pragma unroll
  for (int n = 0; n < 5; n++) pp[n] = pack2(sc[n][0] * i0, sc[n][1] * i0);
  float o[4][4];
#pragma unroll
  for (int n = 0; n < 4; n++) {
#pragma unroll
    for (int i = 0; i < 4; i++) o[n][i] = 0.f;
    mma16816(o[n], pp[1], pp[1], pp[2], pp[2], vt[n][0], vt[n][1]);
  }
#pragma unroll
  for (int n = 0; n < 4; n++) mma16816(o[n], pp[3], pp[3], pp[4], pp[4], vt[n][2], vt[n][3]);
  mma16816(o[0], pp[0], 0u, 0u, 0u, vma[0], vma[1]);
  mma16816(o[1], pp[0], 0u, 0u, 0u, vmb[0], vmb[1]);
  mma16816(o[2], pp[0], 0u, 0u, 0u, vma[2], vma[3]);
  mma16816(o[3], pp[0], 0u, 0u, 0u, vmb[2], vmb[3]);
#pragma unroll
  for (int n = 0; n < 4; n++) {
    const int e = 32 * wq4 + 8 * n + 2 * c;
    if (TOK) *reinterpret_cast<uint32_t*>(otok_row + e) = pack2(o[n][0], o[n][1]);
    else asm volatile("st.shared.u32 [%0],%1;" ::"r"(sb + OFF_SA + g * TP + e * 2), "r"(pack2(o[n][0], o[n][1])) : "memory");
  }
}

__global__ void __launch_bounds__(256, 1)
chain_kernel(const bf16* __restrict__ mem0, const bf16* __restrict__ Wq, const bf16* __restrict__ Wk, const bf16* __restrict__ Wv,
             const bf16* __restrict__ Wo, const bf16* __restrict__ wgate, const bf16* __restrict__ wup, const bf16* __restrict__ wdown) {
  extern __shared__ __align__(1024) uint8_t smem[];
  const int cta = blockIdx.x, t = threadIdx.x, warp = t >> 5, lane = t & 31;
  if (cta >= 128) {
    moe_part(cta - 128, wgate, wup, wdown, smem);
    return;
  }
  const int h = cta >> 2, j = cta & 3;
  const int g = lane >> 2, c = lane & 3;
  const uint32_t sb = smem_u32(smem);
  const int mg = warp & 1, kq = warp >> 1;

  uint32_t wq[RK][3][4];
  uint32_t wo[2][8][4];
  {
    for (int i = t; i < 128 * 4; i += 256)
      asm volatile("prefetch.global.L2 [%0];" ::"l"(Wo + (size_t)(h * 128 + (i >> 2)) * DM + 256 * j + (i & 3) * 64));
    for (int i = t; i < 1024 * 12; i += 256) {
      int k = i / 12, ch = i - 12 * k;
      int F = 96 * j + 8 * ch;
      const bf16* W = F < 128 ? Wq : (F < 256 ? Wk : Wv);
      cp_async16(sb + k * 192 + ch * 16, W + (size_t)k * HD + h * 128 + (F & 127));
    }
    cp_commit(); cp_wait<0>();
    __syncthreads();
    uint32_t tmp[SK][3][4];
#pragma unroll
    for (int ks = 0; ks < 16; ks++) {
#pragma unroll
      for (int tt = 0; tt < 3; tt++) {
        int tile = 3 * mg + tt;
        int k = (16 * kq + ks) * 16 + (lane & 7) + 8 * (lane >> 4);
        uint32_t addr = sb + k * 192 + tile * 32 + 16 * ((lane >> 3) & 1);
        if (ks < RK) ldsm4t(wq[ks][tt][0], wq[ks][tt][1], wq[ks][tt][2], wq[ks][tt][3], addr);
        else ldsm4t(tmp[ks - RK][tt][0], tmp[ks - RK][tt][1], tmp[ks - RK][tt][2], tmp[ks - RK][tt][3], addr);
      }
    }
    __syncthreads();
#pragma unroll
    for (int ks = 0; ks < SK; ks++)
#pragma unroll
      for (int tt = 0; tt < 3; tt++)
        *reinterpret_cast<uint4*>(smem + OFF_WQS + (((warp * SK + ks) * 3 + tt) * 32 + lane) * 16) =
            make_uint4(tmp[ks][tt][0], tmp[ks][tt][1], tmp[ks][tt][2], tmp[ks][tt][3]);
    for (int i = t; i < 128 * 32; i += 256) {
      int e = i >> 5, ch = i & 31;
      cp_async16(sb + CH_STG2 + e * 512 + ch * 16, Wo + (size_t)(h * 128 + e) * DM + 256 * j + ch * 8);
    }
    cp_commit(); cp_wait<0>();
    __syncthreads();
#pragma unroll
    for (int tt = 0; tt < 2; tt++)
#pragma unroll
      for (int ks = 0; ks < 8; ks++) {
        int e = 16 * ks + (lane & 7) + 8 * (lane >> 4);
        uint32_t addr = sb + CH_STG2 + e * 512 + (32 * warp + 16 * tt + 8 * ((lane >> 3) & 1)) * 2;
        ldsm4t(wo[tt][ks][0], wo[tt][ks][1], wo[tt][ks][2], wo[tt][ks][3], addr);
      }
    if (t == 0) {
      mbar_init(sb + OFF_BAR, 1); mbar_init(sb + OFF_BAR + 8, 1);
      asm volatile("fence.mbarrier_init.release.cluster;" ::: "memory");
    }
    __syncthreads();
    asm volatile("fence.proxy.async.shared::cta;" ::: "memory");
  }
  auto prefetch_tok = [&](int s) {
    const int i = t - 192;
    const uint32_t dst = sb + OFF_TOK + (s & 1) * TOK_BYTES + (i >> 4) * TP + (i & 15) * 16;
    const bf16* src = g_qkv + (size_t)(s * 32 + (i >> 4)) * NQKV + HD + h * 128 + (i & 15) * 8;
#pragma unroll
    for (int r = 0; r < 8; r++) {
      cp_async16(dst + 4 * r * TP, src + (size_t)4 * r * NQKV);
      cp_async16(dst + (32 + 4 * r) * TP, src + (size_t)4 * r * NQKV + HD);
    }
    cp_async16(dst + 64 * TP, src + (size_t)(8 * j) * NQKV - HD);
    cp_async16(dst + 68 * TP, src + (size_t)(8 * j + 4) * NQKV - HD);
    cp_commit();
  };
  auto side_work = [&](int s) {
    if (warp >= 6) {
      prefetch_tok(s + 1);
    } else {
      const int slot2 = (s + 2) & 3;
      const int i = t - 128;
      st_pub128(&g_bufA[slot2][cta][i], SENT);
      if (i < 32) st_pub128(&g_bufA[slot2][cta][64 + i], SENT);
      if (i < 8) st_pub128(&g_bufC[slot2][8 * cta + i], SENT);
      uint4* bb = &g_bufB[slot2][32 * j + (i >> 1)][0][0] + 2 * h + (i & 1);
#pragma unroll
      for (int col = 0; col < 8; col++) st_pub128(bb + 64 * col, SENT);
    }
  };
  if (warp >= 6) prefetch_tok(0);
  for (int i = t; i < 1024; i += 256) {
    int r = i >> 7, k = (i & 127) * 8;
    uint4 v = *reinterpret_cast<const uint4*>(mem0 + r * 1024 + k);
    unsigned short* d = reinterpret_cast<unsigned short*>(smem + OFF_MEMT) + k * 8 + r;
    d[0] = (unsigned short)v.x; d[8] = (unsigned short)(v.x >> 16); d[16] = (unsigned short)v.y; d[24] = (unsigned short)(v.y >> 16);
    d[32] = (unsigned short)v.z; d[40] = (unsigned short)(v.z >> 16); d[48] = (unsigned short)v.w; d[56] = (unsigned short)(v.w >> 16);
  }
  __syncthreads();
  const uint32_t p2dst0 = sb + OFF_QKVM + t * 16, p2dst1 = p2dst0 + 4096;
  const int p0idx = 256 * kq + 128 * mg + lane;
  uint32_t tpub = 0;
  const uint32_t dA = DLY_A, dB = DLY_B, dC = DLY_C;
  TS(0);
  for (int s = 0; s < NSEG; s++) {
    const int slot = s & 3, slot2 = (s + 2) & 3;
    if (s > 0) {
      const uint4* src = &g_bufC[(s - 1) & 3][p0idx];
      uint4 v[4];
      wait_until(tpub, dC);
#pragma unroll
      for (int i = 0; i < 4; i++) v[i] = ld_poll(src + 32 * i);
      int it = 0;
      while (!__all_sync(0xffffffffu, pkt_ok(v[0]) && pkt_ok(v[1]) && pkt_ok(v[2]) && pkt_ok(v[3])) && ++it < POLL_MAX) {
#pragma unroll
        for (int i = 0; i < 4; i++)
          if (!pkt_ok(v[i])) v[i] = ld_poll(src + 32 * i);
      }
#pragma unroll
      for (int i = 0; i < 4; i++) sts128(sb + OFF_MEMT + (p0idx + 32 * i) * 16, v[i]);
      TS(1);
      asm volatile("bar.sync %0, 64;" ::"r"(1 + kq) : "memory");
      TS(2);
    }
    {
      float acc[2][3][4];
#pragma unroll
      for (int a = 0; a < 2; a++)
#pragma unroll
        for (int tt = 0; tt < 3; tt++)
#pragma unroll
          for (int i = 0; i < 4; i++) acc[a][tt][i] = 0.f;
      uint4 sa[SK][3];
#pragma unroll
      for (int kp = 0; kp < 8; kp++) {
        uint32_t b0, b1, b2, b3;
        ldsm4t(b0, b1, b2, b3, sb + OFF_MEMT + ((16 * kq + 2 * kp) * 16 + lane) * 16);
#pragma unroll
        for (int u = 0; u < 2; u++) {
          int ks = 2 * (kp + 1) + u;
          if (ks >= RK && ks < 16) {
#pragma unroll
            for (int tt = 0; tt < 3; tt++)
              sa[ks - RK][tt] = *reinterpret_cast<const uint4*>(smem + OFF_WQS + (((warp * SK + (ks - RK)) * 3 + tt) * 32 + lane) * 16);
          }
        }
#pragma unroll
        for (int u = 0; u < 2; u++) {
          int ks = 2 * kp + u;
#pragma unroll
          for (int tt = 0; tt < 3; tt++) {
            if (ks < RK) mma16816(acc[u][tt], wq[ks][tt][0], wq[ks][tt][1], wq[ks][tt][2], wq[ks][tt][3], u ? b2 : b0, u ? b3 : b1);
            else mma16816(acc[u][tt], sa[ks - RK][tt].x, sa[ks - RK][tt].y, sa[ks - RK][tt].z, sa[ks - RK][tt].w, u ? b2 : b0, u ? b3 : b1);
          }
        }
      }
#pragma unroll
      for (int tt = 0; tt < 3; tt++)
        *reinterpret_cast<float4*>(smem + OFF_RED + ((kq * 6 + 3 * mg + tt) * 32 + lane) * 16) =
            make_float4(acc[0][tt][0] + acc[1][tt][0], acc[0][tt][1] + acc[1][tt][1], acc[0][tt][2] + acc[1][tt][2], acc[0][tt][3] + acc[1][tt][3]);
    }
    TS(3);
    __syncthreads();
    TS(4);
    if (warp < 6) {
      float4 r = *reinterpret_cast<const float4*>(smem + OFF_RED + ((0 * 6 + warp) * 32 + lane) * 16);
#pragma unroll
      for (int q = 1; q < 4; q++) {
        float4 x = *reinterpret_cast<const float4*>(smem + OFF_RED + ((q * 6 + warp) * 32 + lane) * 16);
        r.x += x.x; r.y += x.y; r.z += x.z; r.w += x.w;
      }
      uint32_t* dst = reinterpret_cast<uint32_t*>(&g_bufA[slot][cta][16 * warp + g]) + c;
      st_pub32(dst, desent(pack2(r.x, r.y)));
      st_pub32(dst + 32, desent(pack2(r.z, r.w)));
    }
    tpub = clk32();
    {
      const uint4* src = &g_bufA[slot][4 * h][t];
      wait_until(tpub, dA);
      uint4 v0 = ld_poll(src);
      uint4 v1 = make_uint4(0, 0, 0, 0);
      if (t < 128) v1 = ld_poll(src + 256);
      int it = 0;
      while (!__all_sync(0xffffffffu, pkt_ok(v0) && pkt_ok(v1)) && ++it < POLL_MAX) {
        if (!pkt_ok(v0)) v0 = ld_poll(src);
        if (!pkt_ok(v1)) v1 = ld_poll(src + 256);
      }
      sts128(p2dst0, v0);
      if (t < 128) sts128(p2dst1, v1);
    }
    TS(5);
    if (warp >= 6) cp_wait<0>();
    __syncthreads();
    TS(6);
    const uint32_t tok = sb + OFF_TOK + (s & 1) * TOK_BYTES;
    if (s < NSEG - 1) {
      if (warp < 4) attn8<false>(sb, tok, lane, warp, 0, nullptr);
      else if (VAR == 1 || VAR == 3) side_work(s);
      else if (VAR == 4) attn8<true>(sb, tok, lane, warp - 4, 8 * j + g, g_otok + (size_t)(s * 32 + 8 * j + g) * HD + h * 128);
      TS(7);
      __syncthreads();
      TS(8);
      {
        float acc[2][2][4];
#pragma unroll
        for (int a = 0; a < 2; a++)
#pragma unroll
          for (int tt = 0; tt < 2; tt++)
#pragma unroll
            for (int i = 0; i < 4; i++) acc[a][tt][i] = 0.f;
        uint32_t b[4][4];
#pragma unroll
        for (int kp = 0; kp < 4; kp++) ldsm4(b[kp][0], b[kp][1], b[kp][2], b[kp][3], sb + OFF_SA + (lane & 7) * TP + (32 * kp + 8 * (lane >> 3)) * 2);
#pragma unroll
        for (int kp = 0; kp < 4; kp++) {
#pragma unroll
          for (int tt = 0; tt < 2; tt++) {
            mma16816(acc[0][tt], wo[tt][2 * kp][0], wo[tt][2 * kp][1], wo[tt][2 * kp][2], wo[tt][2 * kp][3], b[kp][0], b[kp][1]);
            mma16816(acc[1][tt], wo[tt][2 * kp + 1][0], wo[tt][2 * kp + 1][1], wo[tt][2 * kp + 1][2], wo[tt][2 * kp + 1][3], b[kp][2], b[kp][3]);
          }
        }
        const int off = (g * 32 + h) * 4 + c;
#pragma unroll
        for (int tt = 0; tt < 2; tt++) {
          int r0 = 32 * j + 4 * warp + 2 * tt;
          uint32_t x0 = __float_as_uint(acc[0][tt][0] + acc[1][tt][0]), x1 = __float_as_uint(acc[0][tt][1] + acc[1][tt][1]);
          uint32_t x2 = __float_as_uint(acc[0][tt][2] + acc[1][tt][2]), x3 = __float_as_uint(acc[0][tt][3] + acc[1][tt][3]);
          x0 = x0 == SENT ? 0x7FFFFFFFu : x0; x1 = x1 == SENT ? 0x7FFFFFFFu : x1;
          x2 = x2 == SENT ? 0x7FFFFFFFu : x2; x3 = x3 == SENT ? 0x7FFFFFFFu : x3;
          st_pub64(reinterpret_cast<uint2*>(&g_bufB[slot][r0][0][0]) + off, x0, x1);
          st_pub64(reinterpret_cast<uint2*>(&g_bufB[slot][r0 + 1][0][0]) + off, x2, x3);
        }
        tpub = clk32();
      }
      if ((VAR == 2 || VAR == 3) && warp >= 4) attn8<true>(sb, tok, lane, warp - 4, 8 * j + g, g_otok + (size_t)(s * 32 + 8 * j + g) * HD + h * 128);
      TS(9);
      {
        const uint4* src = &g_bufB[slot][cta][0][0] + 64 * warp + 2 * lane;
        wait_until(tpub, dB);
        uint4 v0 = ld_poll(src), v1 = ld_poll(src + 1);
        int it = 0;
          while (!__all_sync(0xffffffffu, pkt_ok(v0) && pkt_ok(v1)) && ++it < POLL_MAX) {
            if (!pkt_ok(v0)) v0 = ld_poll(src);
          if (!pkt_ok(v1)) v1 = ld_poll(src + 1);
        }
        TS(10);
        const bool hi = lane & 16;
        float a0 = __uint_as_float(hi ? v1.x : v0.x), a1 = __uint_as_float(hi ? v1.y : v0.y);
        float a2 = __uint_as_float(hi ? v1.z : v0.z), a3 = __uint_as_float(hi ? v1.w : v0.w);
        float b0 = __uint_as_float(hi ? v0.x : v1.x), b1 = __uint_as_float(hi ? v0.y : v1.y);
        float b2 = __uint_as_float(hi ? v0.z : v1.z), b3 = __uint_as_float(hi ? v0.w : v1.w);
        a0 += __shfl_xor_sync(0xffffffffu, b0, 16); a1 += __shfl_xor_sync(0xffffffffu, b1, 16);
        a2 += __shfl_xor_sync(0xffffffffu, b2, 16); a3 += __shfl_xor_sync(0xffffffffu, b3, 16);
        const bool h8 = lane & 8;
        float k0 = h8 ? a2 : a0, k1 = h8 ? a3 : a1, s0 = h8 ? a0 : a2, s1 = h8 ? a1 : a3;
        k0 += __shfl_xor_sync(0xffffffffu, s0, 8); k1 += __shfl_xor_sync(0xffffffffu, s1, 8);
        const bool h4 = lane & 4;
        float z = h4 ? k1 : k0, zs = h4 ? k0 : k1;
        z += __shfl_xor_sync(0xffffffffu, zs, 4);
        z += __shfl_xor_sync(0xffffffffu, z, 2);
        z += __shfl_xor_sync(0xffffffffu, z, 1);
        float zo = __shfl_xor_sync(0xffffffffu, z, 4);
        if ((lane & 7) == 0) {
          uint32_t* d = reinterpret_cast<uint32_t*>(&g_bufC[slot][8 * cta + warp]) + (lane >> 3);
          st_pub32(d, desent(pack2(z, zo)));
        }
        tpub = clk32();
      }
    }
    if (warp >= 4) {
      if ((s == NSEG - 1 || VAR == 1) && !NOTOK) attn8<true>(sb, tok, lane, warp - 4, 8 * j + g, g_otok + (size_t)(s * 32 + 8 * j + g) * HD + h * 128);
      if (s < NSEG - 1 && (VAR == 2 || VAR == 4)) side_work(s);
    }
    TS(11);
  }
}

__device__ void moe_part(int m, const bf16* __restrict__ wg, const bf16* __restrict__ wu, const bf16* __restrict__ wd, uint8_t* smem) {
  const int t = threadIdx.x, warp = t >> 5, lane = t & 31;
  float* xs = reinterpret_cast<float*>(smem);
  float* red = reinterpret_cast<float*>(smem + 8192);
  float* hs = reinterpret_cast<float*>(smem + 65536);
  __shared__ float bv[8];
  __shared__ int bi[8];
  __shared__ int sel[2];
  int first = -1;
  for (int pass = 0; pass < 2; pass++) {
    float best = -INFINITY; int bidx = 0x7fffffff;
    for (int i = t; i < S_LEN; i += 256) {
      float v = g_r[i];
      if (i == first) continue;
      if (v > best || (v == best && i < bidx) || bidx == 0x7fffffff) { best = v; bidx = i; }
    }
#pragma unroll
    for (int o = 16; o > 0; o >>= 1) {
      float ov = __shfl_xor_sync(0xffffffffu, best, o); int oi = __shfl_xor_sync(0xffffffffu, bidx, o);
      if (oi != 0x7fffffff && (bidx == 0x7fffffff || ov > best || (ov == best && oi < bidx))) { best = ov; bidx = oi; }
    }
    if (lane == 0) { bv[warp] = best; bi[warp] = bidx; }
    __syncthreads();
    if (t == 0) {
      float b = bv[0]; int ix = bi[0];
      for (int w = 1; w < 8; w++) if (bv[w] > b || (bv[w] == b && bi[w] < ix)) { b = bv[w]; ix = bi[w]; }
      sel[pass] = ix;
    }
    __syncthreads();
    first = sel[0];
  }
  const int s0 = sel[0], s1 = sel[1];
  for (int i = t; i < 2048; i += 256) xs[i] = __bfloat162float(g_xn[(size_t)(i < 1024 ? s0 : s1) * DM + (i & 1023)]);
  __syncthreads();
  {
    int cg = t % 112, kh = t / 112;
    float a[2][2][8];
#pragma unroll
    for (int i = 0; i < 8; i++) { a[0][0][i] = a[0][1][i] = a[1][0][i] = a[1][1][i] = 0.f; }
    if (kh < 2) {
      const bf16* pg = wg + (size_t)(kh * 512) * FF + 896 * m + cg * 8;
      const bf16* pu = wu + (size_t)(kh * 512) * FF + 896 * m + cg * 8;
#pragma unroll 8
      for (int k = 0; k < 512; k++) {
        uint4 gv = __ldg(reinterpret_cast<const uint4*>(pg + (size_t)k * FF));
        uint4 uv = __ldg(reinterpret_cast<const uint4*>(pu + (size_t)k * FF));
        float x0 = xs[kh * 512 + k], x1 = xs[1024 + kh * 512 + k];
        float gf[8] = {bflo(gv.x), bfhi(gv.x), bflo(gv.y), bfhi(gv.y), bflo(gv.z), bfhi(gv.z), bflo(gv.w), bfhi(gv.w)};
        float uf[8] = {bflo(uv.x), bfhi(uv.x), bflo(uv.y), bfhi(uv.y), bflo(uv.z), bfhi(uv.z), bflo(uv.w), bfhi(uv.w)};
#pragma unroll
        for (int i = 0; i < 8; i++) {
          a[0][0][i] += x0 * gf[i]; a[0][1][i] += x1 * gf[i];
          a[1][0][i] += x0 * uf[i]; a[1][1][i] += x1 * uf[i];
        }
      }
      if (kh == 1) {
#pragma unroll
        for (int i = 0; i < 8; i++) {
          red[(0 * 2 + 0) * 896 + cg * 8 + i] = a[0][0][i]; red[(0 * 2 + 1) * 896 + cg * 8 + i] = a[0][1][i];
          red[(1 * 2 + 0) * 896 + cg * 8 + i] = a[1][0][i]; red[(1 * 2 + 1) * 896 + cg * 8 + i] = a[1][1][i];
        }
      }
    }
    __syncthreads();
    if (kh == 0) {
#pragma unroll
      for (int i = 0; i < 8; i++) {
#pragma unroll
        for (int tk = 0; tk < 2; tk++) {
          float gq = bfr(a[0][tk][i] + red[(0 * 2 + tk) * 896 + cg * 8 + i]);
          float uq = bfr(a[1][tk][i] + red[(1 * 2 + tk) * 896 + cg * 8 + i]);
          float sg = bfr(gq / (1.0f + __expf(-gq)));
          g_h[tk][896 * m + cg * 8 + i] = __float2bfloat16_rn(sg * uq);
        }
      }
    }
    __threadfence();
    __syncthreads();
    if (t == 0) {
      atomicAdd(&g_moe_cnt, 1u);
      int it = 0;
      while (*reinterpret_cast<volatile unsigned*>(&g_moe_cnt) < 4u && ++it < (1 << 24)) {}
      __threadfence();
    }
    __syncthreads();
  }
  for (int i = t; i < 2 * FF; i += 256) {
    const volatile unsigned short* p = reinterpret_cast<const volatile unsigned short*>(&g_h[0][0]);
    hs[i] = __uint_as_float(((uint32_t)p[i]) << 16);
  }
  __syncthreads();
  {
    int cg = t & 31, ksl = t >> 5;
    float a[2][8];
#pragma unroll
    for (int i = 0; i < 8; i++) a[0][i] = a[1][i] = 0.f;
    const bf16* pd = wd + (size_t)(ksl * 448) * DM + 256 * m + cg * 8;
#pragma unroll 8
    for (int k = 0; k < 448; k++) {
      uint4 dv = __ldg(reinterpret_cast<const uint4*>(pd + (size_t)k * DM));
      float x0 = hs[ksl * 448 + k], x1 = hs[FF + ksl * 448 + k];
      float df[8] = {bflo(dv.x), bfhi(dv.x), bflo(dv.y), bfhi(dv.y), bflo(dv.z), bfhi(dv.z), bflo(dv.w), bfhi(dv.w)};
#pragma unroll
      for (int i = 0; i < 8; i++) { a[0][i] += x0 * df[i]; a[1][i] += x1 * df[i]; }
    }
#pragma unroll
    for (int i = 0; i < 8; i++) { red[(ksl * 2 + 0) * 256 + cg * 8 + i] = a[0][i]; red[(ksl * 2 + 1) * 256 + cg * 8 + i] = a[1][i]; }
    __syncthreads();
    for (int i = t; i < 512; i += 256) {
      int tk = i >> 8, col = i & 255;
      float y = 0.f;
#pragma unroll
      for (int q = 0; q < 8; q++) y += red[(q * 2 + tk) * 256 + col];
      float rr = g_r[tk == 0 ? s0 : s1];
      float sg = bfr(1.0f / (1.0f + __expf(-rr)));
      g_upd[tk][256 * m + col] = bfr(bfr(y) * sg);
    }
    if (m == 0 && t == 0) { g_sel[0] = s0; g_sel[1] = s1; }
  }
}

typedef CUresult (*EncodeFn)(CUtensorMap*, CUtensorMapDataType, cuuint32_t, void*, const cuuint64_t*, const cuuint64_t*,
                             const cuuint32_t*, const cuuint32_t*, CUtensorMapInterleave, CUtensorMapSwizzle,
                             CUtensorMapL2promotion, CUtensorMapFloatOOBfill);

static void make_map(EncodeFn enc, CUtensorMap* m, const void* ptr, uint64_t inner, uint64_t outer, uint32_t bi, uint32_t bo) {
  cuuint64_t dims[2] = {inner, outer};
  cuuint64_t strides[1] = {inner * 2};
  cuuint32_t box[2] = {bi, bo};
  cuuint32_t es[2] = {1, 1};
  enc(m, CU_TENSOR_MAP_DATA_TYPE_BFLOAT16, 2, const_cast<void*>(ptr), dims, strides, box, es, CU_TENSOR_MAP_INTERLEAVE_NONE,
      CU_TENSOR_MAP_SWIZZLE_128B, CU_TENSOR_MAP_L2_PROMOTION_L2_256B, CU_TENSOR_MAP_FLOAT_OOB_FILL_NONE);
}

extern "C" void kernel_launch(void* const* d_in, const int* in_sizes, int n_in, void* d_out, int out_size) {
  const bf16* x = (const bf16*)d_in[0];
  const bf16* mem0 = (const bf16*)d_in[1];
  const bf16* Wq = (const bf16*)d_in[2];
  const bf16* Wk = (const bf16*)d_in[3];
  const bf16* Wv = (const bf16*)d_in[4];
  const bf16* Wo = (const bf16*)d_in[5];
  const bf16* w_r = (const bf16*)d_in[8];
  const bf16* wg = (const bf16*)d_in[9];
  const bf16* wu = (const bf16*)d_in[10];
  const bf16* wd = (const bf16*)d_in[11];
  bf16* out = (bf16*)d_out;

  static EncodeFn enc = nullptr;
  static void *p_xn, *p_qkv, *p_otok;
  if (!enc) {
    cudaDriverEntryPointQueryResult qr;
    void* fn = nullptr;
    cudaGetDriverEntryPoint("cuTensorMapEncodeTiled", &fn, cudaEnableDefault, &qr);
    enc = (EncodeFn)fn;
    cudaGetSymbolAddress(&p_xn, g_xn);
    cudaGetSymbolAddress(&p_qkv, g_qkv);
    cudaGetSymbolAddress(&p_otok, g_otok);
    cudaFuncSetAttribute(gemm_kernel<256, 4, 0>, cudaFuncAttributeMaxDynamicSharedMemorySize, GemmSmem<256, 4>::TOTAL);
    cudaFuncSetAttribute(gemm_kernel<128, 6, 1>, cudaFuncAttributeMaxDynamicSharedMemorySize, GemmSmem<128, 6>::TOTAL);
    cudaFuncSetAttribute(chain_kernel, cudaFuncAttributeMaxDynamicSharedMemorySize, CH_SMEM);
  }
  CUtensorMap mA, mQ, mK, mV, mO, mWo;
  make_map(enc, &mA, p_xn, DM, S_LEN, 64, 128);
  make_map(enc, &mQ, Wq, HD, DM, 64, 64);
  make_map(enc, &mK, Wk, HD, DM, 64, 64);
  make_map(enc, &mV, Wv, HD, DM, 64, 64);
  make_map(enc, &mO, p_otok, HD, S_LEN, 64, 128);
  make_map(enc, &mWo, Wo, DM, HD, 64, 64);

  cudaStream_t st = cudaStreamPerThread;
  ln_kernel<<<256, 256, 0, st>>>(x, w_r);
  cudaLaunchAttribute cat[1];
  cat[0].id = cudaLaunchAttributeClusterDimension;
  cat[0].val.clusterDim.x = 2; cat[0].val.clusterDim.y = 1; cat[0].val.clusterDim.z = 1;
  cudaLaunchConfig_t cfg = {};
  cfg.gridDim = dim3(132); cfg.blockDim = dim3(288); cfg.dynamicSmemBytes = GemmSmem<256, 4>::TOTAL; cfg.stream = st;
  cfg.attrs = cat; cfg.numAttrs = 1;
  cudaLaunchKernelEx(&cfg, gemm_kernel<256, 4, 0>, mA, mQ, mK, mV, 16, 16, 16 * 48, (const bf16*)nullptr, (bf16*)p_qkv);
  chain_kernel<<<132, 256, CH_SMEM, st>>>(mem0, Wq, Wk, Wv, Wo, wg, wu, wd);
  cfg.gridDim = dim3(128); cfg.dynamicSmemBytes = GemmSmem<128, 6>::TOTAL;
  cudaLaunchKernelEx(&cfg, gemm_kernel<128, 6, 1>, mO, mWo, mWo, mWo, 64, 16, 16 * 8, x, out);
}
```

```cpp
#include <cuda_runtime.h>
#include <cuda_bf16.h>
#include <cuda.h>
#include <stdint.h>

typedef __nv_bfloat16 bf16;

#define S_LEN 2048
#define DM 1024
#define NH 32
#define DH 128
#define NSEG 64
#define SEGL 32
#define HD 4096
#define NQKV 12288
#define FF 3584
#define SENT 0xFFFFFFFFu

__device__ __align__(1024) bf16 g_xn[S_LEN * DM];
__device__ __align__(1024) bf16 g_qkv[(size_t)S_LEN * NQKV];
__device__ __align__(1024) bf16 g_otok[(size_t)S_LEN * HD];
__device__ float g_r[S_LEN];
__device__ __align__(128) uint4 g_bufA[4][128][96];
__device__ __align__(128) uint4 g_bufB[4][128][16][32];
__device__ __align__(128) uint4 g_bufC[4][1024];
__device__ __align__(128) bf16 g_h[2][FF];
__device__ float g_upd[2][DM];
__device__ int g_sel[2];
__device__ unsigned g_moe_cnt;
#define NOTOK 0
#define VAR 1
#define DLY_A 300u
#define DLY_B 800u
#define DLY_C 700u
#define TS(i)

__device__ __forceinline__ float bfr(float x) { return __bfloat162float(__float2bfloat16_rn(x)); }
__device__ __forceinline__ uint32_t pack2(float lo, float hi) {
  __nv_bfloat162 v = __floats2bfloat162_rn(lo, hi);
  return *reinterpret_cast<uint32_t*>(&v);
}
__device__ __forceinline__ float bflo(uint32_t v) { return __uint_as_float(v << 16); }
__device__ __forceinline__ float bfhi(uint32_t v) { return __uint_as_float(v & 0xFFFF0000u); }
__device__ __forceinline__ uint32_t smem_u32(const void* p) { return (uint32_t)__cvta_generic_to_shared(p); }

__device__ __forceinline__ uint4 ld_poll(const uint4* p) {
  uint4 v;
  asm volatile("ld.relaxed.gpu.global.v4.u32 {%0,%1,%2,%3},[%4];" : "=r"(v.x), "=r"(v.y), "=r"(v.z), "=r"(v.w) : "l"(p) : "memory");
  return v;
}
__device__ __forceinline__ void st_pub32(void* p, uint32_t v) {
  asm volatile("st.relaxed.gpu.global.u32 [%0],%1;" ::"l"(p), "r"(v) : "memory");
}
__device__ __forceinline__ void st_pub64(void* p, uint32_t a, uint32_t b) {
  asm volatile("st.relaxed.gpu.global.v2.u32 [%0],{%1,%2};" ::"l"(p), "r"(a), "r"(b) : "memory");
}
__device__ __forceinline__ bool pkt_ok(const uint4& v) { return v.x != SENT && v.y != SENT && v.z != SENT && v.w != SENT; }
__device__ __forceinline__ uint32_t desent(uint32_t v) { return v == SENT ? 0x7FFF7FFFu : v; }

__device__ __forceinline__ void ldsm4(uint32_t& r0, uint32_t& r1, uint32_t& r2, uint32_t& r3, uint32_t addr) {
  asm volatile("ldmatrix.sync.aligned.m8n8.x4.shared.b16 {%0,%1,%2,%3},[%4];" : "=r"(r0), "=r"(r1), "=r"(r2), "=r"(r3) : "r"(addr) : "memory");
}
__device__ __forceinline__ void ldsm4t(uint32_t& r0, uint32_t& r1, uint32_t& r2, uint32_t& r3, uint32_t addr) {
  asm volatile("ldmatrix.sync.aligned.m8n8.x4.trans.shared.b16 {%0,%1,%2,%3},[%4];" : "=r"(r0), "=r"(r1), "=r"(r2), "=r"(r3) : "r"(addr) : "memory");
}
__device__ __forceinline__ void mma16816(float (&d)[4], uint32_t a0, uint32_t a1, uint32_t a2, uint32_t a3, uint32_t b0, uint32_t b1) {
  asm volatile("mma.sync.aligned.m16n8k16.row.col.f32.bf16.bf16.f32 {%0,%1,%2,%3},{%4,%5,%6,%7},{%8,%9},{%0,%1,%2,%3};"
               : "+f"(d[0]), "+f"(d[1]), "+f"(d[2]), "+f"(d[3])
               : "r"(a0), "r"(a1), "r"(a2), "r"(a3), "r"(b0), "r"(b1));
}
__device__ __forceinline__ void cp_async16(uint32_t dst, const void* src) {
  asm volatile("cp.async.cg.shared.global [%0],[%1],16;" ::"r"(dst), "l"(src) : "memory");
}
__device__ __forceinline__ void cp_commit() { asm volatile("cp.async.commit_group;" ::: "memory"); }
template <int N>
__device__ __forceinline__ void cp_wait() { asm volatile("cp.async.wait_group %0;" ::"n"(N) : "memory"); }

__device__ __forceinline__ void mbar_init(uint32_t bar, uint32_t cnt) { asm volatile("mbarrier.init.shared::cta.b64 [%0],%1;" ::"r"(bar), "r"(cnt) : "memory"); }
__device__ __forceinline__ void mbar_expect_tx(uint32_t bar, uint32_t bytes) {
  asm volatile("mbarrier.arrive.expect_tx.shared::cta.b64 _,[%0],%1;" ::"r"(bar), "r"(bytes) : "memory");
}
__device__ __forceinline__ void mbar_arrive(uint32_t bar) { asm volatile("mbarrier.arrive.shared::cta.b64 _,[%0];" ::"r"(bar) : "memory"); }
__device__ __forceinline__ void mbar_wait(uint32_t bar, uint32_t parity) {
  asm volatile(
      "{\n.reg .pred p;\n"
      "WAIT_LOOP:\n"
      "mbarrier.try_wait.parity.shared::cta.b64 p,[%0],%1;\n"
      "@p bra WAIT_DONE;\n"
      "bra WAIT_LOOP;\n"
      "WAIT_DONE:\n}\n" ::"r"(bar), "r"(parity) : "memory");
}
__device__ __forceinline__ void tma_load2d(uint32_t dst, const CUtensorMap* tm, uint32_t bar, int c0, int c1) {
  asm volatile("cp.async.bulk.tensor.2d.shared::cluster.global.mbarrier::complete_tx::bytes [%0],[%1,{%3,%4}],[%2];"
               ::"r"(dst), "l"(tm), "r"(bar), "r"(c0), "r"(c1) : "memory");
}
__device__ __forceinline__ void tma_load2d_mc(uint32_t dst, const CUtensorMap* tm, uint32_t bar, int c0, int c1, uint16_t mask) {
  asm volatile("cp.async.bulk.tensor.2d.shared::cluster.global.mbarrier::complete_tx::bytes.multicast::cluster [%0],[%1,{%3,%4}],[%2],%5;"
               ::"r"(dst), "l"(tm), "r"(bar), "r"(c0), "r"(c1), "h"(mask) : "memory");
}
__device__ __forceinline__ void mbar_arrive_cluster(uint32_t bar, uint32_t cta) {
  asm volatile("{\n.reg .b32 ra;\nmapa.shared::cluster.u32 ra,%0,%1;\nmbarrier.arrive.shared::cluster.b64 _,[ra];\n}\n" ::"r"(bar), "r"(cta) : "memory");
}
__device__ __forceinline__ void cluster_sync() {
  asm volatile("barrier.cluster.arrive.release.aligned;\nbarrier.cluster.wait.acquire.aligned;\n" ::: "memory");
}
__device__ __forceinline__ void wg_fence() { asm volatile("wgmma.fence.sync.aligned;" ::: "memory"); }
__device__ __forceinline__ void wg_commit() { asm volatile("wgmma.commit_group.sync.aligned;" ::: "memory"); }
template <int N>
__device__ __forceinline__ void wg_wait() { asm volatile("wgmma.wait_group.sync.aligned %0;" ::"n"(N) : "memory"); }
__device__ __forceinline__ uint64_t make_desc(uint32_t addr, uint32_t lbo, uint32_t sbo) {
  return (uint64_t)((addr & 0x3FFFF) >> 4) | ((uint64_t)(lbo >> 4) << 16) | ((uint64_t)(sbo >> 4) << 32) | (1ull << 62);
}

__device__ __forceinline__ void wgmma_m64n256k16(float (&d)[128], uint64_t da, uint64_t db, int scaleD) {
  asm volatile(
    "{\n.reg .pred p;\nsetp.ne.b32 p, %130, 0;\n"
    "wgmma.mma_async.sync.aligned.m64n256k16.f32.bf16.bf16 "
    "{%0, %1, %2, %3, %4, %5, %6, %7, %8, %9, %10, %11, %12, %13, %14, %15, %16, %17, %18, %19, %20, %21, %22, %23, %24, %25, %26, %27, %28, %29, %30, %31, %32, %33, %34, %35, %36, %37, %38, %39, %40, %41, %42, %43, %44, %45, %46, %47, %48, %49, %50, %51, %52, %53, %54, %55, %56, %57, %58, %59, %60, %61, %62, %63, %64, %65, %66, %67, %68, %69, %70, %71, %72, %73, %74, %75, %76, %77, %78, %79, %80, %81, %82, %83, %84, %85, %86, %87, %88, %89, %90, %91, %92, %93, %94, %95, %96, %97, %98, %99, %100, %101, %102, %103, %104, %105, %106, %107, %108, %109, %110, %111, %112, %113, %114, %115, %116, %117, %118, %119, %120, %121, %122, %123, %124, %125, %126, %127}, %128, %129, p, 1, 1, 0, 1;\n}\n"
    : "+f"(d[0]), "+f"(d[1]), "+f"(d[2]), "+f"(d[3]), "+f"(d[4]), "+f"(d[5]), "+f"(d[6]), "+f"(d[7]), "+f"(d[8]), "+f"(d[9]), "+f"(d[10]), "+f"(d[11]), "+f"(d[12]), "+f"(d[13]), "+f"(d[14]), "+f"(d[15]), "+f"(d[16]), "+f"(d[17]), "+f"(d[18]), "+f"(d[19]), "+f"(d[20]), "+f"(d[21]), "+f"(d[22]), "+f"(d[23]), "+f"(d[24]), "+f"(d[25]), "+f"(d[26]), "+f"(d[27]), "+f"(d[28]), "+f"(d[29]), "+f"(d[30]), "+f"(d[31]), "+f"(d[32]), "+f"(d[33]), "+f"(d[34]), "+f"(d[35]), "+f"(d[36]), "+f"(d[37]), "+f"(d[38]), "+f"(d[39]), "+f"(d[40]), "+f"(d[41]), "+f"(d[42]), "+f"(d[43]), "+f"(d[44]), "+f"(d[45]), "+f"(d[46]), "+f"(d[47]), "+f"(d[48]), "+f"(d[49]), "+f"(d[50]), "+f"(d[51]), "+f"(d[52]), "+f"(d[53]), "+f"(d[54]), "+f"(d[55]), "+f"(d[56]), "+f"(d[57]), "+f"(d[58]), "+f"(d[59]), "+f"(d[60]), "+f"(d[61]), "+f"(d[62]), "+f"(d[63]), "+f"(d[64]), "+f"(d[65]), "+f"(d[66]), "+f"(d[67]), "+f"(d[68]), "+f"(d[69]), "+f"(d[70]), "+f"(d[71]), "+f"(d[72]), "+f"(d[73]), "+f"(d[74]), "+f"(d[75]), "+f"(d[76]), "+f"(d[77]), "+f"(d[78]), "+f"(d[79]), "+f"(d[80]), "+f"(d[81]), "+f"(d[82]), "+f"(d[83]), "+f"(d[84]), "+f"(d[85]), "+f"(d[86]), "+f"(d[87]), "+f"(d[88]), "+f"(d[89]), "+f"(d[90]), "+f"(d[91]), "+f"(d[92]), "+f"(d[93]), "+f"(d[94]), "+f"(d[95]), "+f"(d[96]), "+f"(d[97]), "+f"(d[98]), "+f"(d[99]), "+f"(d[100]), "+f"(d[101]), "+f"(d[102]), "+f"(d[103]), "+f"(d[104]), "+f"(d[105]), "+f"(d[106]), "+f"(d[107]), "+f"(d[108]), "+f"(d[109]), "+f"(d[110]), "+f"(d[111]), "+f"(d[112]), "+f"(d[113]), "+f"(d[114]), "+f"(d[115]), "+f"(d[116]), "+f"(d[117]), "+f"(d[118]), "+f"(d[119]), "+f"(d[120]), "+f"(d[121]), "+f"(d[122]), "+f"(d[123]), "+f"(d[124]), "+f"(d[125]), "+f"(d[126]), "+f"(d[127])
    : "l"(da), "l"(db), "r"(scaleD));
}

__device__ __forceinline__ void wgmma_m64n128k16(float (&d)[64], uint64_t da, uint64_t db, int scaleD) {
  asm volatile(
    "{\n.reg .pred p;\nsetp.ne.b32 p, %66, 0;\n"
    "wgmma.mma_async.sync.aligned.m64n128k16.f32.bf16.bf16 "
    "{%0, %1, %2, %3, %4, %5, %6, %7, %8, %9, %10, %11, %12, %13, %14, %15, %16, %17, %18, %19, %20, %21, %22, %23, %24, %25, %26, %27, %28, %29, %30, %31, %32, %33, %34, %35, %36, %37, %38, %39, %40, %41, %42, %43, %44, %45, %46, %47, %48, %49, %50, %51, %52, %53, %54, %55, %56, %57, %58, %59, %60, %61, %62, %63}, %64, %65, p, 1, 1, 0, 1;\n}\n"
    : "+f"(d[0]), "+f"(d[1]), "+f"(d[2]), "+f"(d[3]), "+f"(d[4]), "+f"(d[5]), "+f"(d[6]), "+f"(d[7]), "+f"(d[8]), "+f"(d[9]), "+f"(d[10]), "+f"(d[11]), "+f"(d[12]), "+f"(d[13]), "+f"(d[14]), "+f"(d[15]), "+f"(d[16]), "+f"(d[17]), "+f"(d[18]), "+f"(d[19]), "+f"(d[20]), "+f"(d[21]), "+f"(d[22]), "+f"(d[23]), "+f"(d[24]), "+f"(d[25]), "+f"(d[26]), "+f"(d[27]), "+f"(d[28]), "+f"(d[29]), "+f"(d[30]), "+f"(d[31]), "+f"(d[32]), "+f"(d[33]), "+f"(d[34]), "+f"(d[35]), "+f"(d[36]), "+f"(d[37]), "+f"(d[38]), "+f"(d[39]), "+f"(d[40]), "+f"(d[41]), "+f"(d[42]), "+f"(d[43]), "+f"(d[44]), "+f"(d[45]), "+f"(d[46]), "+f"(d[47]), "+f"(d[48]), "+f"(d[49]), "+f"(d[50]), "+f"(d[51]), "+f"(d[52]), "+f"(d[53]), "+f"(d[54]), "+f"(d[55]), "+f"(d[56]), "+f"(d[57]), "+f"(d[58]), "+f"(d[59]), "+f"(d[60]), "+f"(d[61]), "+f"(d[62]), "+f"(d[63])
    : "l"(da), "l"(db), "r"(scaleD));
}

template <int BN> struct WG;
template <> struct WG<256> { static __device__ __forceinline__ void mma(float (&d)[128], uint64_t a, uint64_t b, int s) { wgmma_m64n256k16(d, a, b, s); } };
template <> struct WG<128> { static __device__ __forceinline__ void mma(float (&d)[64], uint64_t a, uint64_t b, int s) { wgmma_m64n128k16(d, a, b, s); } };

__global__ void __launch_bounds__(256) ln_kernel(const bf16* __restrict__ x, const bf16* __restrict__ w_r) {
  int warp = threadIdx.x >> 5, lane = threadIdx.x & 31;
  int row = blockIdx.x * 8 + warp;
  const uint4* xp = reinterpret_cast<const uint4*>(x + (size_t)row * DM);
  uint4 v[4];
#pragma unroll
  for (int i = 0; i < 4; i++) v[i] = xp[lane + 32 * i];
  float f[32];
#pragma unroll
  for (int i = 0; i < 4; i++) {
    f[8 * i + 0] = bflo(v[i].x); f[8 * i + 1] = bfhi(v[i].x);
    f[8 * i + 2] = bflo(v[i].y); f[8 * i + 3] = bfhi(v[i].y);
    f[8 * i + 4] = bflo(v[i].z); f[8 * i + 5] = bfhi(v[i].z);
    f[8 * i + 6] = bflo(v[i].w); f[8 * i + 7] = bfhi(v[i].w);
  }
  float s = 0.f;
#pragma unroll
  for (int i = 0; i < 32; i++) s += f[i];
#pragma unroll
  for (int o = 16; o > 0; o >>= 1) s += __shfl_xor_sync(0xffffffffu, s, o);
  float mean = s * (1.0f / DM);
  float q = 0.f;
#pragma unroll
  for (int i = 0; i < 32; i++) { float d = f[i] - mean; q += d * d; }
#pragma unroll
  for (int o = 16; o > 0; o >>= 1) q += __shfl_xor_sync(0xffffffffu, q, o);
  float var = bfr(q * (1.0f / DM));
  float mb = bfr(mean);
  float den = bfr(sqrtf(bfr(var + 1e-5f)));
  const uint4* wp = reinterpret_cast<const uint4*>(w_r);
  uint4* op = reinterpret_cast<uint4*>(g_xn + (size_t)row * DM);
  float r = 0.f;
#pragma unroll
  for (int i = 0; i < 4; i++) {
    uint4 w = wp[lane + 32 * i];
    float y[8];
#pragma unroll
    for (int k = 0; k < 8; k++) y[k] = bfr(bfr(f[8 * i + k] - mb) / den);
    r += y[0] * bflo(w.x) + y[1] * bfhi(w.x) + y[2] * bflo(w.y) + y[3] * bfhi(w.y) + y[4] * bflo(w.z) + y[5] * bfhi(w.z) +
         y[6] * bflo(w.w) + y[7] * bfhi(w.w);
    op[lane + 32 * i] = make_uint4(pack2(y[0], y[1]), pack2(y[2], y[3]), pack2(y[4], y[5]), pack2(y[6], y[7]));
  }
#pragma unroll
  for (int o = 16; o > 0; o >>= 1) r += __shfl_xor_sync(0xffffffffu, r, o);
  if (lane == 0) g_r[row] = bfr(r);
  int gt = blockIdx.x * 256 + threadIdx.x;
  const uint4 sv = make_uint4(SENT, SENT, SENT, SENT);
  uint4* a = &g_bufA[0][0][0];
  for (int i = gt; i < 2 * 128 * 96; i += 65536) a[i] = sv;
  uint4* b = &g_bufB[0][0][0][0];
  for (int i = gt; i < 2 * 128 * 32 * 16; i += 65536) b[i] = sv;
  uint4* c = &g_bufC[0][0];
  for (int i = gt; i < 2 * 1024; i += 65536) c[i] = sv;
  if (gt == 0) g_moe_cnt = 0;
}

template <int BN, int STAGES>
struct GemmSmem {
  static constexpr int A_BYTES = 128 * 64 * 2;
  static constexpr int B_BYTES = 64 * BN * 2;
  static constexpr int STAGE_BYTES = A_BYTES + B_BYTES;
  static constexpr int TOTAL = STAGES * STAGE_BYTES + 1024 + 256;
};

__device__ __forceinline__ void quad_transpose(uint32_t (&v)[4], int c) {
  {
    uint32_t s0 = (c & 1) ? v[0] : v[1];
    uint32_t s1 = (c & 1) ? v[2] : v[3];
    uint32_t r0 = __shfl_xor_sync(0xffffffffu, s0, 1);
    uint32_t r1 = __shfl_xor_sync(0xffffffffu, s1, 1);
    if (c & 1) { v[0] = r0; v[2] = r1; } else { v[1] = r0; v[3] = r1; }
  }
  {
    uint32_t s0 = (c & 2) ? v[0] : v[2];
    uint32_t s1 = (c & 2) ? v[1] : v[3];
    uint32_t r0 = __shfl_xor_sync(0xffffffffu, s0, 2);
    uint32_t r1 = __shfl_xor_sync(0xffffffffu, s1, 2);
    if (c & 2) { v[0] = r0; v[1] = r1; } else { v[2] = r0; v[3] = r1; }
  }
}

__device__ __forceinline__ uint32_t add3(uint32_t a, uint32_t x, uint32_t b) {
  float lo = bfr(bflo(x) + bflo(a)) + bflo(b);
  float hi = bfr(bfhi(x) + bfhi(a)) + bfhi(b);
  return pack2(lo, hi);
}

template <int BN, int STAGES, int EPI>
__global__ void __launch_bounds__(288, 1)
gemm_kernel(const __grid_constant__ CUtensorMap tmA, const __grid_constant__ CUtensorMap tmB0,
            const __grid_constant__ CUtensorMap tmB1, const __grid_constant__ CUtensorMap tmB2,
            int kblocks, int tiles_m, int tiles_total, const bf16* __restrict__ xin, bf16* __restrict__ outp,
            const bf16* pf0, const bf16* pf1, const bf16* pf2, const bf16* pf3) {
  using SM = GemmSmem<BN, STAGES>;
  extern __shared__ uint8_t smem_raw[];
  uint32_t base = (smem_u32(smem_raw) + 1023) & ~1023u;
  uint32_t bars = base + STAGES * SM::STAGE_BYTES;
  int warp = threadIdx.x >> 5, lane = threadIdx.x & 31;
  uint32_t rank;
  asm volatile("mov.u32 %0,%%cluster_ctarank;" : "=r"(rank));
  const int cl = blockIdx.x >> 1, ncl = gridDim.x >> 1;
  const int pairs_m = tiles_m >> 1, pairs_total = tiles_total >> 1;
  if (threadIdx.x == 0) {
    for (int i = 0; i < STAGES; i++) { mbar_init(bars + 8 * i, 1); mbar_init(bars + 8 * (STAGES + i), 16); }
    asm volatile("fence.mbarrier_init.release.cluster;" ::: "memory");
  }
  __syncthreads();
  cluster_sync();
  if (warp == 8) {
    if (lane == 0) {
      int it = 0;
      for (int t = cl; t < pairs_total; t += ncl) {
        int tm = 2 * (t % pairs_m) + rank, tn = t / pairs_m;
        int n0 = tn * BN;
        const CUtensorMap* tb = &tmB0;
        if (EPI == 0) { int wsel = n0 >> 12; tb = wsel == 0 ? &tmB0 : (wsel == 1 ? &tmB1 : &tmB2); n0 &= 4095; }
        for (int kb = 0; kb < kblocks; kb++, it++) {
          int st = it % STAGES; uint32_t ph = (it / STAGES) & 1;
          mbar_wait(bars + 8 * (STAGES + st), ph ^ 1);
          uint32_t sa = base + st * SM::STAGE_BYTES, sb = sa + SM::A_BYTES;
          mbar_expect_tx(bars + 8 * st, SM::STAGE_BYTES);
          tma_load2d(sa, &tmA, bars + 8 * st, kb * 64, tm * 128);
#pragma unroll
          for (int i = 0; i < BN / 128; i++) {
            int bx = rank * (BN / 128) + i;
            tma_load2d_mc(sb + bx * 8192, tb, bars + 8 * st, n0 + bx * 64, kb * 64, (uint16_t)3);
          }
        }
      }
      if (EPI == 0 && blockIdx.x < 128) {
        const size_t o = (size_t)blockIdx.x * 32768;
#pragma unroll
        for (int q = 0; q < 4; q++) {
          asm volatile("cp.async.bulk.prefetch.L2.global [%0],%1;" ::"l"(pf0 + o + q * 8192), "r"(16384) : "memory");
          asm volatile("cp.async.bulk.prefetch.L2.global [%0],%1;" ::"l"(pf1 + o + q * 8192), "r"(16384) : "memory");
          asm volatile("cp.async.bulk.prefetch.L2.global [%0],%1;" ::"l"(pf2 + o + q * 8192), "r"(16384) : "memory");
          asm volatile("cp.async.bulk.prefetch.L2.global [%0],%1;" ::"l"(pf3 + o + q * 8192), "r"(16384) : "memory");
        }
      }
    }
    __syncwarp();
  } else {
    int wg = warp >> 2;
    int g = lane >> 2, c = lane & 3;
    int it = 0;
    float acc[BN / 2];
    for (int t = cl; t < pairs_total; t += ncl) {
      int tm = 2 * (t % pairs_m) + rank, tn = t / pairs_m;
      for (int kb = 0; kb < kblocks; kb++, it++) {
        int st = it % STAGES; uint32_t ph = (it / STAGES) & 1;
        mbar_wait(bars + 8 * st, ph);
        uint32_t sa = base + st * SM::STAGE_BYTES + wg * 8192, sb = base + st * SM::STAGE_BYTES + SM::A_BYTES;
        wg_fence();
#pragma unroll
        for (int kk = 0; kk < 4; kk++) {
          uint64_t da = make_desc(sa + kk * 32, 16, 1024);
          uint64_t db = make_desc(sb + kk * 2048, 8192, 1024);
          WG<BN>::mma(acc, da, db, (kb | kk) != 0);
        }
        wg_commit();
        if (kb > 0) {
          wg_wait<1>();
          int pst = (it - 1) % STAGES;
          if (lane < 2) mbar_arrive_cluster(bars + 8 * (STAGES + pst), lane);
        }
      }
      wg_wait<0>();
      { int pst = (it - 1) % STAGES; if (lane < 2) mbar_arrive_cluster(bars + 8 * (STAGES + pst), lane); }
      int row0 = tm * 128 + wg * 64 + (warp & 3) * 16 + g;
      int sel0 = -1, sel1 = -1;
      if (EPI == 1) { sel0 = g_sel[0]; sel1 = g_sel[1]; }
#pragma unroll
      for (int half = 0; half < 2; half++) {
        int row = row0 + half * 8;
#pragma unroll
        for (int q = 0; q < BN / 32; q++) {
          uint32_t v[4];
#pragma unroll
          for (int tt = 0; tt < 4; tt++) v[tt] = pack2(acc[(q * 4 + tt) * 4 + half * 2], acc[(q * 4 + tt) * 4 + half * 2 + 1]);
          quad_transpose(v, c);
          int col = tn * BN + q * 32 + c * 8;
          if (EPI == 0) {
            __stcs(reinterpret_cast<uint4*>(outp + (size_t)row * NQKV + col), make_uint4(v[0], v[1], v[2], v[3]));
          } else {
            uint4 xv = *reinterpret_cast<const uint4*>(xin + (size_t)row * DM + col);
            uint4 bv = *reinterpret_cast<const uint4*>(g_xn + (size_t)row * DM + col);
            if (row == sel0 || row == sel1) {
              const float* u = &g_upd[row == sel0 ? 0 : 1][col];
              bv.x = pack2(bflo(bv.x) + u[0], bfhi(bv.x) + u[1]);
              bv.y = pack2(bflo(bv.y) + u[2], bfhi(bv.y) + u[3]);
              bv.z = pack2(bflo(bv.z) + u[4], bfhi(bv.z) + u[5]);
              bv.w = pack2(bflo(bv.w) + u[6], bfhi(bv.w) + u[7]);
            }
            uint4 o = make_uint4(add3(v[0], xv.x, bv.x), add3(v[1], xv.y, bv.y), add3(v[2], xv.z, bv.z), add3(v[3], xv.w, bv.w));
            *reinterpret_cast<uint4*>(outp + (size_t)row * DM + col) = o;
          }
        }
      }
    }
  }
  cluster_sync();
}

#define RK 10
#define SK (16 - RK)
#define TP 272
#define OFF_WQS 0
#define OFF_MEMT (OFF_WQS + 8 * SK * 3 * 512)
#define OFF_RED (OFF_MEMT + 16384)
#define OFF_QKVM (OFF_RED + 12288)
#define OFF_TOK (OFF_QKVM + 6144)
#define TOK_BYTES (72 * TP)
#define OFF_SA (OFF_TOK + 2 * TOK_BYTES)
#define OFF_BAR (OFF_SA + 8 * TP)
#define CH_END (OFF_BAR + 64)
#define CH_STG2 (131072)
#define CH_SMEM (196608 + 1024)
static_assert(CH_END <= CH_SMEM, "smem");

__device__ void moe_part(int m, const bf16* __restrict__ wg, const bf16* __restrict__ wu, const bf16* __restrict__ wd, uint8_t* smem);

__device__ __forceinline__ void bulk_copy(uint32_t dst, const void* src, uint32_t bytes, uint32_t bar) {
  asm volatile("cp.async.bulk.shared::cluster.global.mbarrier::complete_tx::bytes [%0],[%1],%2,[%3];"
               ::"r"(dst), "l"(src), "r"(bytes), "r"(bar) : "memory");
}
__device__ __forceinline__ void st_pub128(void* p, uint32_t v) {
  asm volatile("st.relaxed.gpu.global.v4.u32 [%0],{%1,%1,%1,%1};" ::"l"(p), "r"(v) : "memory");
}
__device__ __forceinline__ void sts128(uint32_t addr, const uint4& v) {
  asm volatile("st.shared.v4.u32 [%0],{%1,%2,%3,%4};" ::"r"(addr), "r"(v.x), "r"(v.y), "r"(v.z), "r"(v.w) : "memory");
}

#define POLL_MAX (1 << 22)
__device__ __forceinline__ uint32_t clk32() { uint32_t c; asm volatile("mov.u32 %0,%%clock;" : "=r"(c)); return c; }
__device__ __forceinline__ void wait_until(uint32_t t0, uint32_t d) { while (clk32() - t0 < d) {} }
#define DLY_DEC 48u

__device__ __forceinline__ float ex2f(float x) { float y; asm("ex2.approx.ftz.f32 %0,%1;" : "=f"(y) : "f"(x)); return y; }
__device__ __forceinline__ float rcpf(float x) { float y; asm("rcp.approx.ftz.f32 %0,%1;" : "=f"(y) : "f"(x)); return y; }
template <bool TOK>
__device__ __forceinline__ void attn8(uint32_t sb, uint32_t tok, int lane, int wq4, int tr, bf16* otok_row) {
  const int g = lane >> 2, c = lane & 3;
  float sc[5][4];
#pragma unroll
  for (int n = 0; n < 5; n++)
#pragma unroll
    for (int i = 0; i < 4; i++) sc[n][i] = 0.f;
  const uint32_t tokrow = tok + (lane & 7) * TP + (lane >> 3) * 16;
  const uint32_t qaddr = TOK ? (tok + (64 + (lane & 7)) * TP + (lane >> 4) * 16) : (sb + OFF_QKVM + ((lane & 7) + 8 * (lane >> 4)) * 16);
#pragma unroll
  for (int kp = 0; kp < 4; kp++) {
    uint32_t q0[4], q1[4], km[4], kt[4][4];
    if (TOK) {
      ldsm4(q0[0], q0[1], q0[2], q0[3], qaddr + 64 * kp);
      ldsm4(q1[0], q1[1], q1[2], q1[3], qaddr + 64 * kp + 32);
    } else {
      ldsm4t(q0[0], q0[1], q0[2], q0[3], qaddr + 512 * kp);
      ldsm4t(q1[0], q1[1], q1[2], q1[3], qaddr + 512 * kp + 256);
    }
    ldsm4t(km[0], km[1], km[2], km[3], sb + OFF_QKVM + (128 + 32 * kp + lane) * 16);
#pragma unroll
    for (int n = 0; n < 4; n++) ldsm4(kt[n][0], kt[n][1], kt[n][2], kt[n][3], tokrow + 8 * n * TP + 64 * kp);
    mma16816(sc[0], q0[0], q0[1], q0[2], q0[3], km[0], km[1]);
#pragma unroll
    for (int n = 0; n < 4; n++) mma16816(sc[n + 1], q0[0], q0[1], q0[2], q0[3], kt[n][0], kt[n][1]);
    mma16816(sc[0], q1[0], q1[1], q1[2], q1[3], km[2], km[3]);
#pragma unroll
    for (int n = 0; n < 4; n++) mma16816(sc[n + 1], q1[0], q1[1], q1[2], q1[3], kt[n][2], kt[n][3]);
  }
  uint32_t vma[4], vmb[4], vt[4][4];
  ldsm4(vma[0], vma[1], vma[2], vma[3], sb + OFF_QKVM + (256 + 32 * wq4 + lane) * 16);
  ldsm4(vmb[0], vmb[1], vmb[2], vmb[3], sb + OFF_QKVM + (256 + 32 * wq4 + (lane ^ 8)) * 16);
#pragma unroll
  for (int n = 0; n < 4; n++) ldsm4t(vt[n][0], vt[n][1], vt[n][2], vt[n][3], tok + (32 + lane) * TP + (32 * wq4 + 8 * n) * 2);
  const float scale = 0.08838834764831845f;
  float m0 = -3.0e38f;
#pragma unroll
  for (int n = 0; n < 5; n++) {
    uint32_t p1 = pack2(sc[n][0], sc[n][1]);
    uint32_t p2 = pack2(bflo(p1) * scale, bfhi(p1) * scale);
    sc[n][0] = bflo(p2);
    sc[n][1] = bfhi(p2);
    if (TOK && n > 0) {
      int kt = 8 * (n - 1) + 2 * c;
      if (kt > tr) sc[n][0] = -1.0e9f;
      if (kt + 1 > tr) sc[n][1] = -1.0e9f;
    }
    m0 = fmaxf(m0, fmaxf(sc[n][0], sc[n][1]));
  }
  m0 = fmaxf(m0, __shfl_xor_sync(0xffffffffu, m0, 1));
  m0 = fmaxf(m0, __shfl_xor_sync(0xffffffffu, m0, 2));
  const float l2e = 1.4426950408889634f;
  float s0 = 0.f;
#pragma unroll
  for (int n = 0; n < 5; n++) {
    sc[n][0] = ex2f((sc[n][0] - m0) * l2e);
    sc[n][1] = ex2f((sc[n][1] - m0) * l2e);
    s0 += sc[n][0] + sc[n][1];
  }
  s0 += __shfl_xor_sync(0xffffffffu, s0, 1);
  s0 += __shfl_xor_sync(0xffffffffu, s0, 2);
  const float i0 = rcpf(s0);
  uint32_t pp[5];
#pragma unroll
  for (int n = 0; n < 5; n++) pp[n] = pack2(sc[n][0] * i0, sc[n][1] * i0);
  float o[4][4];
#pragma unroll
  for (int n = 0; n < 4; n++) {
#pragma unroll
    for (int i = 0; i < 4; i++) o[n][i] = 0.f;
    mma16816(o[n], pp[1], pp[1], pp[2], pp[2], vt[n][0], vt[n][1]);
  }
#pragma unroll
  for (int n = 0; n < 4; n++) mma16816(o[n], pp[3], pp[3], pp[4], pp[4], vt[n][2], vt[n][3]);
  mma16816(o[0], pp[0], 0u, 0u, 0u, vma[0], vma[1]);
  mma16816(o[1], pp[0], 0u, 0u, 0u, vmb[0], vmb[1]);
  mma16816(o[2], pp[0], 0u, 0u, 0u, vma[2], vma[3]);
  mma16816(o[3], pp[0], 0u, 0u, 0u, vmb[2], vmb[3]);
#pragma unroll
  for (int n = 0; n < 4; n++) {
    const int e = 32 * wq4 + 8 * n + 2 * c;
    if (TOK) *reinterpret_cast<uint32_t*>(otok_row + e) = pack2(o[n][0], o[n][1]);
    else asm volatile("st.shared.u32 [%0],%1;" ::"r"(sb + OFF_SA + g * TP + e * 2), "r"(pack2(o[n][0], o[n][1])) : "memory");
  }
}

__global__ void __launch_bounds__(256, 1)
chain_kernel(const bf16* __restrict__ mem0, const bf16* __restrict__ Wq, const bf16* __restrict__ Wk, const bf16* __restrict__ Wv,
             const bf16* __restrict__ Wo, const bf16* __restrict__ wgate, const bf16* __restrict__ wup, const bf16* __restrict__ wdown) {
  extern __shared__ __align__(1024) uint8_t smem[];
  const int cta = blockIdx.x, t = threadIdx.x, warp = t >> 5, lane = t & 31;
  if (cta >= 128) {
    moe_part(cta - 128, wgate, wup, wdown, smem);
    return;
  }
  const int h = cta >> 2, j = cta & 3;
  const int g = lane >> 2, c = lane & 3;
  const uint32_t sb = smem_u32(smem);
  const int mg = warp & 1, kq = warp >> 1;

  uint32_t wq[RK][3][4];
  uint32_t wo[2][8][4];
  {
    for (int i = t; i < 128 * 4; i += 256)
      asm volatile("prefetch.global.L2 [%0];" ::"l"(Wo + (size_t)(h * 128 + (i >> 2)) * DM + 256 * j + (i & 3) * 64));
    for (int i = t; i < 1024 * 12; i += 256) {
      int k = i / 12, ch = i - 12 * k;
      int F = 96 * j + 8 * ch;
      const bf16* W = F < 128 ? Wq : (F < 256 ? Wk : Wv);
      cp_async16(sb + k * 192 + ch * 16, W + (size_t)k * HD + h * 128 + (F & 127));
    }
    cp_commit(); cp_wait<0>();
    __syncthreads();
    uint32_t tmp[SK][3][4];
#pragma unroll
    for (int ks = 0; ks < 16; ks++) {
#pragma unroll
      for (int tt = 0; tt < 3; tt++) {
        int tile = 3 * mg + tt;
        int k = (16 * kq + ks) * 16 + (lane & 7) + 8 * (lane >> 4);
        uint32_t addr = sb + k * 192 + tile * 32 + 16 * ((lane >> 3) & 1);
        if (ks < RK) ldsm4t(wq[ks][tt][0], wq[ks][tt][1], wq[ks][tt][2], wq[ks][tt][3], addr);
        else ldsm4t(tmp[ks - RK][tt][0], tmp[ks - RK][tt][1], tmp[ks - RK][tt][2], tmp[ks - RK][tt][3], addr);
      }
    }
    __syncthreads();
#pragma unroll
    for (int ks = 0; ks < SK; ks++)
#pragma unroll
      for (int tt = 0; tt < 3; tt++)
        *reinterpret_cast<uint4*>(smem + OFF_WQS + (((warp * SK + ks) * 3 + tt) * 32 + lane) * 16) =
            make_uint4(tmp[ks][tt][0], tmp[ks][tt][1], tmp[ks][tt][2], tmp[ks][tt][3]);
    for (int i = t; i < 128 * 32; i += 256) {
      int e = i >> 5, ch = i & 31;
      cp_async16(sb + CH_STG2 + e * 512 + ch * 16, Wo + (size_t)(h * 128 + e) * DM + 256 * j + ch * 8);
    }
    cp_commit(); cp_wait<0>();
    __syncthreads();
#pragma unroll
    for (int tt = 0; tt < 2; tt++)
#pragma unroll
      for (int ks = 0; ks < 8; ks++) {
        int e = 16 * ks + (lane & 7) + 8 * (lane >> 4);
        uint32_t addr = sb + CH_STG2 + e * 512 + (32 * warp + 16 * tt + 8 * ((lane >> 3) & 1)) * 2;
        ldsm4t(wo[tt][ks][0], wo[tt][ks][1], wo[tt][ks][2], wo[tt][ks][3], addr);
      }
    if (t == 0) {
      mbar_init(sb + OFF_BAR, 1); mbar_init(sb + OFF_BAR + 8, 1);
      asm volatile("fence.mbarrier_init.release.cluster;" ::: "memory");
    }
    __syncthreads();
    asm volatile("fence.proxy.async.shared::cta;" ::: "memory");
  }
  auto prefetch_tok = [&](int s) {
    const int i = t - 192;
    const uint32_t dst = sb + OFF_TOK + (s & 1) * TOK_BYTES + (i >> 4) * TP + (i & 15) * 16;
    const bf16* src = g_qkv + (size_t)(s * 32 + (i >> 4)) * NQKV + HD + h * 128 + (i & 15) * 8;
#pragma unroll
    for (int r = 0; r < 8; r++) {
      cp_async16(dst + 4 * r * TP, src + (size_t)4 * r * NQKV);
      cp_async16(dst + (32 + 4 * r) * TP, src + (size_t)4 * r * NQKV + HD);
    }
    cp_async16(dst + 64 * TP, src + (size_t)(8 * j) * NQKV - HD);
    cp_async16(dst + 68 * TP, src + (size_t)(8 * j + 4) * NQKV - HD);
    cp_commit();
  };
  auto side_work = [&](int s) {
    if (warp >= 6) {
      prefetch_tok(s + 1);
    } else {
      const int slot2 = (s + 2) & 3;
      const int i = t - 128;
      st_pub128(&g_bufA[slot2][cta][i], SENT);
      if (i < 32) st_pub128(&g_bufA[slot2][cta][64 + i], SENT);
      if (i < 8) st_pub128(&g_bufC[slot2][8 * cta + i], SENT);
      uint4* bb = &g_bufB[slot2][32 * j + (i >> 1)][0][0] + 2 * h + (i & 1);
#pragma unroll
      for (int col = 0; col < 8; col++) st_pub128(bb + 64 * col, SENT);
    }
  };
  if (warp >= 6) prefetch_tok(0);
  for (int i = t; i < 1024; i += 256) {
    int r = i >> 7, k = (i & 127) * 8;
    uint4 v = *reinterpret_cast<const uint4*>(mem0 + r * 1024 + k);
    unsigned short* d = reinterpret_cast<unsigned short*>(smem + OFF_MEMT) + k * 8 + r;
    d[0] = (unsigned short)v.x; d[8] = (unsigned short)(v.x >> 16); d[16] = (unsigned short)v.y; d[24] = (unsigned short)(v.y >> 16);
    d[32] = (unsigned short)v.z; d[40] = (unsigned short)(v.z >> 16); d[48] = (unsigned short)v.w; d[56] = (unsigned short)(v.w >> 16);
  }
  __syncthreads();
  const uint32_t p2dst0 = sb + OFF_QKVM + t * 16, p2dst1 = p2dst0 + 4096;
  const int p0idx = 256 * kq + 128 * mg + lane;
  uint32_t tpub = 0;
  const uint32_t dA = DLY_A, dB = DLY_B, dC = DLY_C;
  TS(0);
  for (int s = 0; s < NSEG; s++) {
    const int slot = s & 3, slot2 = (s + 2) & 3;
    if (s > 0) {
      const uint4* src = &g_bufC[(s - 1) & 3][p0idx];
      uint4 v[4];
      wait_until(tpub, dC);
#pragma unroll
      for (int i = 0; i < 4; i++) v[i] = ld_poll(src + 32 * i);
      int it = 0;
      while (!__all_sync(0xffffffffu, pkt_ok(v[0]) && pkt_ok(v[1]) && pkt_ok(v[2]) && pkt_ok(v[3])) && ++it < POLL_MAX) {
#pragma unroll
        for (int i = 0; i < 4; i++)
          if (!pkt_ok(v[i])) v[i] = ld_poll(src + 32 * i);
      }
#pragma unroll
      for (int i = 0; i < 4; i++) sts128(sb + OFF_MEMT + (p0idx + 32 * i) * 16, v[i]);
      TS(1);
      asm volatile("bar.sync %0, 64;" ::"r"(1 + kq) : "memory");
      TS(2);
    }
    {
      float acc[2][3][4];
#pragma unroll
      for (int a = 0; a < 2; a++)
#pragma unroll
        for (int tt = 0; tt < 3; tt++)
#pragma unroll
          for (int i = 0; i < 4; i++) acc[a][tt][i] = 0.f;
      uint4 sa[SK][3];
#pragma unroll
      for (int kp = 0; kp < 8; kp++) {
        uint32_t b0, b1, b2, b3;
        ldsm4t(b0, b1, b2, b3, sb + OFF_MEMT + ((16 * kq + 2 * kp) * 16 + lane) * 16);
#pragma unroll
        for (int u = 0; u < 2; u++) {
          int ks = 2 * (kp + 1) + u;
          if (ks >= RK && ks < 16) {
#pragma unroll
            for (int tt = 0; tt < 3; tt++)
              sa[ks - RK][tt] = *reinterpret_cast<const uint4*>(smem + OFF_WQS + (((warp * SK + (ks - RK)) * 3 + tt) * 32 + lane) * 16);
          }
        }
#pragma unroll
        for (int u = 0; u < 2; u++) {
          int ks = 2 * kp + u;
#pragma unroll
          for (int tt = 0; tt < 3; tt++) {
            if (ks < RK) mma16816(acc[u][tt], wq[ks][tt][0], wq[ks][tt][1], wq[ks][tt][2], wq[ks][tt][3], u ? b2 : b0, u ? b3 : b1);
            else mma16816(acc[u][tt], sa[ks - RK][tt].x, sa[ks - RK][tt].y, sa[ks - RK][tt].z, sa[ks - RK][tt].w, u ? b2 : b0, u ? b3 : b1);
          }
        }
      }
#pragma unroll
      for (int tt = 0; tt < 3; tt++)
        *reinterpret_cast<float4*>(smem + OFF_RED + ((kq * 6 + 3 * mg + tt) * 32 + lane) * 16) =
            make_float4(acc[0][tt][0] + acc[1][tt][0], acc[0][tt][1] + acc[1][tt][1], acc[0][tt][2] + acc[1][tt][2], acc[0][tt][3] + acc[1][tt][3]);
    }
    TS(3);
    __syncthreads();
    TS(4);
    if (warp < 6) {
      float4 r = *reinterpret_cast<const float4*>(smem + OFF_RED + ((0 * 6 + warp) * 32 + lane) * 16);
#pragma unroll
      for (int q = 1; q < 4; q++) {
        float4 x = *reinterpret_cast<const float4*>(smem + OFF_RED + ((q * 6 + warp) * 32 + lane) * 16);
        r.x += x.x; r.y += x.y; r.z += x.z; r.w += x.w;
      }
      uint32_t* dst = reinterpret_cast<uint32_t*>(&g_bufA[slot][cta][16 * warp + g]) + c;
      st_pub32(dst, desent(pack2(r.x, r.y)));
      st_pub32(dst + 32, desent(pack2(r.z, r.w)));
    }
    tpub = clk32();
    {
      const uint4* src = &g_bufA[slot][4 * h][t];
      wait_until(tpub, dA);
      uint4 v0 = ld_poll(src);
      uint4 v1 = make_uint4(0, 0, 0, 0);
      if (t < 128) v1 = ld_poll(src + 256);
      int it = 0;
      while (!__all_sync(0xffffffffu, pkt_ok(v0) && pkt_ok(v1)) && ++it < POLL_MAX) {
        if (!pkt_ok(v0)) v0 = ld_poll(src);
        if (!pkt_ok(v1)) v1 = ld_poll(src + 256);
      }
      sts128(p2dst0, v0);
      if (t < 128) sts128(p2dst1, v1);
    }
    TS(5);
    if (warp >= 6) cp_wait<0>();
    __syncthreads();
    TS(6);
    const uint32_t tok = sb + OFF_TOK + (s & 1) * TOK_BYTES;
    if (s < NSEG - 1) {
      if (warp < 4) attn8<false>(sb, tok, lane, warp, 0, nullptr);
      else if (VAR == 1 || VAR == 3) side_work(s);
      else if (VAR == 4) attn8<true>(sb, tok, lane, warp - 4, 8 * j + g, g_otok + (size_t)(s * 32 + 8 * j + g) * HD + h * 128);
      TS(7);
      __syncthreads();
      TS(8);
      {
        float acc[2][2][4];
#pragma unroll
        for (int a = 0; a < 2; a++)
#pragma unroll
          for (int tt = 0; tt < 2; tt++)
#pragma unroll
            for (int i = 0; i < 4; i++) acc[a][tt][i] = 0.f;
        uint32_t b[4][4];
#pragma unroll
        for (int kp = 0; kp < 4; kp++) ldsm4(b[kp][0], b[kp][1], b[kp][2], b[kp][3], sb + OFF_SA + (lane & 7) * TP + (32 * kp + 8 * (lane >> 3)) * 2);
#pragma unroll
        for (int kp = 0; kp < 4; kp++) {
#pragma unroll
          for (int tt = 0; tt < 2; tt++) {
            mma16816(acc[0][tt], wo[tt][2 * kp][0], wo[tt][2 * kp][1], wo[tt][2 * kp][2], wo[tt][2 * kp][3], b[kp][0], b[kp][1]);
            mma16816(acc[1][tt], wo[tt][2 * kp + 1][0], wo[tt][2 * kp + 1][1], wo[tt][2 * kp + 1][2], wo[tt][2 * kp + 1][3], b[kp][2], b[kp][3]);
          }
        }
        const int off = (g * 32 + h) * 4 + c;
#pragma unroll
        for (int tt = 0; tt < 2; tt++) {
          int r0 = 32 * j + 4 * warp + 2 * tt;
          uint32_t x0 = __float_as_uint(acc[0][tt][0] + acc[1][tt][0]), x1 = __float_as_uint(acc[0][tt][1] + acc[1][tt][1]);
          uint32_t x2 = __float_as_uint(acc[0][tt][2] + acc[1][tt][2]), x3 = __float_as_uint(acc[0][tt][3] + acc[1][tt][3]);
          x0 = x0 == SENT ? 0x7FFFFFFFu : x0; x1 = x1 == SENT ? 0x7FFFFFFFu : x1;
          x2 = x2 == SENT ? 0x7FFFFFFFu : x2; x3 = x3 == SENT ? 0x7FFFFFFFu : x3;
          st_pub64(reinterpret_cast<uint2*>(&g_bufB[slot][r0][0][0]) + off, x0, x1);
          st_pub64(reinterpret_cast<uint2*>(&g_bufB[slot][r0 + 1][0][0]) + off, x2, x3);
        }
        tpub = clk32();
      }
      if ((VAR == 2 || VAR == 3) && warp >= 4) attn8<true>(sb, tok, lane, warp - 4, 8 * j + g, g_otok + (size_t)(s * 32 + 8 * j + g) * HD + h * 128);
      TS(9);
      {
        const uint4* src = &g_bufB[slot][cta][0][0] + 64 * warp + 2 * lane;
        wait_until(tpub, dB);
        uint4 v0 = ld_poll(src), v1 = ld_poll(src + 1);
        int it = 0;
          while (!__all_sync(0xffffffffu, pkt_ok(v0) && pkt_ok(v1)) && ++it < POLL_MAX) {
            if (!pkt_ok(v0)) v0 = ld_poll(src);
          if (!pkt_ok(v1)) v1 = ld_poll(src + 1);
        }
        TS(10);
        const bool hi = lane & 16;
        float a0 = __uint_as_float(hi ? v1.x : v0.x), a1 = __uint_as_float(hi ? v1.y : v0.y);
        float a2 = __uint_as_float(hi ? v1.z : v0.z), a3 = __uint_as_float(hi ? v1.w : v0.w);
        float b0 = __uint_as_float(hi ? v0.x : v1.x), b1 = __uint_as_float(hi ? v0.y : v1.y);
        float b2 = __uint_as_float(hi ? v0.z : v1.z), b3 = __uint_as_float(hi ? v0.w : v1.w);
        a0 += __shfl_xor_sync(0xffffffffu, b0, 16); a1 += __shfl_xor_sync(0xffffffffu, b1, 16);
        a2 += __shfl_xor_sync(0xffffffffu, b2, 16); a3 += __shfl_xor_sync(0xffffffffu, b3, 16);
        const bool h8 = lane & 8;
        float k0 = h8 ? a2 : a0, k1 = h8 ? a3 : a1, s0 = h8 ? a0 : a2, s1 = h8 ? a1 : a3;
        k0 += __shfl_xor_sync(0xffffffffu, s0, 8); k1 += __shfl_xor_sync(0xffffffffu, s1, 8);
        const bool h4 = lane & 4;
        float z = h4 ? k1 : k0, zs = h4 ? k0 : k1;
        z += __shfl_xor_sync(0xffffffffu, zs, 4);
        z += __shfl_xor_sync(0xffffffffu, z, 2);
        z += __shfl_xor_sync(0xffffffffu, z, 1);
        float zo = __shfl_xor_sync(0xffffffffu, z, 4);
        if ((lane & 7) == 0) {
          uint32_t* d = reinterpret_cast<uint32_t*>(&g_bufC[slot][8 * cta + warp]) + (lane >> 3);
          st_pub32(d, desent(pack2(z, zo)));
        }
        tpub = clk32();
      }
    }
    if (warp >= 4) {
      if ((s == NSEG - 1 || VAR == 1) && !NOTOK) attn8<true>(sb, tok, lane, warp - 4, 8 * j + g, g_otok + (size_t)(s * 32 + 8 * j + g) * HD + h * 128);
      if (s < NSEG - 1 && (VAR == 2 || VAR == 4)) side_work(s);
    }
    TS(11);
  }
}

__device__ void moe_part(int m, const bf16* __restrict__ wg, const bf16* __restrict__ wu, const bf16* __restrict__ wd, uint8_t* smem) {
  const int t = threadIdx.x, warp = t >> 5, lane = t & 31;
  float* xs = reinterpret_cast<float*>(smem);
  float* red = reinterpret_cast<float*>(smem + 8192);
  float* hs = reinterpret_cast<float*>(smem + 65536);
  __shared__ float bv[8];
  __shared__ int bi[8];
  __shared__ int sel[2];
  int first = -1;
  for (int pass = 0; pass < 2; pass++) {
    float best = -INFINITY; int bidx = 0x7fffffff;
    for (int i = t; i < S_LEN; i += 256) {
      float v = g_r[i];
      if (i == first) continue;
      if (v > best || (v == best && i < bidx) || bidx == 0x7fffffff) { best = v; bidx = i; }
    }
#pragma unroll
    for (int o = 16; o > 0; o >>= 1) {
      float ov = __shfl_xor_sync(0xffffffffu, best, o); int oi = __shfl_xor_sync(0xffffffffu, bidx, o);
      if (oi != 0x7fffffff && (bidx == 0x7fffffff || ov > best || (ov == best && oi < bidx))) { best = ov; bidx = oi; }
    }
    if (lane == 0) { bv[warp] = best; bi[warp] = bidx; }
    __syncthreads();
    if (t == 0) {
      float b = bv[0]; int ix = bi[0];
      for (int w = 1; w < 8; w++) if (bv[w] > b || (bv[w] == b && bi[w] < ix)) { b = bv[w]; ix = bi[w]; }
      sel[pass] = ix;
    }
    __syncthreads();
    first = sel[0];
  }
  const int s0 = sel[0], s1 = sel[1];
  for (int i = t; i < 2048; i += 256) xs[i] = __bfloat162float(g_xn[(size_t)(i < 1024 ? s0 : s1) * DM + (i & 1023)]);
  __syncthreads();
  {
    int cg = t % 112, kh = t / 112;
    float a[2][2][8];
#pragma unroll
    for (int i = 0; i < 8; i++) { a[0][0][i] = a[0][1][i] = a[1][0][i] = a[1][1][i] = 0.f; }
    if (kh < 2) {
      const bf16* pg = wg + (size_t)(kh * 512) * FF + 896 * m + cg * 8;
      const bf16* pu = wu + (size_t)(kh * 512) * FF + 896 * m + cg * 8;
#pragma unroll 8
      for (int k = 0; k < 512; k++) {
        uint4 gv = __ldg(reinterpret_cast<const uint4*>(pg + (size_t)k * FF));
        uint4 uv = __ldg(reinterpret_cast<const uint4*>(pu + (size_t)k * FF));
        float x0 = xs[kh * 512 + k], x1 = xs[1024 + kh * 512 + k];
        float gf[8] = {bflo(gv.x), bfhi(gv.x), bflo(gv.y), bfhi(gv.y), bflo(gv.z), bfhi(gv.z), bflo(gv.w), bfhi(gv.w)};
        float uf[8] = {bflo(uv.x), bfhi(uv.x), bflo(uv.y), bfhi(uv.y), bflo(uv.z), bfhi(uv.z), bflo(uv.w), bfhi(uv.w)};
#pragma unroll
        for (int i = 0; i < 8; i++) {
          a[0][0][i] += x0 * gf[i]; a[0][1][i] += x1 * gf[i];
          a[1][0][i] += x0 * uf[i]; a[1][1][i] += x1 * uf[i];
        }
      }
      if (kh == 1) {
#pragma unroll
        for (int i = 0; i < 8; i++) {
          red[(0 * 2 + 0) * 896 + cg * 8 + i] = a[0][0][i]; red[(0 * 2 + 1) * 896 + cg * 8 + i] = a[0][1][i];
          red[(1 * 2 + 0) * 896 + cg * 8 + i] = a[1][0][i]; red[(1 * 2 + 1) * 896 + cg * 8 + i] = a[1][1][i];
        }
      }
    }
    __syncthreads();
    if (kh == 0) {
#pragma unroll
      for (int i = 0; i < 8; i++) {
#pragma unroll
        for (int tk = 0; tk < 2; tk++) {
          float gq = bfr(a[0][tk][i] + red[(0 * 2 + tk) * 896 + cg * 8 + i]);
          float uq = bfr(a[1][tk][i] + red[(1 * 2 + tk) * 896 + cg * 8 + i]);
          float sg = bfr(gq / (1.0f + __expf(-gq)));
          g_h[tk][896 * m + cg * 8 + i] = __float2bfloat16_rn(sg * uq);
        }
      }
    }
    __threadfence();
    __syncthreads();
    if (t == 0) {
      atomicAdd(&g_moe_cnt, 1u);
      int it = 0;
      while (*reinterpret_cast<volatile unsigned*>(&g_moe_cnt) < 4u && ++it < (1 << 24)) {}
      __threadfence();
    }
    __syncthreads();
  }
  for (int i = t; i < 2 * FF; i += 256) {
    const volatile unsigned short* p = reinterpret_cast<const volatile unsigned short*>(&g_h[0][0]);
    hs[i] = __uint_as_float(((uint32_t)p[i]) << 16);
  }
  __syncthreads();
  {
    int cg = t & 31, ksl = t >> 5;
    float a[2][8];
#pragma unroll
    for (int i = 0; i < 8; i++) a[0][i] = a[1][i] = 0.f;
    const bf16* pd = wd + (size_t)(ksl * 448) * DM + 256 * m + cg * 8;
#pragma unroll 8
    for (int k = 0; k < 448; k++) {
      uint4 dv = __ldg(reinterpret_cast<const uint4*>(pd + (size_t)k * DM));
      float x0 = hs[ksl * 448 + k], x1 = hs[FF + ksl * 448 + k];
      float df[8] = {bflo(dv.x), bfhi(dv.x), bflo(dv.y), bfhi(dv.y), bflo(dv.z), bfhi(dv.z), bflo(dv.w), bfhi(dv.w)};
#pragma unroll
      for (int i = 0; i < 8; i++) { a[0][i] += x0 * df[i]; a[1][i] += x1 * df[i]; }
    }
#pragma unroll
    for (int i = 0; i < 8; i++) { red[(ksl * 2 + 0) * 256 + cg * 8 + i] = a[0][i]; red[(ksl * 2 + 1) * 256 + cg * 8 + i] = a[1][i]; }
    __syncthreads();
    for (int i = t; i < 512; i += 256) {
      int tk = i >> 8, col = i & 255;
      float y = 0.f;
#pragma unroll
      for (int q = 0; q < 8; q++) y += red[(q * 2 + tk) * 256 + col];
      float rr = g_r[tk == 0 ? s0 : s1];
      float sg = bfr(1.0f / (1.0f + __expf(-rr)));
      g_upd[tk][256 * m + col] = bfr(bfr(y) * sg);
    }
    if (m == 0 && t == 0) { g_sel[0] = s0; g_sel[1] = s1; }
  }
}

typedef CUresult (*EncodeFn)(CUtensorMap*, CUtensorMapDataType, cuuint32_t, void*, const cuuint64_t*, const cuuint64_t*,
                             const cuuint32_t*, const cuuint32_t*, CUtensorMapInterleave, CUtensorMapSwizzle,
                             CUtensorMapL2promotion, CUtensorMapFloatOOBfill);

static void make_map(EncodeFn enc, CUtensorMap* m, const void* ptr, uint64_t inner, uint64_t outer, uint32_t bi, uint32_t bo) {
  cuuint64_t dims[2] = {inner, outer};
  cuuint64_t strides[1] = {inner * 2};
  cuuint32_t box[2] = {bi, bo};
  cuuint32_t es[2] = {1, 1};
  enc(m, CU_TENSOR_MAP_DATA_TYPE_BFLOAT16, 2, const_cast<void*>(ptr), dims, strides, box, es, CU_TENSOR_MAP_INTERLEAVE_NONE,
      CU_TENSOR_MAP_SWIZZLE_128B, CU_TENSOR_MAP_L2_PROMOTION_L2_256B, CU_TENSOR_MAP_FLOAT_OOB_FILL_NONE);
}

extern "C" void kernel_launch(void* const* d_in, const int* in_sizes, int n_in, void* d_out, int out_size) {
  const bf16* x = (const bf16*)d_in[0];
  const bf16* mem0 = (const bf16*)d_in[1];
  const bf16* Wq = (const bf16*)d_in[2];
  const bf16* Wk = (const bf16*)d_in[3];
  const bf16* Wv = (const bf16*)d_in[4];
  const bf16* Wo = (const bf16*)d_in[5];
  const bf16* w_r = (const bf16*)d_in[8];
  const bf16* wg = (const bf16*)d_in[9];
  const bf16* wu = (const bf16*)d_in[10];
  const bf16* wd = (const bf16*)d_in[11];
  bf16* out = (bf16*)d_out;

  static EncodeFn enc = nullptr;
  static void *p_xn, *p_qkv, *p_otok;
  if (!enc) {
    cudaDriverEntryPointQueryResult qr;
    void* fn = nullptr;
    cudaGetDriverEntryPoint("cuTensorMapEncodeTiled", &fn, cudaEnableDefault, &qr);
    enc = (EncodeFn)fn;
    cudaGetSymbolAddress(&p_xn, g_xn);
    cudaGetSymbolAddress(&p_qkv, g_qkv);
    cudaGetSymbolAddress(&p_otok, g_otok);
    cudaFuncSetAttribute(gemm_kernel<256, 4, 0>, cudaFuncAttributeMaxDynamicSharedMemorySize, GemmSmem<256, 4>::TOTAL);
    cudaFuncSetAttribute(gemm_kernel<128, 6, 1>, cudaFuncAttributeMaxDynamicSharedMemorySize, GemmSmem<128, 6>::TOTAL);
    cudaFuncSetAttribute(chain_kernel, cudaFuncAttributeMaxDynamicSharedMemorySize, CH_SMEM);
  }
  CUtensorMap mA, mQ, mK, mV, mO, mWo;
  make_map(enc, &mA, p_xn, DM, S_LEN, 64, 128);
  make_map(enc, &mQ, Wq, HD, DM, 64, 64);
  make_map(enc, &mK, Wk, HD, DM, 64, 64);
  make_map(enc, &mV, Wv, HD, DM, 64, 64);
  make_map(enc, &mO, p_otok, HD, S_LEN, 64, 128);
  make_map(enc, &mWo, Wo, DM, HD, 64, 64);

  cudaStream_t st = cudaStreamPerThread;
  ln_kernel<<<256, 256, 0, st>>>(x, w_r);
  cudaLaunchAttribute cat[1];
  cat[0].id = cudaLaunchAttributeClusterDimension;
  cat[0].val.clusterDim.x = 2; cat[0].val.clusterDim.y = 1; cat[0].val.clusterDim.z = 1;
  cudaLaunchConfig_t cfg = {};
  cfg.gridDim = dim3(132); cfg.blockDim = dim3(288); cfg.dynamicSmemBytes = GemmSmem<256, 4>::TOTAL; cfg.stream = st;
  cfg.attrs = cat; cfg.numAttrs = 1;
  cudaLaunchKernelEx(&cfg, gemm_kernel<256, 4, 0>, mA, mQ, mK, mV, 16, 16, 16 * 48, (const bf16*)nullptr, (bf16*)p_qkv, Wq, Wk, Wv, Wo);
  chain_kernel<<<132, 256, CH_SMEM, st>>>(mem0, Wq, Wk, Wv, Wo, wg, wu, wd);
  cfg.gridDim = dim3(128); cfg.dynamicSmemBytes = GemmSmem<128, 6>::TOTAL;
  cudaLaunchKernelEx(&cfg, gemm_kernel<128, 6, 1>, mO, mWo, mWo, mWo, 64, 16, 16 * 8, x, out, Wq, Wk, Wv, Wo);
}
```

```cpp
#include <cuda_runtime.h>
#include <cuda_bf16.h>
#include <cuda.h>
#include <stdint.h>

typedef __nv_bfloat16 bf16;

#define S_LEN 2048
#define DM 1024
#define NH 32
#define DH 128
#define NSEG 64
#define SEGL 32
#define HD 4096
#define NQKV 12288
#define FF 3584
#define SENT 0xFFFFFFFFu

__device__ __align__(1024) bf16 g_xn[S_LEN * DM];
__device__ __align__(1024) bf16 g_qkv[(size_t)S_LEN * NQKV];
__device__ __align__(1024) bf16 g_otok[(size_t)S_LEN * HD];
__device__ float g_r[S_LEN];
__device__ __align__(128) uint4 g_bufA[4][128][96];
__device__ __align__(128) uint4 g_bufB[4][128][16][32];
__device__ __align__(128) uint4 g_bufC[4][1024];
__device__ __align__(128) bf16 g_h[2][FF];
__device__ float g_upd[2][DM];
__device__ int g_sel[2];
__device__ unsigned g_moe_cnt;
#define NOTOK 0
#define VAR 1
#define DLY_A 300u
#define DLY_B 800u
#define DLY_C 700u
#define TS(i)

__device__ __forceinline__ float bfr(float x) { return __bfloat162float(__float2bfloat16_rn(x)); }
__device__ __forceinline__ uint32_t pack2(float lo, float hi) {
  __nv_bfloat162 v = __floats2bfloat162_rn(lo, hi);
  return *reinterpret_cast<uint32_t*>(&v);
}
__device__ __forceinline__ float bflo(uint32_t v) { return __uint_as_float(v << 16); }
__device__ __forceinline__ float bfhi(uint32_t v) { return __uint_as_float(v & 0xFFFF0000u); }
__device__ __forceinline__ uint32_t smem_u32(const void* p) { return (uint32_t)__cvta_generic_to_shared(p); }

__device__ __forceinline__ uint4 ld_poll(const uint4* p) {
  uint4 v;
  asm volatile("ld.relaxed.gpu.global.v4.u32 {%0,%1,%2,%3},[%4];" : "=r"(v.x), "=r"(v.y), "=r"(v.z), "=r"(v.w) : "l"(p) : "memory");
  return v;
}
__device__ __forceinline__ void st_pub32(void* p, uint32_t v) {
  asm volatile("st.relaxed.gpu.global.u32 [%0],%1;" ::"l"(p), "r"(v) : "memory");
}
__device__ __forceinline__ void st_pub64(void* p, uint32_t a, uint32_t b) {
  asm volatile("st.relaxed.gpu.global.v2.u32 [%0],{%1,%2};" ::"l"(p), "r"(a), "r"(b) : "memory");
}
__device__ __forceinline__ bool pkt_ok(const uint4& v) { return v.x != SENT && v.y != SENT && v.z != SENT && v.w != SENT; }
__device__ __forceinline__ uint32_t desent(uint32_t v) { return v == SENT ? 0x7FFF7FFFu : v; }

__device__ __forceinline__ void ldsm4(uint32_t& r0, uint32_t& r1, uint32_t& r2, uint32_t& r3, uint32_t addr) {
  asm volatile("ldmatrix.sync.aligned.m8n8.x4.shared.b16 {%0,%1,%2,%3},[%4];" : "=r"(r0), "=r"(r1), "=r"(r2), "=r"(r3) : "r"(addr) : "memory");
}
__device__ __forceinline__ void ldsm4t(uint32_t& r0, uint32_t& r1, uint32_t& r2, uint32_t& r3, uint32_t addr) {
  asm volatile("ldmatrix.sync.aligned.m8n8.x4.trans.shared.b16 {%0,%1,%2,%3},[%4];" : "=r"(r0), "=r"(r1), "=r"(r2), "=r"(r3) : "r"(addr) : "memory");
}
__device__ __forceinline__ void mma16816(float (&d)[4], uint32_t a0, uint32_t a1, uint32_t a2, uint32_t a3, uint32_t b0, uint32_t b1) {
  asm volatile("mma.sync.aligned.m16n8k16.row.col.f32.bf16.bf16.f32 {%0,%1,%2,%3},{%4,%5,%6,%7},{%8,%9},{%0,%1,%2,%3};"
               : "+f"(d[0]), "+f"(d[1]), "+f"(d[2]), "+f"(d[3])
               : "r"(a0), "r"(a1), "r"(a2), "r"(a3), "r"(b0), "r"(b1));
}
__device__ __forceinline__ void cp_async16(uint32_t dst, const void* src) {
  asm volatile("cp.async.cg.shared.global [%0],[%1],16;" ::"r"(dst), "l"(src) : "memory");
}
__device__ __forceinline__ void cp_commit() { asm volatile("cp.async.commit_group;" ::: "memory"); }
template <int N>
__device__ __forceinline__ void cp_wait() { asm volatile("cp.async.wait_group %0;" ::"n"(N) : "memory"); }

__device__ __forceinline__ void mbar_init(uint32_t bar, uint32_t cnt) { asm volatile("mbarrier.init.shared::cta.b64 [%0],%1;" ::"r"(bar), "r"(cnt) : "memory"); }
__device__ __forceinline__ void mbar_expect_tx(uint32_t bar, uint32_t bytes) {
  asm volatile("mbarrier.arrive.expect_tx.shared::cta.b64 _,[%0],%1;" ::"r"(bar), "r"(bytes) : "memory");
}
__device__ __forceinline__ void mbar_arrive(uint32_t bar) { asm volatile("mbarrier.arrive.shared::cta.b64 _,[%0];" ::"r"(bar) : "memory"); }
__device__ __forceinline__ void mbar_wait(uint32_t bar, uint32_t parity) {
  asm volatile(
      "{\n.reg .pred p;\n"
      "WAIT_LOOP:\n"
      "mbarrier.try_wait.parity.shared::cta.b64 p,[%0],%1;\n"
      "@p bra WAIT_DONE;\n"
      "bra WAIT_LOOP;\n"
      "WAIT_DONE:\n}\n" ::"r"(bar), "r"(parity) : "memory");
}
__device__ __forceinline__ void tma_load2d(uint32_t dst, const CUtensorMap* tm, uint32_t bar, int c0, int c1) {
  asm volatile("cp.async.bulk.tensor.2d.shared::cluster.global.mbarrier::complete_tx::bytes [%0],[%1,{%3,%4}],[%2];"
               ::"r"(dst), "l"(tm), "r"(bar), "r"(c0), "r"(c1) : "memory");
}
__device__ __forceinline__ void tma_load2d_mc(uint32_t dst, const CUtensorMap* tm, uint32_t bar, int c0, int c1, uint16_t mask) {
  asm volatile("cp.async.bulk.tensor.2d.shared::cluster.global.mbarrier::complete_tx::bytes.multicast::cluster [%0],[%1,{%3,%4}],[%2],%5;"
               ::"r"(dst), "l"(tm), "r"(bar), "r"(c0), "r"(c1), "h"(mask) : "memory");
}
__device__ __forceinline__ void mbar_arrive_cluster(uint32_t bar, uint32_t cta) {
  asm volatile("{\n.reg .b32 ra;\nmapa.shared::cluster.u32 ra,%0,%1;\nmbarrier.arrive.shared::cluster.b64 _,[ra];\n}\n" ::"r"(bar), "r"(cta) : "memory");
}
__device__ __forceinline__ void cluster_sync() {
  asm volatile("barrier.cluster.arrive.release.aligned;\nbarrier.cluster.wait.acquire.aligned;\n" ::: "memory");
}
__device__ __forceinline__ void wg_fence() { asm volatile("wgmma.fence.sync.aligned;" ::: "memory"); }
__device__ __forceinline__ void wg_commit() { asm volatile("wgmma.commit_group.sync.aligned;" ::: "memory"); }
template <int N>
__device__ __forceinline__ void wg_wait() { asm volatile("wgmma.wait_group.sync.aligned %0;" ::"n"(N) : "memory"); }
__device__ __forceinline__ uint64_t make_desc(uint32_t addr, uint32_t lbo, uint32_t sbo) {
  return (uint64_t)((addr & 0x3FFFF) >> 4) | ((uint64_t)(lbo >> 4) << 16) | ((uint64_t)(sbo >> 4) << 32) | (1ull << 62);
}

__device__ __forceinline__ void wgmma_m64n256k16(float (&d)[128], uint64_t da, uint64_t db, int scaleD) {
  asm volatile(
    "{\n.reg .pred p;\nsetp.ne.b32 p, %130, 0;\n"
    "wgmma.mma_async.sync.aligned.m64n256k16.f32.bf16.bf16 "
    "{%0, %1, %2, %3, %4, %5, %6, %7, %8, %9, %10, %11, %12, %13, %14, %15, %16, %17, %18, %19, %20, %21, %22, %23, %24, %25, %26, %27, %28, %29, %30, %31, %32, %33, %34, %35, %36, %37, %38, %39, %40, %41, %42, %43, %44, %45, %46, %47, %48, %49, %50, %51, %52, %53, %54, %55, %56, %57, %58, %59, %60, %61, %62, %63, %64, %65, %66, %67, %68, %69, %70, %71, %72, %73, %74, %75, %76, %77, %78, %79, %80, %81, %82, %83, %84, %85, %86, %87, %88, %89, %90, %91, %92, %93, %94, %95, %96, %97, %98, %99, %100, %101, %102, %103, %104, %105, %106, %107, %108, %109, %110, %111, %112, %113, %114, %115, %116, %117, %118, %119, %120, %121, %122, %123, %124, %125, %126, %127}, %128, %129, p, 1, 1, 0, 1;\n}\n"
    : "+f"(d[0]), "+f"(d[1]), "+f"(d[2]), "+f"(d[3]), "+f"(d[4]), "+f"(d[5]), "+f"(d[6]), "+f"(d[7]), "+f"(d[8]), "+f"(d[9]), "+f"(d[10]), "+f"(d[11]), "+f"(d[12]), "+f"(d[13]), "+f"(d[14]), "+f"(d[15]), "+f"(d[16]), "+f"(d[17]), "+f"(d[18]), "+f"(d[19]), "+f"(d[20]), "+f"(d[21]), "+f"(d[22]), "+f"(d[23]), "+f"(d[24]), "+f"(d[25]), "+f"(d[26]), "+f"(d[27]), "+f"(d[28]), "+f"(d[29]), "+f"(d[30]), "+f"(d[31]), "+f"(d[32]), "+f"(d[33]), "+f"(d[34]), "+f"(d[35]), "+f"(d[36]), "+f"(d[37]), "+f"(d[38]), "+f"(d[39]), "+f"(d[40]), "+f"(d[41]), "+f"(d[42]), "+f"(d[43]), "+f"(d[44]), "+f"(d[45]), "+f"(d[46]), "+f"(d[47]), "+f"(d[48]), "+f"(d[49]), "+f"(d[50]), "+f"(d[51]), "+f"(d[52]), "+f"(d[53]), "+f"(d[54]), "+f"(d[55]), "+f"(d[56]), "+f"(d[57]), "+f"(d[58]), "+f"(d[59]), "+f"(d[60]), "+f"(d[61]), "+f"(d[62]), "+f"(d[63]), "+f"(d[64]), "+f"(d[65]), "+f"(d[66]), "+f"(d[67]), "+f"(d[68]), "+f"(d[69]), "+f"(d[70]), "+f"(d[71]), "+f"(d[72]), "+f"(d[73]), "+f"(d[74]), "+f"(d[75]), "+f"(d[76]), "+f"(d[77]), "+f"(d[78]), "+f"(d[79]), "+f"(d[80]), "+f"(d[81]), "+f"(d[82]), "+f"(d[83]), "+f"(d[84]), "+f"(d[85]), "+f"(d[86]), "+f"(d[87]), "+f"(d[88]), "+f"(d[89]), "+f"(d[90]), "+f"(d[91]), "+f"(d[92]), "+f"(d[93]), "+f"(d[94]), "+f"(d[95]), "+f"(d[96]), "+f"(d[97]), "+f"(d[98]), "+f"(d[99]), "+f"(d[100]), "+f"(d[101]), "+f"(d[102]), "+f"(d[103]), "+f"(d[104]), "+f"(d[105]), "+f"(d[106]), "+f"(d[107]), "+f"(d[108]), "+f"(d[109]), "+f"(d[110]), "+f"(d[111]), "+f"(d[112]), "+f"(d[113]), "+f"(d[114]), "+f"(d[115]), "+f"(d[116]), "+f"(d[117]), "+f"(d[118]), "+f"(d[119]), "+f"(d[120]), "+f"(d[121]), "+f"(d[122]), "+f"(d[123]), "+f"(d[124]), "+f"(d[125]), "+f"(d[126]), "+f"(d[127])
    : "l"(da), "l"(db), "r"(scaleD));
}

__device__ __forceinline__ void wgmma_m64n128k16(float (&d)[64], uint64_t da, uint64_t db, int scaleD) {
  asm volatile(
    "{\n.reg .pred p;\nsetp.ne.b32 p, %66, 0;\n"
    "wgmma.mma_async.sync.aligned.m64n128k16.f32.bf16.bf16 "
    "{%0, %1, %2, %3, %4, %5, %6, %7, %8, %9, %10, %11, %12, %13, %14, %15, %16, %17, %18, %19, %20, %21, %22, %23, %24, %25, %26, %27, %28, %29, %30, %31, %32, %33, %34, %35, %36, %37, %38, %39, %40, %41, %42, %43, %44, %45, %46, %47, %48, %49, %50, %51, %52, %53, %54, %55, %56, %57, %58, %59, %60, %61, %62, %63}, %64, %65, p, 1, 1, 0, 1;\n}\n"
    : "+f"(d[0]), "+f"(d[1]), "+f"(d[2]), "+f"(d[3]), "+f"(d[4]), "+f"(d[5]), "+f"(d[6]), "+f"(d[7]), "+f"(d[8]), "+f"(d[9]), "+f"(d[10]), "+f"(d[11]), "+f"(d[12]), "+f"(d[13]), "+f"(d[14]), "+f"(d[15]), "+f"(d[16]), "+f"(d[17]), "+f"(d[18]), "+f"(d[19]), "+f"(d[20]), "+f"(d[21]), "+f"(d[22]), "+f"(d[23]), "+f"(d[24]), "+f"(d[25]), "+f"(d[26]), "+f"(d[27]), "+f"(d[28]), "+f"(d[29]), "+f"(d[30]), "+f"(d[31]), "+f"(d[32]), "+f"(d[33]), "+f"(d[34]), "+f"(d[35]), "+f"(d[36]), "+f"(d[37]), "+f"(d[38]), "+f"(d[39]), "+f"(d[40]), "+f"(d[41]), "+f"(d[42]), "+f"(d[43]), "+f"(d[44]), "+f"(d[45]), "+f"(d[46]), "+f"(d[47]), "+f"(d[48]), "+f"(d[49]), "+f"(d[50]), "+f"(d[51]), "+f"(d[52]), "+f"(d[53]), "+f"(d[54]), "+f"(d[55]), "+f"(d[56]), "+f"(d[57]), "+f"(d[58]), "+f"(d[59]), "+f"(d[60]), "+f"(d[61]), "+f"(d[62]), "+f"(d[63])
    : "l"(da), "l"(db), "r"(scaleD));
}

template <int BN> struct WG;
template <> struct WG<256> { static __device__ __forceinline__ void mma(float (&d)[128], uint64_t a, uint64_t b, int s) { wgmma_m64n256k16(d, a, b, s); } };
template <> struct WG<128> { static __device__ __forceinline__ void mma(float (&d)[64], uint64_t a, uint64_t b, int s) { wgmma_m64n128k16(d, a, b, s); } };

__global__ void __launch_bounds__(256) ln_kernel(const bf16* __restrict__ x, const bf16* __restrict__ w_r) {
  int warp = threadIdx.x >> 5, lane = threadIdx.x & 31;
  int row = blockIdx.x * 8 + warp;
  const uint4* xp = reinterpret_cast<const uint4*>(x + (size_t)row * DM);
  uint4 v[4];
#pragma unroll
  for (int i = 0; i < 4; i++) v[i] = xp[lane + 32 * i];
  float f[32];
#pragma unroll
  for (int i = 0; i < 4; i++) {
    f[8 * i + 0] = bflo(v[i].x); f[8 * i + 1] = bfhi(v[i].x);
    f[8 * i + 2] = bflo(v[i].y); f[8 * i + 3] = bfhi(v[i].y);
    f[8 * i + 4] = bflo(v[i].z); f[8 * i + 5] = bfhi(v[i].z);
    f[8 * i + 6] = bflo(v[i].w); f[8 * i + 7] = bfhi(v[i].w);
  }
  float s = 0.f;
#pragma unroll
  for (int i = 0; i < 32; i++) s += f[i];
#pragma unroll
  for (int o = 16; o > 0; o >>= 1) s += __shfl_xor_sync(0xffffffffu, s, o);
  float mean = s * (1.0f / DM);
  float q = 0.f;
#pragma unroll
  for (int i = 0; i < 32; i++) { float d = f[i] - mean; q += d * d; }
#pragma unroll
  for (int o = 16; o > 0; o >>= 1) q += __shfl_xor_sync(0xffffffffu, q, o);
  float var = bfr(q * (1.0f / DM));
  float mb = bfr(mean);
  float den = bfr(sqrtf(bfr(var + 1e-5f)));
  const uint4* wp = reinterpret_cast<const uint4*>(w_r);
  uint4* op = reinterpret_cast<uint4*>(g_xn + (size_t)row * DM);
  float r = 0.f;
#pragma unroll
  for (int i = 0; i < 4; i++) {
    uint4 w = wp[lane + 32 * i];
    float y[8];
#pragma unroll
    for (int k = 0; k < 8; k++) y[k] = bfr(bfr(f[8 * i + k] - mb) / den);
    r += y[0] * bflo(w.x) + y[1] * bfhi(w.x) + y[2] * bflo(w.y) + y[3] * bfhi(w.y) + y[4] * bflo(w.z) + y[5] * bfhi(w.z) +
         y[6] * bflo(w.w) + y[7] * bfhi(w.w);
    op[lane + 32 * i] = make_uint4(pack2(y[0], y[1]), pack2(y[2], y[3]), pack2(y[4], y[5]), pack2(y[6], y[7]));
  }
#pragma unroll
  for (int o = 16; o > 0; o >>= 1) r += __shfl_xor_sync(0xffffffffu, r, o);
  if (lane == 0) g_r[row] = bfr(r);
  int gt = blockIdx.x * 256 + threadIdx.x;
  const uint4 sv = make_uint4(SENT, SENT, SENT, SENT);
  uint4* a = &g_bufA[0][0][0];
  for (int i = gt; i < 2 * 128 * 96; i += 65536) a[i] = sv;
  uint4* b = &g_bufB[0][0][0][0];
  for (int i = gt; i < 2 * 128 * 32 * 16; i += 65536) b[i] = sv;
  uint4* c = &g_bufC[0][0];
  for (int i = gt; i < 2 * 1024; i += 65536) c[i] = sv;
  if (gt == 0) g_moe_cnt = 0;
}

template <int BN, int STAGES>
struct GemmSmem {
  static constexpr int A_BYTES = 128 * 64 * 2;
  static constexpr int B_BYTES = 64 * BN * 2;
  static constexpr int STAGE_BYTES = A_BYTES + B_BYTES;
  static constexpr int TOTAL = STAGES * STAGE_BYTES + 1024 + 256;
};

__device__ __forceinline__ void quad_transpose(uint32_t (&v)[4], int c) {
  {
    uint32_t s0 = (c & 1) ? v[0] : v[1];
    uint32_t s1 = (c & 1) ? v[2] : v[3];
    uint32_t r0 = __shfl_xor_sync(0xffffffffu, s0, 1);
    uint32_t r1 = __shfl_xor_sync(0xffffffffu, s1, 1);
    if (c & 1) { v[0] = r0; v[2] = r1; } else { v[1] = r0; v[3] = r1; }
  }
  {
    uint32_t s0 = (c & 2) ? v[0] : v[2];
    uint32_t s1 = (c & 2) ? v[1] : v[3];
    uint32_t r0 = __shfl_xor_sync(0xffffffffu, s0, 2);
    uint32_t r1 = __shfl_xor_sync(0xffffffffu, s1, 2);
    if (c & 2) { v[0] = r0; v[1] = r1; } else { v[2] = r0; v[3] = r1; }
  }
}

__device__ __forceinline__ uint32_t add3(uint32_t a, uint32_t x, uint32_t b) {
  float lo = bfr(bflo(x) + bflo(a)) + bflo(b);
  float hi = bfr(bfhi(x) + bfhi(a)) + bfhi(b);
  return pack2(lo, hi);
}

template <int BN, int STAGES, int EPI>
__global__ void __launch_bounds__(288, 1)
gemm_kernel(const __grid_constant__ CUtensorMap tmA, const __grid_constant__ CUtensorMap tmB0,
            const __grid_constant__ CUtensorMap tmB1, const __grid_constant__ CUtensorMap tmB2,
            int kblocks, int tiles_m, int tiles_total, const bf16* __restrict__ xin, bf16* __restrict__ outp,
            const bf16* pf0, const bf16* pf1, const bf16* pf2, const bf16* pf3) {
  using SM = GemmSmem<BN, STAGES>;
  extern __shared__ uint8_t smem_raw[];
  uint32_t base = (smem_u32(smem_raw) + 1023) & ~1023u;
  uint32_t bars = base + STAGES * SM::STAGE_BYTES;
  int warp = threadIdx.x >> 5, lane = threadIdx.x & 31;
  uint32_t rank;
  asm volatile("mov.u32 %0,%%cluster_ctarank;" : "=r"(rank));
  const int cl = blockIdx.x >> 1, ncl = gridDim.x >> 1;
  const int pairs_m = tiles_m >> 1, pairs_total = tiles_total >> 1;
  if (threadIdx.x == 0) {
    for (int i = 0; i < STAGES; i++) { mbar_init(bars + 8 * i, 1); mbar_init(bars + 8 * (STAGES + i), 16); }
    asm volatile("fence.mbarrier_init.release.cluster;" ::: "memory");
  }
  __syncthreads();
  cluster_sync();
  if (warp == 8) {
    if (lane == 0) {
      int it = 0;
      for (int t = cl; t < pairs_total; t += ncl) {
        int tm = 2 * (t % pairs_m) + rank, tn = t / pairs_m;
        int n0 = tn * BN;
        const CUtensorMap* tb = &tmB0;
        if (EPI == 0) { int wsel = n0 >> 12; tb = wsel == 0 ? &tmB0 : (wsel == 1 ? &tmB1 : &tmB2); n0 &= 4095; }
        for (int kb = 0; kb < kblocks; kb++, it++) {
          int st = it % STAGES; uint32_t ph = (it / STAGES) & 1;
          mbar_wait(bars + 8 * (STAGES + st), ph ^ 1);
          uint32_t sa = base + st * SM::STAGE_BYTES, sb = sa + SM::A_BYTES;
          mbar_expect_tx(bars + 8 * st, SM::STAGE_BYTES);
          tma_load2d(sa, &tmA, bars + 8 * st, kb * 64, tm * 128);
#pragma unroll
          for (int i = 0; i < BN / 128; i++) {
            int bx = rank * (BN / 128) + i;
            tma_load2d_mc(sb + bx * 8192, tb, bars + 8 * st, n0 + bx * 64, kb * 64, (uint16_t)3);
          }
        }
      }
      if (EPI == 0 && blockIdx.x < 128) {
        const size_t o = (size_t)blockIdx.x * 32768;
#pragma unroll
        for (int q = 0; q < 4; q++) {
          asm volatile("cp.async.bulk.prefetch.L2.global [%0],%1;" ::"l"(pf0 + o + q * 8192), "r"(16384) : "memory");
          asm volatile("cp.async.bulk.prefetch.L2.global [%0],%1;" ::"l"(pf1 + o + q * 8192), "r"(16384) : "memory");
          asm volatile("cp.async.bulk.prefetch.L2.global [%0],%1;" ::"l"(pf2 + o + q * 8192), "r"(16384) : "memory");
          asm volatile("cp.async.bulk.prefetch.L2.global [%0],%1;" ::"l"(pf3 + o + q * 8192), "r"(16384) : "memory");
        }
      }
    }
    __syncwarp();
  } else {
    int wg = warp >> 2;
    int g = lane >> 2, c = lane & 3;
    int it = 0;
    float acc[BN / 2];
    for (int t = cl; t < pairs_total; t += ncl) {
      int tm = 2 * (t % pairs_m) + rank, tn = t / pairs_m;
      for (int kb = 0; kb < kblocks; kb++, it++) {
        int st = it % STAGES; uint32_t ph = (it / STAGES) & 1;
        mbar_wait(bars + 8 * st, ph);
        uint32_t sa = base + st * SM::STAGE_BYTES + wg * 8192, sb = base + st * SM::STAGE_BYTES + SM::A_BYTES;
        wg_fence();
#pragma unroll
        for (int kk = 0; kk < 4; kk++) {
          uint64_t da = make_desc(sa + kk * 32, 16, 1024);
          uint64_t db = make_desc(sb + kk * 2048, 8192, 1024);
          WG<BN>::mma(acc, da, db, (kb | kk) != 0);
        }
        wg_commit();
        if (kb > 0) {
          wg_wait<1>();
          int pst = (it - 1) % STAGES;
          if (lane < 2) mbar_arrive_cluster(bars + 8 * (STAGES + pst), lane);
        }
      }
      wg_wait<0>();
      { int pst = (it - 1) % STAGES; if (lane < 2) mbar_arrive_cluster(bars + 8 * (STAGES + pst), lane); }
      int row0 = tm * 128 + wg * 64 + (warp & 3) * 16 + g;
      int sel0 = -1, sel1 = -1;
      if (EPI == 1) { sel0 = g_sel[0]; sel1 = g_sel[1]; }
#pragma unroll
      for (int half = 0; half < 2; half++) {
        int row = row0 + half * 8;
#pragma unroll
        for (int q = 0; q < BN / 32; q++) {
          uint32_t v[4];
#pragma unroll
          for (int tt = 0; tt < 4; tt++) v[tt] = pack2(acc[(q * 4 + tt) * 4 + half * 2], acc[(q * 4 + tt) * 4 + half * 2 + 1]);
          quad_transpose(v, c);
          int col = tn * BN + q * 32 + c * 8;
          if (EPI == 0) {
            __stcs(reinterpret_cast<uint4*>(outp + (size_t)row * NQKV + col), make_uint4(v[0], v[1], v[2], v[3]));
          } else {
            uint4 xv = *reinterpret_cast<const uint4*>(xin + (size_t)row * DM + col);
            uint4 bv = *reinterpret_cast<const uint4*>(g_xn + (size_t)row * DM + col);
            if (row == sel0 || row == sel1) {
              const float* u = &g_upd[row == sel0 ? 0 : 1][col];
              bv.x = pack2(bflo(bv.x) + u[0], bfhi(bv.x) + u[1]);
              bv.y = pack2(bflo(bv.y) + u[2], bfhi(bv.y) + u[3]);
              bv.z = pack2(bflo(bv.z) + u[4], bfhi(bv.z) + u[5]);
              bv.w = pack2(bflo(bv.w) + u[6], bfhi(bv.w) + u[7]);
            }
            uint4 o = make_uint4(add3(v[0], xv.x, bv.x), add3(v[1], xv.y, bv.y), add3(v[2], xv.z, bv.z), add3(v[3], xv.w, bv.w));
            *reinterpret_cast<uint4*>(outp + (size_t)row * DM + col) = o;
          }
        }
      }
    }
  }
  cluster_sync();
}

#define RK 10
#define SK (16 - RK)
#define TP 272
#define OFF_WQS 0
#define OFF_MEMT (OFF_WQS + 8 * SK * 3 * 512)
#define OFF_RED (OFF_MEMT + 16384)
#define OFF_QKVM (OFF_RED + 12288)
#define OFF_TOK (OFF_QKVM + 6144)
#define TOK_BYTES (72 * TP)
#define OFF_SA (OFF_TOK + 2 * TOK_BYTES)
#define OFF_BAR (OFF_SA + 8 * TP)
#define CH_END (OFF_BAR + 64)
#define CH_STG2 (131072)
#define WSP 208
#define CH_SMEM (1024 * WSP + 1024)
static_assert(CH_END <= CH_SMEM, "smem");

__device__ void moe_part(int m, const bf16* __restrict__ wg, const bf16* __restrict__ wu, const bf16* __restrict__ wd, uint8_t* smem);

__device__ __forceinline__ void bulk_copy(uint32_t dst, const void* src, uint32_t bytes, uint32_t bar) {
  asm volatile("cp.async.bulk.shared::cluster.global.mbarrier::complete_tx::bytes [%0],[%1],%2,[%3];"
               ::"r"(dst), "l"(src), "r"(bytes), "r"(bar) : "memory");
}
__device__ __forceinline__ void st_pub128(void* p, uint32_t v) {
  asm volatile("st.relaxed.gpu.global.v4.u32 [%0],{%1,%1,%1,%1};" ::"l"(p), "r"(v) : "memory");
}
__device__ __forceinline__ void sts128(uint32_t addr, const uint4& v) {
  asm volatile("st.shared.v4.u32 [%0],{%1,%2,%3,%4};" ::"r"(addr), "r"(v.x), "r"(v.y), "r"(v.z), "r"(v.w) : "memory");
}

#define POLL_MAX (1 << 22)
__device__ __forceinline__ uint32_t clk32() { uint32_t c; asm volatile("mov.u32 %0,%%clock;" : "=r"(c)); return c; }
__device__ __forceinline__ void wait_until(uint32_t t0, uint32_t d) { while (clk32() - t0 < d) {} }
#define DLY_DEC 48u

__device__ __forceinline__ float ex2f(float x) { float y; asm("ex2.approx.ftz.f32 %0,%1;" : "=f"(y) : "f"(x)); return y; }
__device__ __forceinline__ float rcpf(float x) { float y; asm("rcp.approx.ftz.f32 %0,%1;" : "=f"(y) : "f"(x)); return y; }
template <bool TOK>
__device__ __forceinline__ void attn8(uint32_t sb, uint32_t tok, int lane, int wq4, int tr, bf16* otok_row) {
  const int g = lane >> 2, c = lane & 3;
  float sc[5][4];
#pragma unroll
  for (int n = 0; n < 5; n++)
#pragma unroll
    for (int i = 0; i < 4; i++) sc[n][i] = 0.f;
  const uint32_t tokrow = tok + (lane & 7) * TP + (lane >> 3) * 16;
  const uint32_t qaddr = TOK ? (tok + (64 + (lane & 7)) * TP + (lane >> 4) * 16) : (sb + OFF_QKVM + ((lane & 7) + 8 * (lane >> 4)) * 16);
#pragma unroll
  for (int kp = 0; kp < 4; kp++) {
    uint32_t q0[4], q1[4], km[4], kt[4][4];
    if (TOK) {
      ldsm4(q0[0], q0[1], q0[2], q0[3], qaddr + 64 * kp);
      ldsm4(q1[0], q1[1], q1[2], q1[3], qaddr + 64 * kp + 32);
    } else {
      ldsm4t(q0[0], q0[1], q0[2], q0[3], qaddr + 512 * kp);
      ldsm4t(q1[0], q1[1], q1[2], q1[3], qaddr + 512 * kp + 256);
    }
    ldsm4t(km[0], km[1], km[2], km[3], sb + OFF_QKVM + (128 + 32 * kp + lane) * 16);
#pragma unroll
    for (int n = 0; n < 4; n++) ldsm4(kt[n][0], kt[n][1], kt[n][2], kt[n][3], tokrow + 8 * n * TP + 64 * kp);
    mma16816(sc[0], q0[0], q0[1], q0[2], q0[3], km[0], km[1]);
#pragma unroll
    for (int n = 0; n < 4; n++) mma16816(sc[n + 1], q0[0], q0[1], q0[2], q0[3], kt[n][0], kt[n][1]);
    mma16816(sc[0], q1[0], q1[1], q1[2], q1[3], km[2], km[3]);
#pragma unroll
    for (int n = 0; n < 4; n++) mma16816(sc[n + 1], q1[0], q1[1], q1[2], q1[3], kt[n][2], kt[n][3]);
  }
  uint32_t vma[4], vmb[4], vt[4][4];
  ldsm4(vma[0], vma[1], vma[2], vma[3], sb + OFF_QKVM + (256 + 32 * wq4 + lane) * 16);
  ldsm4(vmb[0], vmb[1], vmb[2], vmb[3], sb + OFF_QKVM + (256 + 32 * wq4 + (lane ^ 8)) * 16);
#pragma unroll
  for (int n = 0; n < 4; n++) ldsm4t(vt[n][0], vt[n][1], vt[n][2], vt[n][3], tok + (32 + lane) * TP + (32 * wq4 + 8 * n) * 2);
  const float scale = 0.08838834764831845f;
  float m0 = -3.0e38f;
#pragma unroll
  for (int n = 0; n < 5; n++) {
    uint32_t p1 = pack2(sc[n][0], sc[n][1]);
    uint32_t p2 = pack2(bflo(p1) * scale, bfhi(p1) * scale);
    sc[n][0] = bflo(p2);
    sc[n][1] = bfhi(p2);
    if (TOK && n > 0) {
      int kt = 8 * (n - 1) + 2 * c;
      if (kt > tr) sc[n][0] = -1.0e9f;
      if (kt + 1 > tr) sc[n][1] = -1.0e9f;
    }
    m0 = fmaxf(m0, fmaxf(sc[n][0], sc[n][1]));
  }
  m0 = fmaxf(m0, __shfl_xor_sync(0xffffffffu, m0, 1));
  m0 = fmaxf(m0, __shfl_xor_sync(0xffffffffu, m0, 2));
  const float l2e = 1.4426950408889634f;
  float s0 = 0.f;
#pragma unroll
  for (int n = 0; n < 5; n++) {
    sc[n][0] = ex2f((sc[n][0] - m0) * l2e);
    sc[n][1] = ex2f((sc[n][1] - m0) * l2e);
    s0 += sc[n][0] + sc[n][1];
  }
  s0 += __shfl_xor_sync(0xffffffffu, s0, 1);
  s0 += __shfl_xor_sync(0xffffffffu, s0, 2);
  const float i0 = rcpf(s0);
  uint32_t pp[5];
#pragma unroll
  for (int n = 0; n < 5; n++) pp[n] = pack2(sc[n][0] * i0, sc[n][1] * i0);
  float o[4][4];
#pragma unroll
  for (int n = 0; n < 4; n++) {
#pragma unroll
    for (int i = 0; i < 4; i++) o[n][i] = 0.f;
    mma16816(o[n], pp[1], pp[1], pp[2], pp[2], vt[n][0], vt[n][1]);
  }
#pragma unroll
  for (int n = 0; n < 4; n++) mma16816(o[n], pp[3], pp[3], pp[4], pp[4], vt[n][2], vt[n][3]);
  mma16816(o[0], pp[0], 0u, 0u, 0u, vma[0], vma[1]);
  mma16816(o[1], pp[0], 0u, 0u, 0u, vmb[0], vmb[1]);
  mma16816(o[2], pp[0], 0u, 0u, 0u, vma[2], vma[3]);
  mma16816(o[3], pp[0], 0u, 0u, 0u, vmb[2], vmb[3]);
#pragma unroll
  for (int n = 0; n < 4; n++) {
    const int e = 32 * wq4 + 8 * n + 2 * c;
    if (TOK) *reinterpret_cast<uint32_t*>(otok_row + e) = pack2(o[n][0], o[n][1]);
    else asm volatile("st.shared.u32 [%0],%1;" ::"r"(sb + OFF_SA + g * TP + e * 2), "r"(pack2(o[n][0], o[n][1])) : "memory");
  }
}

__global__ void __launch_bounds__(256, 1)
chain_kernel(const bf16* __restrict__ mem0, const bf16* __restrict__ Wq, const bf16* __restrict__ Wk, const bf16* __restrict__ Wv,
             const bf16* __restrict__ Wo, const bf16* __restrict__ wgate, const bf16* __restrict__ wup, const bf16* __restrict__ wdown) {
  extern __shared__ __align__(1024) uint8_t smem[];
  const int cta = blockIdx.x, t = threadIdx.x, warp = t >> 5, lane = t & 31;
  if (cta >= 128) {
    moe_part(cta - 128, wgate, wup, wdown, smem);
    return;
  }
  const int h = cta >> 2, j = cta & 3;
  const int g = lane >> 2, c = lane & 3;
  const uint32_t sb = smem_u32(smem);
  const int mg = warp & 1, kq = warp >> 1;

  uint32_t wq[RK][3][4];
  uint32_t wo[2][8][4];
  {
    for (int i = t; i < 128 * 4; i += 256)
      asm volatile("prefetch.global.L2 [%0];" ::"l"(Wo + (size_t)(h * 128 + (i >> 2)) * DM + 256 * j + (i & 3) * 64));
    if (t < 192) {
      const int r0 = t / 12, ch = t - 12 * r0;
      const int F = 96 * j + 8 * ch;
      const bf16* src = (F < 128 ? Wq : (F < 256 ? Wk : Wv)) + (size_t)r0 * HD + h * 128 + (F & 127);
      const uint32_t dst = sb + r0 * WSP + ch * 16;
#pragma unroll 8
      for (int i = 0; i < 64; i++) cp_async16(dst + i * 16 * WSP, src + (size_t)i * 16 * HD);
    }
    TS(12);
    cp_commit(); cp_wait<0>();
    __syncthreads();
    TS(13);
    uint32_t tmp[SK][3][4];
#pragma unroll
    for (int ks = 0; ks < 16; ks++) {
#pragma unroll
      for (int tt = 0; tt < 3; tt++) {
        int tile = 3 * mg + tt;
        int k = (16 * kq + ks) * 16 + (lane & 7) + 8 * (lane >> 4);
        uint32_t addr = sb + k * WSP + tile * 32 + 16 * ((lane >> 3) & 1);
        if (ks < RK) ldsm4t(wq[ks][tt][0], wq[ks][tt][1], wq[ks][tt][2], wq[ks][tt][3], addr);
        else ldsm4t(tmp[ks - RK][tt][0], tmp[ks - RK][tt][1], tmp[ks - RK][tt][2], tmp[ks - RK][tt][3], addr);
      }
    }
    __syncthreads();
#pragma unroll
    for (int ks = 0; ks < SK; ks++)
#pragma unroll
      for (int tt = 0; tt < 3; tt++)
        *reinterpret_cast<uint4*>(smem + OFF_WQS + (((warp * SK + ks) * 3 + tt) * 32 + lane) * 16) =
            make_uint4(tmp[ks][tt][0], tmp[ks][tt][1], tmp[ks][tt][2], tmp[ks][tt][3]);
    TS(14);
    {
      const bf16* src = Wo + (size_t)(h * 128 + warp) * DM + 256 * j + lane * 8;
      const uint32_t dst = sb + CH_STG2 + warp * 528 + lane * 16;
#pragma unroll
      for (int i = 0; i < 16; i++) cp_async16(dst + i * 8 * 528, src + (size_t)i * 8 * DM);
    }
    cp_commit(); cp_wait<0>();
    __syncthreads();
#pragma unroll
    for (int tt = 0; tt < 2; tt++)
#pragma unroll
      for (int ks = 0; ks < 8; ks++) {
        int e = 16 * ks + (lane & 7) + 8 * (lane >> 4);
        uint32_t addr = sb + CH_STG2 + e * 528 + (32 * warp + 16 * tt + 8 * ((lane >> 3) & 1)) * 2;
        ldsm4t(wo[tt][ks][0], wo[tt][ks][1], wo[tt][ks][2], wo[tt][ks][3], addr);
      }
    TS(15);
    if (t == 0) {
      mbar_init(sb + OFF_BAR, 1); mbar_init(sb + OFF_BAR + 8, 1);
      asm volatile("fence.mbarrier_init.release.cluster;" ::: "memory");
    }
    __syncthreads();
    asm volatile("fence.proxy.async.shared::cta;" ::: "memory");
  }
  auto prefetch_tok = [&](int s) {
    const int i = t - 192;
    const uint32_t dst = sb + OFF_TOK + (s & 1) * TOK_BYTES + (i >> 4) * TP + (i & 15) * 16;
    const bf16* src = g_qkv + (size_t)(s * 32 + (i >> 4)) * NQKV + HD + h * 128 + (i & 15) * 8;
#pragma unroll
    for (int r = 0; r < 8; r++) {
      cp_async16(dst + 4 * r * TP, src + (size_t)4 * r * NQKV);
      cp_async16(dst + (32 + 4 * r) * TP, src + (size_t)4 * r * NQKV + HD);
    }
    cp_async16(dst + 64 * TP, src + (size_t)(8 * j) * NQKV - HD);
    cp_async16(dst + 68 * TP, src + (size_t)(8 * j + 4) * NQKV - HD);
    cp_commit();
  };
  auto side_work = [&](int s) {
    if (warp >= 6) {
      prefetch_tok(s + 1);
    } else {
      const int slot2 = (s + 2) & 3;
      const int i = t - 128;
      st_pub128(&g_bufA[slot2][cta][i], SENT);
      if (i < 32) st_pub128(&g_bufA[slot2][cta][64 + i], SENT);
      if (i < 8) st_pub128(&g_bufC[slot2][8 * cta + i], SENT);
      uint4* bb = &g_bufB[slot2][32 * j + (i >> 1)][0][0] + 2 * h + (i & 1);
#pragma unroll
      for (int col = 0; col < 8; col++) st_pub128(bb + 64 * col, SENT);
    }
  };
  if (warp >= 6) prefetch_tok(0);
  for (int i = t; i < 1024; i += 256) {
    int r = i >> 7, k = (i & 127) * 8;
    uint4 v = *reinterpret_cast<const uint4*>(mem0 + r * 1024 + k);
    unsigned short* d = reinterpret_cast<unsigned short*>(smem + OFF_MEMT) + k * 8 + r;
    d[0] = (unsigned short)v.x; d[8] = (unsigned short)(v.x >> 16); d[16] = (unsigned short)v.y; d[24] = (unsigned short)(v.y >> 16);
    d[32] = (unsigned short)v.z; d[40] = (unsigned short)(v.z >> 16); d[48] = (unsigned short)v.w; d[56] = (unsigned short)(v.w >> 16);
  }
  __syncthreads();
  const uint32_t p2dst0 = sb + OFF_QKVM + t * 16, p2dst1 = p2dst0 + 4096;
  const int p0idx = 256 * kq + 128 * mg + lane;
  uint32_t tpub = 0;
  const uint32_t dA = DLY_A, dB = DLY_B, dC = DLY_C;
  TS(0);
  for (int s = 0; s < NSEG; s++) {
    const int slot = s & 3, slot2 = (s + 2) & 3;
    if (s > 0) {
      const uint4* src = &g_bufC[(s - 1) & 3][p0idx];
      uint4 v[4];
      wait_until(tpub, dC);
#pragma unroll
      for (int i = 0; i < 4; i++) v[i] = ld_poll(src + 32 * i);
      int it = 0;
      while (!__all_sync(0xffffffffu, pkt_ok(v[0]) && pkt_ok(v[1]) && pkt_ok(v[2]) && pkt_ok(v[3])) && ++it < POLL_MAX) {
#pragma unroll
        for (int i = 0; i < 4; i++)
          if (!pkt_ok(v[i])) v[i] = ld_poll(src + 32 * i);
      }
#pragma unroll
      for (int i = 0; i < 4; i++) sts128(sb + OFF_MEMT + (p0idx + 32 * i) * 16, v[i]);
      TS(1);
      asm volatile("bar.sync %0, 64;" ::"r"(1 + kq) : "memory");
      TS(2);
    }
    {
      float acc[2][3][4];
#pragma unroll
      for (int a = 0; a < 2; a++)
#pragma unroll
        for (int tt = 0; tt < 3; tt++)
#pragma unroll
          for (int i = 0; i < 4; i++) acc[a][tt][i] = 0.f;
      uint4 sa[SK][3];
#pragma unroll
      for (int kp = 0; kp < 8; kp++) {
        uint32_t b0, b1, b2, b3;
        ldsm4t(b0, b1, b2, b3, sb + OFF_MEMT + ((16 * kq + 2 * kp) * 16 + lane) * 16);
#pragma unroll
        for (int u = 0; u < 2; u++) {
          int ks = 2 * (kp + 1) + u;
          if (ks >= RK && ks < 16) {
#pragma unroll
            for (int tt = 0; tt < 3; tt++)
              sa[ks - RK][tt] = *reinterpret_cast<const uint4*>(smem + OFF_WQS + (((warp * SK + (ks - RK)) * 3 + tt) * 32 + lane) * 16);
          }
        }
#pragma unroll
        for (int u = 0; u < 2; u++) {
          int ks = 2 * kp + u;
#pragma unroll
          for (int tt = 0; tt < 3; tt++) {
            if (ks < RK) mma16816(acc[u][tt], wq[ks][tt][0], wq[ks][tt][1], wq[ks][tt][2], wq[ks][tt][3], u ? b2 : b0, u ? b3 : b1);
            else mma16816(acc[u][tt], sa[ks - RK][tt].x, sa[ks - RK][tt].y, sa[ks - RK][tt].z, sa[ks - RK][tt].w, u ? b2 : b0, u ? b3 : b1);
          }
        }
      }
#pragma unroll
      for (int tt = 0; tt < 3; tt++)
        *reinterpret_cast<float4*>(smem + OFF_RED + ((kq * 6 + 3 * mg + tt) * 32 + lane) * 16) =
            make_float4(acc[0][tt][0] + acc[1][tt][0], acc[0][tt][1] + acc[1][tt][1], acc[0][tt][2] + acc[1][tt][2], acc[0][tt][3] + acc[1][tt][3]);
    }
    TS(3);
    __syncthreads();
    TS(4);
    if (warp < 6) {
      float4 r = *reinterpret_cast<const float4*>(smem + OFF_RED + ((0 * 6 + warp) * 32 + lane) * 16);
#pragma unroll
      for (int q = 1; q < 4; q++) {
        float4 x = *reinterpret_cast<const float4*>(smem + OFF_RED + ((q * 6 + warp) * 32 + lane) * 16);
        r.x += x.x; r.y += x.y; r.z += x.z; r.w += x.w;
      }
      uint32_t* dst = reinterpret_cast<uint32_t*>(&g_bufA[slot][cta][16 * warp + g]) + c;
      st_pub32(dst, desent(pack2(r.x, r.y)));
      st_pub32(dst + 32, desent(pack2(r.z, r.w)));
    }
    tpub = clk32();
    {
      const uint4* src = &g_bufA[slot][4 * h][t];
      wait_until(tpub, dA);
      uint4 v0 = ld_poll(src);
      uint4 v1 = make_uint4(0, 0, 0, 0);
      if (t < 128) v1 = ld_poll(src + 256);
      int it = 0;
      while (!__all_sync(0xffffffffu, pkt_ok(v0) && pkt_ok(v1)) && ++it < POLL_MAX) {
        if (!pkt_ok(v0)) v0 = ld_poll(src);
        if (!pkt_ok(v1)) v1 = ld_poll(src + 256);
      }
      sts128(p2dst0, v0);
      if (t < 128) sts128(p2dst1, v1);
    }
    TS(5);
    if (warp >= 6) cp_wait<0>();
    __syncthreads();
    TS(6);
    const uint32_t tok = sb + OFF_TOK + (s & 1) * TOK_BYTES;
    if (s < NSEG - 1) {
      if (warp < 4) attn8<false>(sb, tok, lane, warp, 0, nullptr);
      else if (VAR == 1 || VAR == 3) side_work(s);
      else if (VAR == 4) attn8<true>(sb, tok, lane, warp - 4, 8 * j + g, g_otok + (size_t)(s * 32 + 8 * j + g) * HD + h * 128);
      TS(7);
      __syncthreads();
      TS(8);
      {
        float acc[2][2][4];
#pragma unroll
        for (int a = 0; a < 2; a++)
#pragma unroll
          for (int tt = 0; tt < 2; tt++)
#pragma unroll
            for (int i = 0; i < 4; i++) acc[a][tt][i] = 0.f;
        uint32_t b[4][4];
#pragma unroll
        for (int kp = 0; kp < 4; kp++) ldsm4(b[kp][0], b[kp][1], b[kp][2], b[kp][3], sb + OFF_SA + (lane & 7) * TP + (32 * kp + 8 * (lane >> 3)) * 2);
#pragma unroll
        for (int kp = 0; kp < 4; kp++) {
#pragma unroll
          for (int tt = 0; tt < 2; tt++) {
            mma16816(acc[0][tt], wo[tt][2 * kp][0], wo[tt][2 * kp][1], wo[tt][2 * kp][2], wo[tt][2 * kp][3], b[kp][0], b[kp][1]);
            mma16816(acc[1][tt], wo[tt][2 * kp + 1][0], wo[tt][2 * kp + 1][1], wo[tt][2 * kp + 1][2], wo[tt][2 * kp + 1][3], b[kp][2], b[kp][3]);
          }
        }
        const int off = (g * 32 + h) * 4 + c;
#pragma unroll
        for (int tt = 0; tt < 2; tt++) {
          int r0 = 32 * j + 4 * warp + 2 * tt;
          uint32_t x0 = __float_as_uint(acc[0][tt][0] + acc[1][tt][0]), x1 = __float_as_uint(acc[0][tt][1] + acc[1][tt][1]);
          uint32_t x2 = __float_as_uint(acc[0][tt][2] + acc[1][tt][2]), x3 = __float_as_uint(acc[0][tt][3] + acc[1][tt][3]);
          x0 = x0 == SENT ? 0x7FFFFFFFu : x0; x1 = x1 == SENT ? 0x7FFFFFFFu : x1;
          x2 = x2 == SENT ? 0x7FFFFFFFu : x2; x3 = x3 == SENT ? 0x7FFFFFFFu : x3;
          st_pub64(reinterpret_cast<uint2*>(&g_bufB[slot][r0][0][0]) + off, x0, x1);
          st_pub64(reinterpret_cast<uint2*>(&g_bufB[slot][r0 + 1][0][0]) + off, x2, x3);
        }
        tpub = clk32();
      }
      if ((VAR == 2 || VAR == 3) && warp >= 4) attn8<true>(sb, tok, lane, warp - 4, 8 * j + g, g_otok + (size_t)(s * 32 + 8 * j + g) * HD + h * 128);
      TS(9);
      {
        const uint4* src = &g_bufB[slot][cta][0][0] + 64 * warp + 2 * lane;
        wait_until(tpub, dB);
        uint4 v0 = ld_poll(src), v1 = ld_poll(src + 1);
        int it = 0;
          while (!__all_sync(0xffffffffu, pkt_ok(v0) && pkt_ok(v1)) && ++it < POLL_MAX) {
            if (!pkt_ok(v0)) v0 = ld_poll(src);
          if (!pkt_ok(v1)) v1 = ld_poll(src + 1);
        }
        TS(10);
        const bool hi = lane & 16;
        float a0 = __uint_as_float(hi ? v1.x : v0.x), a1 = __uint_as_float(hi ? v1.y : v0.y);
        float a2 = __uint_as_float(hi ? v1.z : v0.z), a3 = __uint_as_float(hi ? v1.w : v0.w);
        float b0 = __uint_as_float(hi ? v0.x : v1.x), b1 = __uint_as_float(hi ? v0.y : v1.y);
        float b2 = __uint_as_float(hi ? v0.z : v1.z), b3 = __uint_as_float(hi ? v0.w : v1.w);
        a0 += __shfl_xor_sync(0xffffffffu, b0, 16); a1 += __shfl_xor_sync(0xffffffffu, b1, 16);
        a2 += __shfl_xor_sync(0xffffffffu, b2, 16); a3 += __shfl_xor_sync(0xffffffffu, b3, 16);
        const bool h8 = lane & 8;
        float k0 = h8 ? a2 : a0, k1 = h8 ? a3 : a1, s0 = h8 ? a0 : a2, s1 = h8 ? a1 : a3;
        k0 += __shfl_xor_sync(0xffffffffu, s0, 8); k1 += __shfl_xor_sync(0xffffffffu, s1, 8);
        const bool h4 = lane & 4;
        float z = h4 ? k1 : k0, zs = h4 ? k0 : k1;
        z += __shfl_xor_sync(0xffffffffu, zs, 4);
        z += __shfl_xor_sync(0xffffffffu, z, 2);
        z += __shfl_xor_sync(0xffffffffu, z, 1);
        float zo = __shfl_xor_sync(0xffffffffu, z, 4);
        if ((lane & 7) == 0) {
          uint32_t* d = reinterpret_cast<uint32_t*>(&g_bufC[slot][8 * cta + warp]) + (lane >> 3);
          st_pub32(d, desent(pack2(z, zo)));
        }
        tpub = clk32();
      }
    }
    if (warp >= 4) {
      if ((s == NSEG - 1 || VAR == 1) && !NOTOK) attn8<true>(sb, tok, lane, warp - 4, 8 * j + g, g_otok + (size_t)(s * 32 + 8 * j + g) * HD + h * 128);
      if (s < NSEG - 1 && (VAR == 2 || VAR == 4)) side_work(s);
    }
    TS(11);
  }
}

__device__ void moe_part(int m, const bf16* __restrict__ wg, const bf16* __restrict__ wu, const bf16* __restrict__ wd, uint8_t* smem) {
  const int t = threadIdx.x, warp = t >> 5, lane = t & 31;
  float* xs = reinterpret_cast<float*>(smem);
  float* red = reinterpret_cast<float*>(smem + 8192);
  float* hs = reinterpret_cast<float*>(smem + 65536);
  __shared__ float bv[8];
  __shared__ int bi[8];
  __shared__ int sel[2];
  int first = -1;
  for (int pass = 0; pass < 2; pass++) {
    float best = -INFINITY; int bidx = 0x7fffffff;
    for (int i = t; i < S_LEN; i += 256) {
      float v = g_r[i];
      if (i == first) continue;
      if (v > best || (v == best && i < bidx) || bidx == 0x7fffffff) { best = v; bidx = i; }
    }
#pragma unroll
    for (int o = 16; o > 0; o >>= 1) {
      float ov = __shfl_xor_sync(0xffffffffu, best, o); int oi = __shfl_xor_sync(0xffffffffu, bidx, o);
      if (oi != 0x7fffffff && (bidx == 0x7fffffff || ov > best || (ov == best && oi < bidx))) { best = ov; bidx = oi; }
    }
    if (lane == 0) { bv[warp] = best; bi[warp] = bidx; }
    __syncthreads();
    if (t == 0) {
      float b = bv[0]; int ix = bi[0];
      for (int w = 1; w < 8; w++) if (bv[w] > b || (bv[w] == b && bi[w] < ix)) { b = bv[w]; ix = bi[w]; }
      sel[pass] = ix;
    }
    __syncthreads();
    first = sel[0];
  }
  const int s0 = sel[0], s1 = sel[1];
  for (int i = t; i < 2048; i += 256) xs[i] = __bfloat162float(g_xn[(size_t)(i < 1024 ? s0 : s1) * DM + (i & 1023)]);
  __syncthreads();
  {
    int cg = t % 112, kh = t / 112;
    float a[2][2][8];
#pragma unroll
    for (int i = 0; i < 8; i++) { a[0][0][i] = a[0][1][i] = a[1][0][i] = a[1][1][i] = 0.f; }
    if (kh < 2) {
      const bf16* pg = wg + (size_t)(kh * 512) * FF + 896 * m + cg * 8;
      const bf16* pu = wu + (size_t)(kh * 512) * FF + 896 * m + cg * 8;
#pragma unroll 8
      for (int k = 0; k < 512; k++) {
        uint4 gv = __ldg(reinterpret_cast<const uint4*>(pg + (size_t)k * FF));
        uint4 uv = __ldg(reinterpret_cast<const uint4*>(pu + (size_t)k * FF));
        float x0 = xs[kh * 512 + k], x1 = xs[1024 + kh * 512 + k];
        float gf[8] = {bflo(gv.x), bfhi(gv.x), bflo(gv.y), bfhi(gv.y), bflo(gv.z), bfhi(gv.z), bflo(gv.w), bfhi(gv.w)};
        float uf[8] = {bflo(uv.x), bfhi(uv.x), bflo(uv.y), bfhi(uv.y), bflo(uv.z), bfhi(uv.z), bflo(uv.w), bfhi(uv.w)};
#pragma unroll
        for (int i = 0; i < 8; i++) {
          a[0][0][i] += x0 * gf[i]; a[0][1][i] += x1 * gf[i];
          a[1][0][i] += x0 * uf[i]; a[1][1][i] += x1 * uf[i];
        }
      }
      if (kh == 1) {
#pragma unroll
        for (int i = 0; i < 8; i++) {
          red[(0 * 2 + 0) * 896 + cg * 8 + i] = a[0][0][i]; red[(0 * 2 + 1) * 896 + cg * 8 + i] = a[0][1][i];
          red[(1 * 2 + 0) * 896 + cg * 8 + i] = a[1][0][i]; red[(1 * 2 + 1) * 896 + cg * 8 + i] = a[1][1][i];
        }
      }
    }
    __syncthreads();
    if (kh == 0) {
#pragma unroll
      for (int i = 0; i < 8; i++) {
#pragma unroll
        for (int tk = 0; tk < 2; tk++) {
          float gq = bfr(a[0][tk][i] + red[(0 * 2 + tk) * 896 + cg * 8 + i]);
          float uq = bfr(a[1][tk][i] + red[(1 * 2 + tk) * 896 + cg * 8 + i]);
          float sg = bfr(gq / (1.0f + __expf(-gq)));
          g_h[tk][896 * m + cg * 8 + i] = __float2bfloat16_rn(sg * uq);
        }
      }
    }
    __threadfence();
    __syncthreads();
    if (t == 0) {
      atomicAdd(&g_moe_cnt, 1u);
      int it = 0;
      while (*reinterpret_cast<volatile unsigned*>(&g_moe_cnt) < 4u && ++it < (1 << 24)) {}
      __threadfence();
    }
    __syncthreads();
  }
  for (int i = t; i < 2 * FF; i += 256) {
    const volatile unsigned short* p = reinterpret_cast<const volatile unsigned short*>(&g_h[0][0]);
    hs[i] = __uint_as_float(((uint32_t)p[i]) << 16);
  }
  __syncthreads();
  {
    int cg = t & 31, ksl = t >> 5;
    float a[2][8];
#pragma unroll
    for (int i = 0; i < 8; i++) a[0][i] = a[1][i] = 0.f;
    const bf16* pd = wd + (size_t)(ksl * 448) * DM + 256 * m + cg * 8;
#pragma unroll 8
    for (int k = 0; k < 448; k++) {
      uint4 dv = __ldg(reinterpret_cast<const uint4*>(pd + (size_t)k * DM));
      float x0 = hs[ksl * 448 + k], x1 = hs[FF + ksl * 448 + k];
      float df[8] = {bflo(dv.x), bfhi(dv.x), bflo(dv.y), bfhi(dv.y), bflo(dv.z), bfhi(dv.z), bflo(dv.w), bfhi(dv.w)};
#pragma unroll
      for (int i = 0; i < 8; i++) { a[0][i] += x0 * df[i]; a[1][i] += x1 * df[i]; }
    }
#pragma unroll
    for (int i = 0; i < 8; i++) { red[(ksl * 2 + 0) * 256 + cg * 8 + i] = a[0][i]; red[(ksl * 2 + 1) * 256 + cg * 8 + i] = a[1][i]; }
    __syncthreads();
    for (int i = t; i < 512; i += 256) {
      int tk = i >> 8, col = i & 255;
      float y = 0.f;
#pragma unroll
      for (int q = 0; q < 8; q++) y += red[(q * 2 + tk) * 256 + col];
      float rr = g_r[tk == 0 ? s0 : s1];
      float sg = bfr(1.0f / (1.0f + __expf(-rr)));
      g_upd[tk][256 * m + col] = bfr(bfr(y) * sg);
    }
    if (m == 0 && t == 0) { g_sel[0] = s0; g_sel[1] = s1; }
  }
}

typedef CUresult (*EncodeFn)(CUtensorMap*, CUtensorMapDataType, cuuint32_t, void*, const cuuint64_t*, const cuuint64_t*,
                             const cuuint32_t*, const cuuint32_t*, CUtensorMapInterleave, CUtensorMapSwizzle,
                             CUtensorMapL2promotion, CUtensorMapFloatOOBfill);

static void make_map(EncodeFn enc, CUtensorMap* m, const void* ptr, uint64_t inner, uint64_t outer, uint32_t bi, uint32_t bo) {
  cuuint64_t dims[2] = {inner, outer};
  cuuint64_t strides[1] = {inner * 2};
  cuuint32_t box[2] = {bi, bo};
  cuuint32_t es[2] = {1, 1};
  enc(m, CU_TENSOR_MAP_DATA_TYPE_BFLOAT16, 2, const_cast<void*>(ptr), dims, strides, box, es, CU_TENSOR_MAP_INTERLEAVE_NONE,
      CU_TENSOR_MAP_SWIZZLE_128B, CU_TENSOR_MAP_L2_PROMOTION_L2_256B, CU_TENSOR_MAP_FLOAT_OOB_FILL_NONE);
}

extern "C" void kernel_launch(void* const* d_in, const int* in_sizes, int n_in, void* d_out, int out_size) {
  const bf16* x = (const bf16*)d_in[0];
  const bf16* mem0 = (const bf16*)d_in[1];
  const bf16* Wq = (const bf16*)d_in[2];
  const bf16* Wk = (const bf16*)d_in[3];
  const bf16* Wv = (const bf16*)d_in[4];
  const bf16* Wo = (const bf16*)d_in[5];
  const bf16* w_r = (const bf16*)d_in[8];
  const bf16* wg = (const bf16*)d_in[9];
  const bf16* wu = (const bf16*)d_in[10];
  const bf16* wd = (const bf16*)d_in[11];
  bf16* out = (bf16*)d_out;

  static EncodeFn enc = nullptr;
  static void *p_xn, *p_qkv, *p_otok;
  if (!enc) {
    cudaDriverEntryPointQueryResult qr;
    void* fn = nullptr;
    cudaGetDriverEntryPoint("cuTensorMapEncodeTiled", &fn, cudaEnableDefault, &qr);
    enc = (EncodeFn)fn;
    cudaGetSymbolAddress(&p_xn, g_xn);
    cudaGetSymbolAddress(&p_qkv, g_qkv);
    cudaGetSymbolAddress(&p_otok, g_otok);
    cudaFuncSetAttribute(gemm_kernel<256, 4, 0>, cudaFuncAttributeMaxDynamicSharedMemorySize, GemmSmem<256, 4>::TOTAL);
    cudaFuncSetAttribute(gemm_kernel<128, 6, 1>, cudaFuncAttributeMaxDynamicSharedMemorySize, GemmSmem<128, 6>::TOTAL);
    cudaFuncSetAttribute(chain_kernel, cudaFuncAttributeMaxDynamicSharedMemorySize, CH_SMEM);
  }
  CUtensorMap mA, mQ, mK, mV, mO, mWo;
  make_map(enc, &mA, p_xn, DM, S_LEN, 64, 128);
  make_map(enc, &mQ, Wq, HD, DM, 64, 64);
  make_map(enc, &mK, Wk, HD, DM, 64, 64);
  make_map(enc, &mV, Wv, HD, DM, 64, 64);
  make_map(enc, &mO, p_otok, HD, S_LEN, 64, 128);
  make_map(enc, &mWo, Wo, DM, HD, 64, 64);

  cudaStream_t st = cudaStreamPerThread;
  ln_kernel<<<256, 256, 0, st>>>(x, w_r);
  cudaLaunchAttribute cat[1];
  cat[0].id = cudaLaunchAttributeClusterDimension;
  cat[0].val.clusterDim.x = 2; cat[0].val.clusterDim.y = 1; cat[0].val.clusterDim.z = 1;
  cudaLaunchConfig_t cfg = {};
  cfg.gridDim = dim3(132); cfg.blockDim = dim3(288); cfg.dynamicSmemBytes = GemmSmem<256, 4>::TOTAL; cfg.stream = st;
  cfg.attrs = cat; cfg.numAttrs = 1;
  cudaLaunchKernelEx(&cfg, gemm_kernel<256, 4, 0>, mA, mQ, mK, mV, 16, 16, 16 * 48, (const bf16*)nullptr, (bf16*)p_qkv, Wq, Wk, Wv, Wo);
  chain_kernel<<<132, 256, CH_SMEM, st>>>(mem0, Wq, Wk, Wv, Wo, wg, wu, wd);
  cfg.gridDim = dim3(128); cfg.dynamicSmemBytes = GemmSmem<128, 6>::TOTAL;
  cudaLaunchKernelEx(&cfg, gemm_kernel<128, 6, 1>, mO, mWo, mWo, mWo, 64, 16, 16 * 8, x, out, Wq, Wk, Wv, Wo);
}
```

```cpp
#include <cuda_runtime.h>
#include <cuda_bf16.h>
#include <cuda.h>
#include <stdint.h>

typedef __nv_bfloat16 bf16;

#define S_LEN 2048
#define DM 1024
#define NH 32
#define DH 128
#define NSEG 64
#define SEGL 32
#define HD 4096
#define NQKV 12288
#define FF 3584
#define SENT 0xFFFFFFFFu

__device__ __align__(1024) bf16 g_xn[S_LEN * DM];
__device__ __align__(1024) bf16 g_qkv[(size_t)S_LEN * NQKV];
__device__ __align__(1024) bf16 g_otok[(size_t)S_LEN * HD];
__device__ float g_r[S_LEN];
__device__ __align__(128) uint4 g_bufA[4][128][96];
__device__ __align__(128) uint4 g_bufB[4][128][16][32];
__device__ __align__(128) uint4 g_bufC[4][1024];
__device__ __align__(128) bf16 g_h[2][FF];
__device__ float g_upd[2][DM];
__device__ int g_sel[2];
__device__ unsigned g_moe_cnt;
__device__ unsigned g_abort;
#define NOTOK 0
#define VAR 1
#define DLY_A 350u
#define DLY_B 800u
#define DLY_C 650u
#define TS(i)

__device__ __forceinline__ float bfr(float x) { return __bfloat162float(__float2bfloat16_rn(x)); }
__device__ __forceinline__ uint32_t pack2(float lo, float hi) {
  __nv_bfloat162 v = __floats2bfloat162_rn(lo, hi);
  return *reinterpret_cast<uint32_t*>(&v);
}
__device__ __forceinline__ float bflo(uint32_t v) { return __uint_as_float(v << 16); }
__device__ __forceinline__ float bfhi(uint32_t v) { return __uint_as_float(v & 0xFFFF0000u); }
__device__ __forceinline__ uint32_t smem_u32(const void* p) { return (uint32_t)__cvta_generic_to_shared(p); }

__device__ __forceinline__ uint4 ld_poll(const uint4* p) {
  uint4 v;
  asm volatile("ld.relaxed.gpu.global.v4.u32 {%0,%1,%2,%3},[%4];" : "=r"(v.x), "=r"(v.y), "=r"(v.z), "=r"(v.w) : "l"(p) : "memory");
  return v;
}
__device__ __forceinline__ void st_pub32(void* p, uint32_t v) {
  asm volatile("st.relaxed.gpu.global.u32 [%0],%1;" ::"l"(p), "r"(v) : "memory");
}
__device__ __forceinline__ void st_pub64(void* p, uint32_t a, uint32_t b) {
  asm volatile("st.relaxed.gpu.global.v2.u32 [%0],{%1,%2};" ::"l"(p), "r"(a), "r"(b) : "memory");
}
__device__ __forceinline__ bool pkt_ok(const uint4& v) { return v.x != SENT && v.y != SENT && v.z != SENT && v.w != SENT; }
__device__ __forceinline__ uint32_t desent(uint32_t v) { return v == SENT ? 0x7FFF7FFFu : v; }

__device__ __forceinline__ void ldsm4(uint32_t& r0, uint32_t& r1, uint32_t& r2, uint32_t& r3, uint32_t addr) {
  asm volatile("ldmatrix.sync.aligned.m8n8.x4.shared.b16 {%0,%1,%2,%3},[%4];" : "=r"(r0), "=r"(r1), "=r"(r2), "=r"(r3) : "r"(addr) : "memory");
}
__device__ __forceinline__ void ldsm4t(uint32_t& r0, uint32_t& r1, uint32_t& r2, uint32_t& r3, uint32_t addr) {
  asm volatile("ldmatrix.sync.aligned.m8n8.x4.trans.shared.b16 {%0,%1,%2,%3},[%4];" : "=r"(r0), "=r"(r1), "=r"(r2), "=r"(r3) : "r"(addr) : "memory");
}
__device__ __forceinline__ void mma16816(float (&d)[4], uint32_t a0, uint32_t a1, uint32_t a2, uint32_t a3, uint32_t b0, uint32_t b1) {
  asm volatile("mma.sync.aligned.m16n8k16.row.col.f32.bf16.bf16.f32 {%0,%1,%2,%3},{%4,%5,%6,%7},{%8,%9},{%0,%1,%2,%3};"
               : "+f"(d[0]), "+f"(d[1]), "+f"(d[2]), "+f"(d[3])
               : "r"(a0), "r"(a1), "r"(a2), "r"(a3), "r"(b0), "r"(b1));
}
__device__ __forceinline__ void cp_async16(uint32_t dst, const void* src) {
  asm volatile("cp.async.cg.shared.global [%0],[%1],16;" ::"r"(dst), "l"(src) : "memory");
}
__device__ __forceinline__ void cp_commit() { asm volatile("cp.async.commit_group;" ::: "memory"); }
template <int N>
__device__ __forceinline__ void cp_wait() { asm volatile("cp.async.wait_group %0;" ::"n"(N) : "memory"); }

__device__ __forceinline__ void mbar_init(uint32_t bar, uint32_t cnt) { asm volatile("mbarrier.init.shared::cta.b64 [%0],%1;" ::"r"(bar), "r"(cnt) : "memory"); }
__device__ __forceinline__ void mbar_expect_tx(uint32_t bar, uint32_t bytes) {
  asm volatile("mbarrier.arrive.expect_tx.shared::cta.b64 _,[%0],%1;" ::"r"(bar), "r"(bytes) : "memory");
}
__device__ __forceinline__ void mbar_arrive(uint32_t bar) { asm volatile("mbarrier.arrive.shared::cta.b64 _,[%0];" ::"r"(bar) : "memory"); }
__device__ __forceinline__ void mbar_wait(uint32_t bar, uint32_t parity) {
  asm volatile(
      "{\n.reg .pred p;\n"
      "WAIT_LOOP:\n"
      "mbarrier.try_wait.parity.shared::cta.b64 p,[%0],%1;\n"
      "@p bra WAIT_DONE;\n"
      "bra WAIT_LOOP;\n"
      "WAIT_DONE:\n}\n" ::"r"(bar), "r"(parity) : "memory");
}
__device__ __forceinline__ void tma_load2d(uint32_t dst, const CUtensorMap* tm, uint32_t bar, int c0, int c1) {
  asm volatile("cp.async.bulk.tensor.2d.shared::cluster.global.mbarrier::complete_tx::bytes [%0],[%1,{%3,%4}],[%2];"
               ::"r"(dst), "l"(tm), "r"(bar), "r"(c0), "r"(c1) : "memory");
}
__device__ __forceinline__ void tma_load2d_mc(uint32_t dst, const CUtensorMap* tm, uint32_t bar, int c0, int c1, uint16_t mask) {
  asm volatile("cp.async.bulk.tensor.2d.shared::cluster.global.mbarrier::complete_tx::bytes.multicast::cluster [%0],[%1,{%3,%4}],[%2],%5;"
               ::"r"(dst), "l"(tm), "r"(bar), "r"(c0), "r"(c1), "h"(mask) : "memory");
}
__device__ __forceinline__ void mbar_arrive_cluster(uint32_t bar, uint32_t cta) {
  asm volatile("{\n.reg .b32 ra;\nmapa.shared::cluster.u32 ra,%0,%1;\nmbarrier.arrive.shared::cluster.b64 _,[ra];\n}\n" ::"r"(bar), "r"(cta) : "memory");
}
__device__ __forceinline__ void cluster_sync() {
  asm volatile("barrier.cluster.arrive.release.aligned;\nbarrier.cluster.wait.acquire.aligned;\n" ::: "memory");
}
__device__ __forceinline__ void wg_fence() { asm volatile("wgmma.fence.sync.aligned;" ::: "memory"); }
__device__ __forceinline__ void wg_commit() { asm volatile("wgmma.commit_group.sync.aligned;" ::: "memory"); }
template <int N>
__device__ __forceinline__ void wg_wait() { asm volatile("wgmma.wait_group.sync.aligned %0;" ::"n"(N) : "memory"); }
__device__ __forceinline__ uint64_t make_desc(uint32_t addr, uint32_t lbo, uint32_t sbo) {
  return (uint64_t)((addr & 0x3FFFF) >> 4) | ((uint64_t)(lbo >> 4) << 16) | ((uint64_t)(sbo >> 4) << 32) | (1ull << 62);
}

__device__ __forceinline__ void wgmma_m64n256k16(float (&d)[128], uint64_t da, uint64_t db, int scaleD) {
  asm volatile(
    "{\n.reg .pred p;\nsetp.ne.b32 p, %130, 0;\n"
    "wgmma.mma_async.sync.aligned.m64n256k16.f32.bf16.bf16 "
    "{%0, %1, %2, %3, %4, %5, %6, %7, %8, %9, %10, %11, %12, %13, %14, %15, %16, %17, %18, %19, %20, %21, %22, %23, %24, %25, %26, %27, %28, %29, %30, %31, %32, %33, %34, %35, %36, %37, %38, %39, %40, %41, %42, %43, %44, %45, %46, %47, %48, %49, %50, %51, %52, %53, %54, %55, %56, %57, %58, %59, %60, %61, %62, %63, %64, %65, %66, %67, %68, %69, %70, %71, %72, %73, %74, %75, %76, %77, %78, %79, %80, %81, %82, %83, %84, %85, %86, %87, %88, %89, %90, %91, %92, %93, %94, %95, %96, %97, %98, %99, %100, %101, %102, %103, %104, %105, %106, %107, %108, %109, %110, %111, %112, %113, %114, %115, %116, %117, %118, %119, %120, %121, %122, %123, %124, %125, %126, %127}, %128, %129, p, 1, 1, 0, 1;\n}\n"
    : "+f"(d[0]), "+f"(d[1]), "+f"(d[2]), "+f"(d[3]), "+f"(d[4]), "+f"(d[5]), "+f"(d[6]), "+f"(d[7]), "+f"(d[8]), "+f"(d[9]), "+f"(d[10]), "+f"(d[11]), "+f"(d[12]), "+f"(d[13]), "+f"(d[14]), "+f"(d[15]), "+f"(d[16]), "+f"(d[17]), "+f"(d[18]), "+f"(d[19]), "+f"(d[20]), "+f"(d[21]), "+f"(d[22]), "+f"(d[23]), "+f"(d[24]), "+f"(d[25]), "+f"(d[26]), "+f"(d[27]), "+f"(d[28]), "+f"(d[29]), "+f"(d[30]), "+f"(d[31]), "+f"(d[32]), "+f"(d[33]), "+f"(d[34]), "+f"(d[35]), "+f"(d[36]), "+f"(d[37]), "+f"(d[38]), "+f"(d[39]), "+f"(d[40]), "+f"(d[41]), "+f"(d[42]), "+f"(d[43]), "+f"(d[44]), "+f"(d[45]), "+f"(d[46]), "+f"(d[47]), "+f"(d[48]), "+f"(d[49]), "+f"(d[50]), "+f"(d[51]), "+f"(d[52]), "+f"(d[53]), "+f"(d[54]), "+f"(d[55]), "+f"(d[56]), "+f"(d[57]), "+f"(d[58]), "+f"(d[59]), "+f"(d[60]), "+f"(d[61]), "+f"(d[62]), "+f"(d[63]), "+f"(d[64]), "+f"(d[65]), "+f"(d[66]), "+f"(d[67]), "+f"(d[68]), "+f"(d[69]), "+f"(d[70]), "+f"(d[71]), "+f"(d[72]), "+f"(d[73]), "+f"(d[74]), "+f"(d[75]), "+f"(d[76]), "+f"(d[77]), "+f"(d[78]), "+f"(d[79]), "+f"(d[80]), "+f"(d[81]), "+f"(d[82]), "+f"(d[83]), "+f"(d[84]), "+f"(d[85]), "+f"(d[86]), "+f"(d[87]), "+f"(d[88]), "+f"(d[89]), "+f"(d[90]), "+f"(d[91]), "+f"(d[92]), "+f"(d[93]), "+f"(d[94]), "+f"(d[95]), "+f"(d[96]), "+f"(d[97]), "+f"(d[98]), "+f"(d[99]), "+f"(d[100]), "+f"(d[101]), "+f"(d[102]), "+f"(d[103]), "+f"(d[104]), "+f"(d[105]), "+f"(d[106]), "+f"(d[107]), "+f"(d[108]), "+f"(d[109]), "+f"(d[110]), "+f"(d[111]), "+f"(d[112]), "+f"(d[113]), "+f"(d[114]), "+f"(d[115]), "+f"(d[116]), "+f"(d[117]), "+f"(d[118]), "+f"(d[119]), "+f"(d[120]), "+f"(d[121]), "+f"(d[122]), "+f"(d[123]), "+f"(d[124]), "+f"(d[125]), "+f"(d[126]), "+f"(d[127])
    : "l"(da), "l"(db), "r"(scaleD));
}

__device__ __forceinline__ void wgmma_m64n128k16(float (&d)[64], uint64_t da, uint64_t db, int scaleD) {
  asm volatile(
    "{\n.reg .pred p;\nsetp.ne.b32 p, %66, 0;\n"
    "wgmma.mma_async.sync.aligned.m64n128k16.f32.bf16.bf16 "
    "{%0, %1, %2, %3, %4, %5, %6, %7, %8, %9, %10, %11, %12, %13, %14, %15, %16, %17, %18, %19, %20, %21, %22, %23, %24, %25, %26, %27, %28, %29, %30, %31, %32, %33, %34, %35, %36, %37, %38, %39, %40, %41, %42, %43, %44, %45, %46, %47, %48, %49, %50, %51, %52, %53, %54, %55, %56, %57, %58, %59, %60, %61, %62, %63}, %64, %65, p, 1, 1, 0, 1;\n}\n"
    : "+f"(d[0]), "+f"(d[1]), "+f"(d[2]), "+f"(d[3]), "+f"(d[4]), "+f"(d[5]), "+f"(d[6]), "+f"(d[7]), "+f"(d[8]), "+f"(d[9]), "+f"(d[10]), "+f"(d[11]), "+f"(d[12]), "+f"(d[13]), "+f"(d[14]), "+f"(d[15]), "+f"(d[16]), "+f"(d[17]), "+f"(d[18]), "+f"(d[19]), "+f"(d[20]), "+f"(d[21]), "+f"(d[22]), "+f"(d[23]), "+f"(d[24]), "+f"(d[25]), "+f"(d[26]), "+f"(d[27]), "+f"(d[28]), "+f"(d[29]), "+f"(d[30]), "+f"(d[31]), "+f"(d[32]), "+f"(d[33]), "+f"(d[34]), "+f"(d[35]), "+f"(d[36]), "+f"(d[37]), "+f"(d[38]), "+f"(d[39]), "+f"(d[40]), "+f"(d[41]), "+f"(d[42]), "+f"(d[43]), "+f"(d[44]), "+f"(d[45]), "+f"(d[46]), "+f"(d[47]), "+f"(d[48]), "+f"(d[49]), "+f"(d[50]), "+f"(d[51]), "+f"(d[52]), "+f"(d[53]), "+f"(d[54]), "+f"(d[55]), "+f"(d[56]), "+f"(d[57]), "+f"(d[58]), "+f"(d[59]), "+f"(d[60]), "+f"(d[61]), "+f"(d[62]), "+f"(d[63])
    : "l"(da), "l"(db), "r"(scaleD));
}

template <int BN> struct WG;
template <> struct WG<256> { static __device__ __forceinline__ void mma(float (&d)[128], uint64_t a, uint64_t b, int s) { wgmma_m64n256k16(d, a, b, s); } };
template <> struct WG<128> { static __device__ __forceinline__ void mma(float (&d)[64], uint64_t a, uint64_t b, int s) { wgmma_m64n128k16(d, a, b, s); } };

__global__ void __launch_bounds__(256) ln_kernel(const bf16* __restrict__ x, const bf16* __restrict__ w_r) {
  int warp = threadIdx.x >> 5, lane = threadIdx.x & 31;
  int row = blockIdx.x * 8 + warp;
  const uint4* xp = reinterpret_cast<const uint4*>(x + (size_t)row * DM);
  uint4 v[4];
#pragma unroll
  for (int i = 0; i < 4; i++) v[i] = xp[lane + 32 * i];
  float f[32];
#pragma unroll
  for (int i = 0; i < 4; i++) {
    f[8 * i + 0] = bflo(v[i].x); f[8 * i + 1] = bfhi(v[i].x);
    f[8 * i + 2] = bflo(v[i].y); f[8 * i + 3] = bfhi(v[i].y);
    f[8 * i + 4] = bflo(v[i].z); f[8 * i + 5] = bfhi(v[i].z);
    f[8 * i + 6] = bflo(v[i].w); f[8 * i + 7] = bfhi(v[i].w);
  }
  float s = 0.f;
#pragma unroll
  for (int i = 0; i < 32; i++) s += f[i];
#pragma unroll
  for (int o = 16; o > 0; o >>= 1) s += __shfl_xor_sync(0xffffffffu, s, o);
  float mean = s * (1.0f / DM);
  float q = 0.f;
#pragma unroll
  for (int i = 0; i < 32; i++) { float d = f[i] - mean; q += d * d; }
#pragma unroll
  for (int o = 16; o > 0; o >>= 1) q += __shfl_xor_sync(0xffffffffu, q, o);
  float var = bfr(q * (1.0f / DM));
  float mb = bfr(mean);
  float den = bfr(sqrtf(bfr(var + 1e-5f)));
  const uint4* wp = reinterpret_cast<const uint4*>(w_r);
  uint4* op = reinterpret_cast<uint4*>(g_xn + (size_t)row * DM);
  float r = 0.f;
#pragma unroll
  for (int i = 0; i < 4; i++) {
    uint4 w = wp[lane + 32 * i];
    float y[8];
#pragma unroll
    for (int k = 0; k < 8; k++) y[k] = bfr(bfr(f[8 * i + k] - mb) / den);
    r += y[0] * bflo(w.x) + y[1] * bfhi(w.x) + y[2] * bflo(w.y) + y[3] * bfhi(w.y) + y[4] * bflo(w.z) + y[5] * bfhi(w.z) +
         y[6] * bflo(w.w) + y[7] * bfhi(w.w);
    op[lane + 32 * i] = make_uint4(pack2(y[0], y[1]), pack2(y[2], y[3]), pack2(y[4], y[5]), pack2(y[6], y[7]));
  }
#pragma unroll
  for (int o = 16; o > 0; o >>= 1) r += __shfl_xor_sync(0xffffffffu, r, o);
  if (lane == 0) g_r[row] = bfr(r);
  int gt = blockIdx.x * 256 + threadIdx.x;
  const uint4 sv = make_uint4(SENT, SENT, SENT, SENT);
  uint4* a = &g_bufA[0][0][0];
  for (int i = gt; i < 2 * 128 * 96; i += 65536) a[i] = sv;
  uint4* b = &g_bufB[0][0][0][0];
  for (int i = gt; i < 2 * 128 * 32 * 16; i += 65536) b[i] = sv;
  uint4* c = &g_bufC[0][0];
  for (int i = gt; i < 2 * 1024; i += 65536) c[i] = sv;
  if (gt == 0) { g_moe_cnt = 0; g_abort = 0; }
}

template <int BN, int STAGES>
struct GemmSmem {
  static constexpr int A_BYTES = 128 * 64 * 2;
  static constexpr int B_BYTES = 64 * BN * 2;
  static constexpr int STAGE_BYTES = A_BYTES + B_BYTES;
  static constexpr int TOTAL = STAGES * STAGE_BYTES + 1024 + 256;
};

__device__ __forceinline__ void quad_transpose(uint32_t (&v)[4], int c) {
  {
    uint32_t s0 = (c & 1) ? v[0] : v[1];
    uint32_t s1 = (c & 1) ? v[2] : v[3];
    uint32_t r0 = __shfl_xor_sync(0xffffffffu, s0, 1);
    uint32_t r1 = __shfl_xor_sync(0xffffffffu, s1, 1);
    if (c & 1) { v[0] = r0; v[2] = r1; } else { v[1] = r0; v[3] = r1; }
  }
  {
    uint32_t s0 = (c & 2) ? v[0] : v[2];
    uint32_t s1 = (c & 2) ? v[1] : v[3];
    uint32_t r0 = __shfl_xor_sync(0xffffffffu, s0, 2);
    uint32_t r1 = __shfl_xor_sync(0xffffffffu, s1, 2);
    if (c & 2) { v[0] = r0; v[1] = r1; } else { v[2] = r0; v[3] = r1; }
  }
}

__device__ __forceinline__ uint32_t add3(uint32_t a, uint32_t x, uint32_t b) {
  float lo = bfr(bflo(x) + bflo(a)) + bflo(b);
  float hi = bfr(bfhi(x) + bfhi(a)) + bfhi(b);
  return pack2(lo, hi);
}

template <int BN, int STAGES, int EPI>
__global__ void __launch_bounds__(288, 1)
gemm_kernel(const __grid_constant__ CUtensorMap tmA, const __grid_constant__ CUtensorMap tmB0,
            const __grid_constant__ CUtensorMap tmB1, const __grid_constant__ CUtensorMap tmB2,
            int kblocks, int tiles_m, int tiles_total, const bf16* __restrict__ xin, bf16* __restrict__ outp,
            const bf16* pf0, const bf16* pf1, const bf16* pf2, const bf16* pf3) {
  using SM = GemmSmem<BN, STAGES>;
  extern __shared__ uint8_t smem_raw[];
  uint32_t base = (smem_u32(smem_raw) + 1023) & ~1023u;
  uint32_t bars = base + STAGES * SM::STAGE_BYTES;
  int warp = threadIdx.x >> 5, lane = threadIdx.x & 31;
  uint32_t rank;
  asm volatile("mov.u32 %0,%%cluster_ctarank;" : "=r"(rank));
  const int cl = blockIdx.x >> 1, ncl = gridDim.x >> 1;
  const int pairs_m = tiles_m >> 1, pairs_total = tiles_total >> 1;
  if (threadIdx.x == 0) {
    for (int i = 0; i < STAGES; i++) { mbar_init(bars + 8 * i, 1); mbar_init(bars + 8 * (STAGES + i), 16); }
    asm volatile("fence.mbarrier_init.release.cluster;" ::: "memory");
  }
  __syncthreads();
  cluster_sync();
  if (warp == 8) {
    if (lane == 0) {
      int it = 0;
      for (int t = cl; t < pairs_total; t += ncl) {
        int tm = 2 * (t % pairs_m) + rank, tn = t / pairs_m;
        int n0 = tn * BN;
        const CUtensorMap* tb = &tmB0;
        if (EPI == 0) { int wsel = n0 >> 12; tb = wsel == 0 ? &tmB0 : (wsel == 1 ? &tmB1 : &tmB2); n0 &= 4095; }
        for (int kb = 0; kb < kblocks; kb++, it++) {
          int st = it % STAGES; uint32_t ph = (it / STAGES) & 1;
          mbar_wait(bars + 8 * (STAGES + st), ph ^ 1);
          uint32_t sa = base + st * SM::STAGE_BYTES, sb = sa + SM::A_BYTES;
          mbar_expect_tx(bars + 8 * st, SM::STAGE_BYTES);
          tma_load2d(sa, &tmA, bars + 8 * st, kb * 64, tm * 128);
#pragma unroll
          for (int i = 0; i < BN / 128; i++) {
            int bx = rank * (BN / 128) + i;
            tma_load2d_mc(sb + bx * 8192, tb, bars + 8 * st, n0 + bx * 64, kb * 64, (uint16_t)3);
          }
        }
      }
      if (EPI == 0 && blockIdx.x < 128) {
        const size_t o = (size_t)blockIdx.x * 32768;
#pragma unroll
        for (int q = 0; q < 4; q++) {
          asm volatile("cp.async.bulk.prefetch.L2.global [%0],%1;" ::"l"(pf0 + o + q * 8192), "r"(16384) : "memory");
          asm volatile("cp.async.bulk.prefetch.L2.global [%0],%1;" ::"l"(pf1 + o + q * 8192), "r"(16384) : "memory");
          asm volatile("cp.async.bulk.prefetch.L2.global [%0],%1;" ::"l"(pf2 + o + q * 8192), "r"(16384) : "memory");
          asm volatile("cp.async.bulk.prefetch.L2.global [%0],%1;" ::"l"(pf3 + o + q * 8192), "r"(16384) : "memory");
        }
      }
    }
    __syncwarp();
  } else {
    int wg = warp >> 2;
    int g = lane >> 2, c = lane & 3;
    int it = 0;
    float acc[BN / 2];
    for (int t = cl; t < pairs_total; t += ncl) {
      int tm = 2 * (t % pairs_m) + rank, tn = t / pairs_m;
      for (int kb = 0; kb < kblocks; kb++, it++) {
        int st = it % STAGES; uint32_t ph = (it / STAGES) & 1;
        mbar_wait(bars + 8 * st, ph);
        uint32_t sa = base + st * SM::STAGE_BYTES + wg * 8192, sb = base + st * SM::STAGE_BYTES + SM::A_BYTES;
        wg_fence();
#pragma unroll
        for (int kk = 0; kk < 4; kk++) {
          uint64_t da = make_desc(sa + kk * 32, 16, 1024);
          uint64_t db = make_desc(sb + kk * 2048, 8192, 1024);
          WG<BN>::mma(acc, da, db, (kb | kk) != 0);
        }
        wg_commit();
        if (kb > 0) {
          wg_wait<1>();
          int pst = (it - 1) % STAGES;
          if (lane < 2) mbar_arrive_cluster(bars + 8 * (STAGES + pst), lane);
        }
      }
      wg_wait<0>();
      { int pst = (it - 1) % STAGES; if (lane < 2) mbar_arrive_cluster(bars + 8 * (STAGES + pst), lane); }
      int row0 = tm * 128 + wg * 64 + (warp & 3) * 16 + g;
      int sel0 = -1, sel1 = -1;
      if (EPI == 1) { sel0 = g_sel[0]; sel1 = g_sel[1]; }
#pragma unroll
      for (int half = 0; half < 2; half++) {
        int row = row0 + half * 8;
#pragma unroll
        for (int q = 0; q < BN / 32; q++) {
          uint32_t v[4];
#pragma unroll
          for (int tt = 0; tt < 4; tt++) v[tt] = pack2(acc[(q * 4 + tt) * 4 + half * 2], acc[(q * 4 + tt) * 4 + half * 2 + 1]);
          quad_transpose(v, c);
          int col = tn * BN + q * 32 + c * 8;
          if (EPI == 0) {
            __stcs(reinterpret_cast<uint4*>(outp + (size_t)row * NQKV + col), make_uint4(v[0], v[1], v[2], v[3]));
          } else {
            uint4 xv = *reinterpret_cast<const uint4*>(xin + (size_t)row * DM + col);
            uint4 bv = *reinterpret_cast<const uint4*>(g_xn + (size_t)row * DM + col);
            if (row == sel0 || row == sel1) {
              const float* u = &g_upd[row == sel0 ? 0 : 1][col];
              bv.x = pack2(bflo(bv.x) + u[0], bfhi(bv.x) + u[1]);
              bv.y = pack2(bflo(bv.y) + u[2], bfhi(bv.y) + u[3]);
              bv.z = pack2(bflo(bv.z) + u[4], bfhi(bv.z) + u[5]);
              bv.w = pack2(bflo(bv.w) + u[6], bfhi(bv.w) + u[7]);
            }
            uint4 o = make_uint4(add3(v[0], xv.x, bv.x), add3(v[1], xv.y, bv.y), add3(v[2], xv.z, bv.z), add3(v[3], xv.w, bv.w));
            *reinterpret_cast<uint4*>(outp + (size_t)row * DM + col) = o;
          }
        }
      }
    }
  }
  cluster_sync();
}

#define RK 10
#define SK (16 - RK)
#define TP 272
#define OFF_WQS 0
#define OFF_MEMT (OFF_WQS + 8 * SK * 3 * 512)
#define OFF_RED (OFF_MEMT + 16384)
#define OFF_QKVM (OFF_RED + 12288)
#define OFF_TOK (OFF_QKVM + 6144)
#define TOK_BYTES (72 * TP)
#define OFF_SA (OFF_TOK + 2 * TOK_BYTES)
#define OFF_BAR (OFF_SA + 8 * TP)
#define CH_END (OFF_BAR + 64)
#define CH_STG2 (131072)
#define WSP 208
#define CH_SMEM (1024 * WSP + 1024)
static_assert(CH_END <= CH_SMEM, "smem");

__device__ void moe_part(int m, const bf16* __restrict__ wg, const bf16* __restrict__ wu, const bf16* __restrict__ wd, uint8_t* smem);

__device__ __forceinline__ void bulk_copy(uint32_t dst, const void* src, uint32_t bytes, uint32_t bar) {
  asm volatile("cp.async.bulk.shared::cluster.global.mbarrier::complete_tx::bytes [%0],[%1],%2,[%3];"
               ::"r"(dst), "l"(src), "r"(bytes), "r"(bar) : "memory");
}
__device__ __forceinline__ void st_pub128(void* p, uint32_t v) {
  asm volatile("st.relaxed.gpu.global.v4.u32 [%0],{%1,%1,%1,%1};" ::"l"(p), "r"(v) : "memory");
}
__device__ __forceinline__ void sts128(uint32_t addr, const uint4& v) {
  asm volatile("st.shared.v4.u32 [%0],{%1,%2,%3,%4};" ::"r"(addr), "r"(v.x), "r"(v.y), "r"(v.z), "r"(v.w) : "memory");
}

__device__ __forceinline__ bool poll_giveup(int& it) {
  if ((++it & 1023) != 0) return false;
  if (it >= (1 << 18)) { *reinterpret_cast<volatile unsigned*>(&g_abort) = 1u; return true; }
  return *reinterpret_cast<volatile unsigned*>(&g_abort) != 0u;
}
__device__ __forceinline__ uint32_t clk32() { uint32_t c; asm volatile("mov.u32 %0,%%clock;" : "=r"(c)); return c; }
__device__ __forceinline__ void wait_until(uint32_t t0, uint32_t d) { while (clk32() - t0 < d) {} }
#define DLY_DEC 48u

__device__ __forceinline__ float ex2f(float x) { float y; asm("ex2.approx.ftz.f32 %0,%1;" : "=f"(y) : "f"(x)); return y; }
__device__ __forceinline__ float rcpf(float x) { float y; asm("rcp.approx.ftz.f32 %0,%1;" : "=f"(y) : "f"(x)); return y; }
template <bool TOK>
__device__ __forceinline__ void attn8(uint32_t sb, uint32_t tok, int lane, int wq4, int tr, bf16* otok_row) {
  const int g = lane >> 2, c = lane & 3;
  float sc[5][4];
#pragma unroll
  for (int n = 0; n < 5; n++)
#pragma unroll
    for (int i = 0; i < 4; i++) sc[n][i] = 0.f;
  const uint32_t tokrow = tok + (lane & 7) * TP + (lane >> 3) * 16;
  const uint32_t qaddr = TOK ? (tok + (64 + (lane & 7)) * TP + (lane >> 4) * 16) : (sb + OFF_QKVM + ((lane & 7) + 8 * (lane >> 4)) * 16);
#pragma unroll
  for (int kp = 0; kp < 4; kp++) {
    uint32_t q0[4], q1[4], km[4], kt[4][4];
    if (TOK) {
      ldsm4(q0[0], q0[1], q0[2], q0[3], qaddr + 64 * kp);
      ldsm4(q1[0], q1[1], q1[2], q1[3], qaddr + 64 * kp + 32);
    } else {
      ldsm4t(q0[0], q0[1], q0[2], q0[3], qaddr + 512 * kp);
      ldsm4t(q1[0], q1[1], q1[2], q1[3], qaddr + 512 * kp + 256);
    }
    ldsm4t(km[0], km[1], km[2], km[3], sb + OFF_QKVM + (128 + 32 * kp + lane) * 16);
#pragma unroll
    for (int n = 0; n < 4; n++) ldsm4(kt[n][0], kt[n][1], kt[n][2], kt[n][3], tokrow + 8 * n * TP + 64 * kp);
    mma16816(sc[0], q0[0], q0[1], q0[2], q0[3], km[0], km[1]);
#pragma unroll
    for (int n = 0; n < 4; n++) mma16816(sc[n + 1], q0[0], q0[1], q0[2], q0[3], kt[n][0], kt[n][1]);
    mma16816(sc[0], q1[0], q1[1], q1[2], q1[3], km[2], km[3]);
#pragma unroll
    for (int n = 0; n < 4; n++) mma16816(sc[n + 1], q1[0], q1[1], q1[2], q1[3], kt[n][2], kt[n][3]);
  }
  uint32_t vma[4], vmb[4], vt[4][4];
  ldsm4(vma[0], vma[1], vma[2], vma[3], sb + OFF_QKVM + (256 + 32 * wq4 + lane) * 16);
  ldsm4(vmb[0], vmb[1], vmb[2], vmb[3], sb + OFF_QKVM + (256 + 32 * wq4 + (lane ^ 8)) * 16);
#pragma unroll
  for (int n = 0; n < 4; n++) ldsm4t(vt[n][0], vt[n][1], vt[n][2], vt[n][3], tok + (32 + lane) * TP + (32 * wq4 + 8 * n) * 2);
  const float scale = 0.08838834764831845f;
  float m0 = -3.0e38f;
#pragma unroll
  for (int n = 0; n < 5; n++) {
    uint32_t p1 = pack2(sc[n][0], sc[n][1]);
    uint32_t p2 = pack2(bflo(p1) * scale, bfhi(p1) * scale);
    sc[n][0] = bflo(p2);
    sc[n][1] = bfhi(p2);
    if (TOK && n > 0) {
      int kt = 8 * (n - 1) + 2 * c;
      if (kt > tr) sc[n][0] = -1.0e9f;
      if (kt + 1 > tr) sc[n][1] = -1.0e9f;
    }
    m0 = fmaxf(m0, fmaxf(sc[n][0], sc[n][1]));
  }
  m0 = fmaxf(m0, __shfl_xor_sync(0xffffffffu, m0, 1));
  m0 = fmaxf(m0, __shfl_xor_sync(0xffffffffu, m0, 2));
  const float l2e = 1.4426950408889634f;
  float s0 = 0.f;
#pragma unroll
  for (int n = 0; n < 5; n++) {
    sc[n][0] = ex2f((sc[n][0] - m0) * l2e);
    sc[n][1] = ex2f((sc[n][1] - m0) * l2e);
    s0 += sc[n][0] + sc[n][1];
  }
  s0 += __shfl_xor_sync(0xffffffffu, s0, 1);
  s0 += __shfl_xor_sync(0xffffffffu, s0, 2);
  const float i0 = rcpf(s0);
  uint32_t pp[5];
#pragma unroll
  for (int n = 0; n < 5; n++) pp[n] = pack2(sc[n][0] * i0, sc[n][1] * i0);
  float o[4][4];
#pragma unroll
  for (int n = 0; n < 4; n++) {
#pragma unroll
    for (int i = 0; i < 4; i++) o[n][i] = 0.f;
    mma16816(o[n], pp[1], pp[1], pp[2], pp[2], vt[n][0], vt[n][1]);
  }
#pragma unroll
  for (int n = 0; n < 4; n++) mma16816(o[n], pp[3], pp[3], pp[4], pp[4], vt[n][2], vt[n][3]);
  mma16816(o[0], pp[0], 0u, 0u, 0u, vma[0], vma[1]);
  mma16816(o[1], pp[0], 0u, 0u, 0u, vmb[0], vmb[1]);
  mma16816(o[2], pp[0], 0u, 0u, 0u, vma[2], vma[3]);
  mma16816(o[3], pp[0], 0u, 0u, 0u, vmb[2], vmb[3]);
#pragma unroll
  for (int n = 0; n < 4; n++) {
    const int e = 32 * wq4 + 8 * n + 2 * c;
    if (TOK) *reinterpret_cast<uint32_t*>(otok_row + e) = pack2(o[n][0], o[n][1]);
    else asm volatile("st.shared.u32 [%0],%1;" ::"r"(sb + OFF_SA + g * TP + e * 2), "r"(pack2(o[n][0], o[n][1])) : "memory");
  }
}

__global__ void __launch_bounds__(256, 1)
chain_kernel(const bf16* __restrict__ mem0, const bf16* __restrict__ Wq, const bf16* __restrict__ Wk, const bf16* __restrict__ Wv,
             const bf16* __restrict__ Wo, const bf16* __restrict__ wgate, const bf16* __restrict__ wup, const bf16* __restrict__ wdown) {
  extern __shared__ __align__(1024) uint8_t smem[];
  const int cta = blockIdx.x, t = threadIdx.x, warp = t >> 5, lane = t & 31;
  if (cta >= 128) {
    moe_part(cta - 128, wgate, wup, wdown, smem);
    return;
  }
  const int h = cta >> 2, j = cta & 3;
  const int g = lane >> 2, c = lane & 3;
  const uint32_t sb = smem_u32(smem);
  const int mg = warp & 1, kq = warp >> 1;

  uint32_t wq[RK][3][4];
  uint32_t wo[2][8][4];
  {
    for (int i = t; i < 128 * 4; i += 256)
      asm volatile("prefetch.global.L2 [%0];" ::"l"(Wo + (size_t)(h * 128 + (i >> 2)) * DM + 256 * j + (i & 3) * 64));
    if (t < 192) {
      const int r0 = t / 12, ch = t - 12 * r0;
      const int F = 96 * j + 8 * ch;
      const bf16* src = (F < 128 ? Wq : (F < 256 ? Wk : Wv)) + (size_t)r0 * HD + h * 128 + (F & 127);
      const uint32_t dst = sb + r0 * WSP + ch * 16;
#pragma unroll 8
      for (int i = 0; i < 64; i++) cp_async16(dst + i * 16 * WSP, src + (size_t)i * 16 * HD);
    }
    TS(12);
    cp_commit(); cp_wait<0>();
    __syncthreads();
    TS(13);
    uint32_t tmp[SK][3][4];
#pragma unroll
    for (int ks = 0; ks < 16; ks++) {
#pragma unroll
      for (int tt = 0; tt < 3; tt++) {
        int tile = 3 * mg + tt;
        int k = (16 * kq + ks) * 16 + (lane & 7) + 8 * (lane >> 4);
        uint32_t addr = sb + k * WSP + tile * 32 + 16 * ((lane >> 3) & 1);
        if (ks < RK) ldsm4t(wq[ks][tt][0], wq[ks][tt][1], wq[ks][tt][2], wq[ks][tt][3], addr);
        else ldsm4t(tmp[ks - RK][tt][0], tmp[ks - RK][tt][1], tmp[ks - RK][tt][2], tmp[ks - RK][tt][3], addr);
      }
    }
    __syncthreads();
#pragma unroll
    for (int ks = 0; ks < SK; ks++)
#pragma unroll
      for (int tt = 0; tt < 3; tt++)
        *reinterpret_cast<uint4*>(smem + OFF_WQS + (((warp * SK + ks) * 3 + tt) * 32 + lane) * 16) =
            make_uint4(tmp[ks][tt][0], tmp[ks][tt][1], tmp[ks][tt][2], tmp[ks][tt][3]);
    TS(14);
    {
      const bf16* src = Wo + (size_t)(h * 128 + warp) * DM + 256 * j + lane * 8;
      const uint32_t dst = sb + CH_STG2 + warp * 528 + lane * 16;
#pragma unroll
      for (int i = 0; i < 16; i++) cp_async16(dst + i * 8 * 528, src + (size_t)i * 8 * DM);
    }
    cp_commit(); cp_wait<0>();
    __syncthreads();
#pragma unroll
    for (int tt = 0; tt < 2; tt++)
#pragma unroll
      for (int ks = 0; ks < 8; ks++) {
        int e = 16 * ks + (lane & 7) + 8 * (lane >> 4);
        uint32_t addr = sb + CH_STG2 + e * 528 + (32 * warp + 16 * tt + 8 * ((lane >> 3) & 1)) * 2;
        ldsm4t(wo[tt][ks][0], wo[tt][ks][1], wo[tt][ks][2], wo[tt][ks][3], addr);
      }
    TS(15);
    if (t == 0) {
      mbar_init(sb + OFF_BAR, 1); mbar_init(sb + OFF_BAR + 8, 1);
      asm volatile("fence.mbarrier_init.release.cluster;" ::: "memory");
    }
    __syncthreads();
    asm volatile("fence.proxy.async.shared::cta;" ::: "memory");
  }
  auto prefetch_tok = [&](int s) {
    const int i = t - 192;
    const uint32_t dst = sb + OFF_TOK + (s & 1) * TOK_BYTES + (i >> 4) * TP + (i & 15) * 16;
    const bf16* src = g_qkv + (size_t)(s * 32 + (i >> 4)) * NQKV + HD + h * 128 + (i & 15) * 8;
#pragma unroll
    for (int r = 0; r < 8; r++) {
      cp_async16(dst + 4 * r * TP, src + (size_t)4 * r * NQKV);
      cp_async16(dst + (32 + 4 * r) * TP, src + (size_t)4 * r * NQKV + HD);
    }
    cp_async16(dst + 64 * TP, src + (size_t)(8 * j) * NQKV - HD);
    cp_async16(dst + 68 * TP, src + (size_t)(8 * j + 4) * NQKV - HD);
    cp_commit();
  };
  auto side_work = [&](int s) {
    if (warp >= 6) {
      prefetch_tok(s + 1);
    } else {
      const int slot2 = (s + 2) & 3;
      const int i = t - 128;
      st_pub128(&g_bufA[slot2][cta][i], SENT);
      if (i < 32) st_pub128(&g_bufA[slot2][cta][64 + i], SENT);
      if (i < 8) st_pub128(&g_bufC[slot2][8 * cta + i], SENT);
      uint4* bb = &g_bufB[slot2][32 * j + (i >> 1)][0][0] + 2 * h + (i & 1);
#pragma unroll
      for (int col = 0; col < 8; col++) st_pub128(bb + 64 * col, SENT);
    }
  };
  if (warp >= 6) prefetch_tok(0);
  for (int i = t; i < 1024; i += 256) {
    int r = i >> 7, k = (i & 127) * 8;
    uint4 v = *reinterpret_cast<const uint4*>(mem0 + r * 1024 + k);
    unsigned short* d = reinterpret_cast<unsigned short*>(smem + OFF_MEMT) + k * 8 + r;
    d[0] = (unsigned short)v.x; d[8] = (unsigned short)(v.x >> 16); d[16] = (unsigned short)v.y; d[24] = (unsigned short)(v.y >> 16);
    d[32] = (unsigned short)v.z; d[40] = (unsigned short)(v.z >> 16); d[48] = (unsigned short)v.w; d[56] = (unsigned short)(v.w >> 16);
  }
  __syncthreads();
  const uint32_t p2dst0 = sb + OFF_QKVM + t * 16, p2dst1 = p2dst0 + 4096;
  const int p0idx = 256 * kq + 128 * mg + lane;
  uint32_t tpub = 0;
  const uint32_t dA = DLY_A, dB = DLY_B, dC = DLY_C;
  TS(0);
  for (int s = 0; s < NSEG; s++) {
    const int slot = s & 3;
    if (s > 0) {
      const uint4* src = &g_bufC[(s - 1) & 3][p0idx];
      uint4 v[4];
      wait_until(tpub, dC);
#pragma unroll
      for (int i = 0; i < 4; i++) v[i] = ld_poll(src + 32 * i);
      int it = 0;
      while (!__all_sync(0xffffffffu, pkt_ok(v[0]) && pkt_ok(v[1]) && pkt_ok(v[2]) && pkt_ok(v[3])) && !poll_giveup(it)) {
#pragma unroll
        for (int i = 0; i < 4; i++)
          if (!pkt_ok(v[i])) v[i] = ld_poll(src + 32 * i);
      }
#pragma unroll
      for (int i = 0; i < 4; i++) sts128(sb + OFF_MEMT + (p0idx + 32 * i) * 16, v[i]);
      TS(1);
      asm volatile("bar.sync %0, 64;" ::"r"(1 + kq) : "memory");
      TS(2);
    }
    {
      float acc[2][3][4];
#pragma unroll
      for (int a = 0; a < 2; a++)
#pragma unroll
        for (int tt = 0; tt < 3; tt++)
#pragma unroll
          for (int i = 0; i < 4; i++) acc[a][tt][i] = 0.f;
      uint4 sa[SK][3];
#pragma unroll
      for (int kp = 0; kp < 8; kp++) {
        uint32_t b0, b1, b2, b3;
        ldsm4t(b0, b1, b2, b3, sb + OFF_MEMT + ((16 * kq + 2 * kp) * 16 + lane) * 16);
#pragma unroll
        for (int u = 0; u < 2; u++) {
          int ks = 2 * (kp + 1) + u;
          if (ks >= RK && ks < 16) {
#pragma unroll
            for (int tt = 0; tt < 3; tt++)
              sa[ks - RK][tt] = *reinterpret_cast<const uint4*>(smem + OFF_WQS + (((warp * SK + (ks - RK)) * 3 + tt) * 32 + lane) * 16);
          }
        }
#pragma unroll
        for (int u = 0; u < 2; u++) {
          int ks = 2 * kp + u;
#pragma unroll
          for (int tt = 0; tt < 3; tt++) {
            if (ks < RK) mma16816(acc[u][tt], wq[ks][tt][0], wq[ks][tt][1], wq[ks][tt][2], wq[ks][tt][3], u ? b2 : b0, u ? b3 : b1);
            else mma16816(acc[u][tt], sa[ks - RK][tt].x, sa[ks - RK][tt].y, sa[ks - RK][tt].z, sa[ks - RK][tt].w, u ? b2 : b0, u ? b3 : b1);
          }
        }
      }
#pragma unroll
      for (int tt = 0; tt < 3; tt++)
        *reinterpret_cast<float4*>(smem + OFF_RED + ((kq * 6 + 3 * mg + tt) * 32 + lane) * 16) =
            make_float4(acc[0][tt][0] + acc[1][tt][0], acc[0][tt][1] + acc[1][tt][1], acc[0][tt][2] + acc[1][tt][2], acc[0][tt][3] + acc[1][tt][3]);
    }
    TS(3);
    __syncthreads();
    TS(4);
    if (warp < 6) {
      float4 r = *reinterpret_cast<const float4*>(smem + OFF_RED + ((0 * 6 + warp) * 32 + lane) * 16);
#pragma unroll
      for (int q = 1; q < 4; q++) {
        float4 x = *reinterpret_cast<const float4*>(smem + OFF_RED + ((q * 6 + warp) * 32 + lane) * 16);
        r.x += x.x; r.y += x.y; r.z += x.z; r.w += x.w;
      }
      uint32_t* dst = reinterpret_cast<uint32_t*>(&g_bufA[slot][cta][16 * warp + g]) + c;
      st_pub32(dst, desent(pack2(r.x, r.y)));
      st_pub32(dst + 32, desent(pack2(r.z, r.w)));
    }
    tpub = clk32();
    {
      const uint4* src = &g_bufA[slot][4 * h][t];
      wait_until(tpub, dA);
      uint4 v0 = ld_poll(src);
      uint4 v1 = make_uint4(0, 0, 0, 0);
      if (t < 128) v1 = ld_poll(src + 256);
      int it = 0;
      while (!__all_sync(0xffffffffu, pkt_ok(v0) && pkt_ok(v1)) && !poll_giveup(it)) {
        if (!pkt_ok(v0)) v0 = ld_poll(src);
        if (!pkt_ok(v1)) v1 = ld_poll(src + 256);
      }
      sts128(p2dst0, v0);
      if (t < 128) sts128(p2dst1, v1);
    }
    TS(5);
    if (warp >= 6) cp_wait<0>();
    __syncthreads();
    TS(6);
    const uint32_t tok = sb + OFF_TOK + (s & 1) * TOK_BYTES;
    if (s < NSEG - 1) {
      if (warp < 4) attn8<false>(sb, tok, lane, warp, 0, nullptr);
      else if (VAR == 1 || VAR == 3) side_work(s);
      else if (VAR == 4) attn8<true>(sb, tok, lane, warp - 4, 8 * j + g, g_otok + (size_t)(s * 32 + 8 * j + g) * HD + h * 128);
      TS(7);
      __syncthreads();
      TS(8);
      {
        float acc[2][2][4];
#pragma unroll
        for (int a = 0; a < 2; a++)
#pragma unroll
          for (int tt = 0; tt < 2; tt++)
#pragma unroll
            for (int i = 0; i < 4; i++) acc[a][tt][i] = 0.f;
        uint32_t b[4][4];
#pragma unroll
        for (int kp = 0; kp < 4; kp++) ldsm4(b[kp][0], b[kp][1], b[kp][2], b[kp][3], sb + OFF_SA + (lane & 7) * TP + (32 * kp + 8 * (lane >> 3)) * 2);
#pragma unroll
        for (int kp = 0; kp < 4; kp++) {
#pragma unroll
          for (int tt = 0; tt < 2; tt++) {
            mma16816(acc[0][tt], wo[tt][2 * kp][0], wo[tt][2 * kp][1], wo[tt][2 * kp][2], wo[tt][2 * kp][3], b[kp][0], b[kp][1]);
            mma16816(acc[1][tt], wo[tt][2 * kp + 1][0], wo[tt][2 * kp + 1][1], wo[tt][2 * kp + 1][2], wo[tt][2 * kp + 1][3], b[kp][2], b[kp][3]);
          }
        }
        const int off = (g * 32 + h) * 4 + c;
#pragma unroll
        for (int tt = 0; tt < 2; tt++) {
          int r0 = 32 * j + 4 * warp + 2 * tt;
          uint32_t x0 = __float_as_uint(acc[0][tt][0] + acc[1][tt][0]), x1 = __float_as_uint(acc[0][tt][1] + acc[1][tt][1]);
          uint32_t x2 = __float_as_uint(acc[0][tt][2] + acc[1][tt][2]), x3 = __float_as_uint(acc[0][tt][3] + acc[1][tt][3]);
          x0 = x0 == SENT ? 0x7FFFFFFFu : x0; x1 = x1 == SENT ? 0x7FFFFFFFu : x1;
          x2 = x2 == SENT ? 0x7FFFFFFFu : x2; x3 = x3 == SENT ? 0x7FFFFFFFu : x3;
          st_pub64(reinterpret_cast<uint2*>(&g_bufB[slot][r0][0][0]) + off, x0, x1);
          st_pub64(reinterpret_cast<uint2*>(&g_bufB[slot][r0 + 1][0][0]) + off, x2, x3);
        }
        tpub = clk32();
      }
      if ((VAR == 2 || VAR == 3) && warp >= 4) attn8<true>(sb, tok, lane, warp - 4, 8 * j + g, g_otok + (size_t)(s * 32 + 8 * j + g) * HD + h * 128);
      TS(9);
      {
        const uint4* src = &g_bufB[slot][cta][0][0] + 64 * warp + 2 * lane;
        wait_until(tpub, dB);
        uint4 v0 = ld_poll(src), v1 = ld_poll(src + 1);
        int it = 0;
          while (!__all_sync(0xffffffffu, pkt_ok(v0) && pkt_ok(v1)) && !poll_giveup(it)) {
            if (!pkt_ok(v0)) v0 = ld_poll(src);
          if (!pkt_ok(v1)) v1 = ld_poll(src + 1);
        }
        TS(10);
        const bool hi = lane & 16;
        float a0 = __uint_as_float(hi ? v1.x : v0.x), a1 = __uint_as_float(hi ? v1.y : v0.y);
        float a2 = __uint_as_float(hi ? v1.z : v0.z), a3 = __uint_as_float(hi ? v1.w : v0.w);
        float b0 = __uint_as_float(hi ? v0.x : v1.x), b1 = __uint_as_float(hi ? v0.y : v1.y);
        float b2 = __uint_as_float(hi ? v0.z : v1.z), b3 = __uint_as_float(hi ? v0.w : v1.w);
        a0 += __shfl_xor_sync(0xffffffffu, b0, 16); a1 += __shfl_xor_sync(0xffffffffu, b1, 16);
        a2 += __shfl_xor_sync(0xffffffffu, b2, 16); a3 += __shfl_xor_sync(0xffffffffu, b3, 16);
        const bool h8 = lane & 8;
        float k0 = h8 ? a2 : a0, k1 = h8 ? a3 : a1, s0 = h8 ? a0 : a2, s1 = h8 ? a1 : a3;
        k0 += __shfl_xor_sync(0xffffffffu, s0, 8); k1 += __shfl_xor_sync(0xffffffffu, s1, 8);
        const bool h4 = lane & 4;
        float z = h4 ? k1 : k0, zs = h4 ? k0 : k1;
        z += __shfl_xor_sync(0xffffffffu, zs, 4);
        z += __shfl_xor_sync(0xffffffffu, z, 2);
        z += __shfl_xor_sync(0xffffffffu, z, 1);
        float zo = __shfl_xor_sync(0xffffffffu, z, 4);
        if ((lane & 7) == 0) {
          uint32_t* d = reinterpret_cast<uint32_t*>(&g_bufC[slot][8 * cta + warp]) + (lane >> 3);
          st_pub32(d, desent(pack2(z, zo)));
        }
        tpub = clk32();
      }
    }
    if (warp >= 4) {
      if ((s == NSEG - 1 || VAR == 1) && !NOTOK) attn8<true>(sb, tok, lane, warp - 4, 8 * j + g, g_otok + (size_t)(s * 32 + 8 * j + g) * HD + h * 128);
      if (s < NSEG - 1 && (VAR == 2 || VAR == 4)) side_work(s);
    }
    TS(11);
  }
}

__device__ void moe_part(int m, const bf16* __restrict__ wg, const bf16* __restrict__ wu, const bf16* __restrict__ wd, uint8_t* smem) {
  const int t = threadIdx.x, warp = t >> 5, lane = t & 31;
  float* xs = reinterpret_cast<float*>(smem);
  float* red = reinterpret_cast<float*>(smem + 8192);
  float* hs = reinterpret_cast<float*>(smem + 65536);
  __shared__ float bv[8];
  __shared__ int bi[8];
  __shared__ int sel[2];
  int first = -1;
  for (int pass = 0; pass < 2; pass++) {
    float best = -INFINITY; int bidx = 0x7fffffff;
    for (int i = t; i < S_LEN; i += 256) {
      float v = g_r[i];
      if (i == first) continue;
      if (v > best || (v == best && i < bidx) || bidx == 0x7fffffff) { best = v; bidx = i; }
    }
#pragma unroll
    for (int o = 16; o > 0; o >>= 1) {
      float ov = __shfl_xor_sync(0xffffffffu, best, o); int oi = __shfl_xor_sync(0xffffffffu, bidx, o);
      if (oi != 0x7fffffff && (bidx == 0x7fffffff || ov > best || (ov == best && oi < bidx))) { best = ov; bidx = oi; }
    }
    if (lane == 0) { bv[warp] = best; bi[warp] = bidx; }
    __syncthreads();
    if (t == 0) {
      float b = bv[0]; int ix = bi[0];
      for (int w = 1; w < 8; w++) if (bv[w] > b || (bv[w] == b && bi[w] < ix)) { b = bv[w]; ix = bi[w]; }
      sel[pass] = ix;
    }
    __syncthreads();
    first = sel[0];
  }
  const int s0 = sel[0], s1 = sel[1];
  for (int i = t; i < 2048; i += 256) xs[i] = __bfloat162float(g_xn[(size_t)(i < 1024 ? s0 : s1) * DM + (i & 1023)]);
  __syncthreads();
  {
    int cg = t % 112, kh = t / 112;
    float a[2][2][8];
#pragma unroll
    for (int i = 0; i < 8; i++) { a[0][0][i] = a[0][1][i] = a[1][0][i] = a[1][1][i] = 0.f; }
    if (kh < 2) {
      const bf16* pg = wg + (size_t)(kh * 512) * FF + 896 * m + cg * 8;
      const bf16* pu = wu + (size_t)(kh * 512) * FF + 896 * m + cg * 8;
#pragma unroll 8
      for (int k = 0; k < 512; k++) {
        uint4 gv = __ldg(reinterpret_cast<const uint4*>(pg + (size_t)k * FF));
        uint4 uv = __ldg(reinterpret_cast<const uint4*>(pu + (size_t)k * FF));
        float x0 = xs[kh * 512 + k], x1 = xs[1024 + kh * 512 + k];
        float gf[8] = {bflo(gv.x), bfhi(gv.x), bflo(gv.y), bfhi(gv.y), bflo(gv.z), bfhi(gv.z), bflo(gv.w), bfhi(gv.w)};
        float uf[8] = {bflo(uv.x), bfhi(uv.x), bflo(uv.y), bfhi(uv.y), bflo(uv.z), bfhi(uv.z), bflo(uv.w), bfhi(uv.w)};
#pragma unroll
        for (int i = 0; i < 8; i++) {
          a[0][0][i] += x0 * gf[i]; a[0][1][i] += x1 * gf[i];
          a[1][0][i] += x0 * uf[i]; a[1][1][i] += x1 * uf[i];
        }
      }
      if (kh == 1) {
#pragma unroll
        for (int i = 0; i < 8; i++) {
          red[(0 * 2 + 0) * 896 + cg * 8 + i] = a[0][0][i]; red[(0 * 2 + 1) * 896 + cg * 8 + i] = a[0][1][i];
          red[(1 * 2 + 0) * 896 + cg * 8 + i] = a[1][0][i]; red[(1 * 2 + 1) * 896 + cg * 8 + i] = a[1][1][i];
        }
      }
    }
    __syncthreads();
    if (kh == 0) {
#pragma unroll
      for (int i = 0; i < 8; i++) {
#pragma unroll
        for (int tk = 0; tk < 2; tk++) {
          float gq = bfr(a[0][tk][i] + red[(0 * 2 + tk) * 896 + cg * 8 + i]);
          float uq = bfr(a[1][tk][i] + red[(1 * 2 + tk) * 896 + cg * 8 + i]);
          float sg = bfr(gq / (1.0f + __expf(-gq)));
          g_h[tk][896 * m + cg * 8 + i] = __float2bfloat16_rn(sg * uq);
        }
      }
    }
    __threadfence();
    __syncthreads();
    if (t == 0) {
      atomicAdd(&g_moe_cnt, 1u);
      int it = 0;
      while (*reinterpret_cast<volatile unsigned*>(&g_moe_cnt) < 4u && ++it < (1 << 24)) {}
      __threadfence();
    }
    __syncthreads();
  }
  for (int i = t; i < 2 * FF; i += 256) {
    const volatile unsigned short* p = reinterpret_cast<const volatile unsigned short*>(&g_h[0][0]);
    hs[i] = __uint_as_float(((uint32_t)p[i]) << 16);
  }
  __syncthreads();
  {
    int cg = t & 31, ksl = t >> 5;
    float a[2][8];
#pragma unroll
    for (int i = 0; i < 8; i++) a[0][i] = a[1][i] = 0.f;
    const bf16* pd = wd + (size_t)(ksl * 448) * DM + 256 * m + cg * 8;
#pragma unroll 8
    for (int k = 0; k < 448; k++) {
      uint4 dv = __ldg(reinterpret_cast<const uint4*>(pd + (size_t)k * DM));
      float x0 = hs[ksl * 448 + k], x1 = hs[FF + ksl * 448 + k];
      float df[8] = {bflo(dv.x), bfhi(dv.x), bflo(dv.y), bfhi(dv.y), bflo(dv.z), bfhi(dv.z), bflo(dv.w), bfhi(dv.w)};
#pragma unroll
      for (int i = 0; i < 8; i++) { a[0][i] += x0 * df[i]; a[1][i] += x1 * df[i]; }
    }
#pragma unroll
    for (int i = 0; i < 8; i++) { red[(ksl * 2 + 0) * 256 + cg * 8 + i] = a[0][i]; red[(ksl * 2 + 1) * 256 + cg * 8 + i] = a[1][i]; }
    __syncthreads();
    for (int i = t; i < 512; i += 256) {
      int tk = i >> 8, col = i & 255;
      float y = 0.f;
#pragma unroll
      for (int q = 0; q < 8; q++) y += red[(q * 2 + tk) * 256 + col];
      float rr = g_r[tk == 0 ? s0 : s1];
      float sg = bfr(1.0f / (1.0f + __expf(-rr)));
      g_upd[tk][256 * m + col] = bfr(bfr(y) * sg);
    }
    if (m == 0 && t == 0) { g_sel[0] = s0; g_sel[1] = s1; }
  }
}

typedef CUresult (*EncodeFn)(CUtensorMap*, CUtensorMapDataType, cuuint32_t, void*, const cuuint64_t*, const cuuint64_t*,
                             const cuuint32_t*, const cuuint32_t*, CUtensorMapInterleave, CUtensorMapSwizzle,
                             CUtensorMapL2promotion, CUtensorMapFloatOOBfill);

static void make_map(EncodeFn enc, CUtensorMap* m, const void* ptr, uint64_t inner, uint64_t outer, uint32_t bi, uint32_t bo) {
  cuuint64_t dims[2] = {inner, outer};
  cuuint64_t strides[1] = {inner * 2};
  cuuint32_t box[2] = {bi, bo};
  cuuint32_t es[2] = {1, 1};
  enc(m, CU_TENSOR_MAP_DATA_TYPE_BFLOAT16, 2, const_cast<void*>(ptr), dims, strides, box, es, CU_TENSOR_MAP_INTERLEAVE_NONE,
      CU_TENSOR_MAP_SWIZZLE_128B, CU_TENSOR_MAP_L2_PROMOTION_L2_256B, CU_TENSOR_MAP_FLOAT_OOB_FILL_NONE);
}

extern "C" void kernel_launch(void* const* d_in, const int* in_sizes, int n_in, void* d_out, int out_size) {
  const bf16* x = (const bf16*)d_in[0];
  const bf16* mem0 = (const bf16*)d_in[1];
  const bf16* Wq = (const bf16*)d_in[2];
  const bf16* Wk = (const bf16*)d_in[3];
  const bf16* Wv = (const bf16*)d_in[4];
  const bf16* Wo = (const bf16*)d_in[5];
  const bf16* w_r = (const bf16*)d_in[8];
  const bf16* wg = (const bf16*)d_in[9];
  const bf16* wu = (const bf16*)d_in[10];
  const bf16* wd = (const bf16*)d_in[11];
  bf16* out = (bf16*)d_out;

  static EncodeFn enc = nullptr;
  static void *p_xn, *p_qkv, *p_otok;
  if (!enc) {
    cudaDriverEntryPointQueryResult qr;
    void* fn = nullptr;
    cudaGetDriverEntryPoint("cuTensorMapEncodeTiled", &fn, cudaEnableDefault, &qr);
    enc = (EncodeFn)fn;
    cudaGetSymbolAddress(&p_xn, g_xn);
    cudaGetSymbolAddress(&p_qkv, g_qkv);
    cudaGetSymbolAddress(&p_otok, g_otok);
    cudaFuncSetAttribute(gemm_kernel<256, 4, 0>, cudaFuncAttributeMaxDynamicSharedMemorySize, GemmSmem<256, 4>::TOTAL);
    cudaFuncSetAttribute(gemm_kernel<128, 6, 1>, cudaFuncAttributeMaxDynamicSharedMemorySize, GemmSmem<128, 6>::TOTAL);
    cudaFuncSetAttribute(chain_kernel, cudaFuncAttributeMaxDynamicSharedMemorySize, CH_SMEM);
  }
  CUtensorMap mA, mQ, mK, mV, mO, mWo;
  make_map(enc, &mA, p_xn, DM, S_LEN, 64, 128);
  make_map(enc, &mQ, Wq, HD, DM, 64, 64);
  make_map(enc, &mK, Wk, HD, DM, 64, 64);
  make_map(enc, &mV, Wv, HD, DM, 64, 64);
  make_map(enc, &mO, p_otok, HD, S_LEN, 64, 128);
  make_map(enc, &mWo, Wo, DM, HD, 64, 64);

  cudaStream_t st = cudaStreamPerThread;
  ln_kernel<<<256, 256, 0, st>>>(x, w_r);
  cudaLaunchAttribute cat[1];
  cat[0].id = cudaLaunchAttributeClusterDimension;
  cat[0].val.clusterDim.x = 2; cat[0].val.clusterDim.y = 1; cat[0].val.clusterDim.z = 1;
  cudaLaunchConfig_t cfg = {};
  cfg.gridDim = dim3(132); cfg.blockDim = dim3(288); cfg.dynamicSmemBytes = GemmSmem<256, 4>::TOTAL; cfg.stream = st;
  cfg.attrs = cat; cfg.numAttrs = 1;
  cudaLaunchKernelEx(&cfg, gemm_kernel<256, 4, 0>, mA, mQ, mK, mV, 16, 16, 16 * 48, (const bf16*)nullptr, (bf16*)p_qkv, Wq, Wk, Wv, Wo);
  chain_kernel<<<132, 256, CH_SMEM, st>>>(mem0, Wq, Wk, Wv, Wo, wg, wu, wd);
  cfg.gridDim = dim3(128); cfg.dynamicSmemBytes = GemmSmem<128, 6>::TOTAL;
  cudaLaunchKernelEx(&cfg, gemm_kernel<128, 6, 1>, mO, mWo, mWo, mWo, 64, 16, 16 * 8, x, out, Wq, Wk, Wv, Wo);
}
```
